```python
import torch

def _softmax(x, axis=-1):
    return torch.softmax(x, dim=axis)
def _gelu(x):
    return torch.nn.functional.gelu(x, approximate="tanh")
def _silu(x):
    return torch.nn.functional.silu(x)
def _sigmoid(x):
    return torch.sigmoid(x)
def _layernorm(x, axis=-1, eps=1e-5):
    m = x.mean(dim=axis, keepdim=True)
    v = x.var(dim=axis, keepdim=True, unbiased=False)
    return (x - m) / torch.sqrt(v + eps)
def _scatter_add(tgt, idx, src, axis=0):
    return tgt.clone().index_add_(axis, idx, src)
def _segment_sum(src, seg, n):
    out = torch.zeros((n,) + src.shape[1:], dtype=src.dtype)
    return out.index_add_(0, seg, src)
def _pad(x, pw):
    flat = tuple(v for pair in reversed(pw) for v in pair)
    return torch.nn.functional.pad(x, flat)

kernel_name = 'sequential_preLN__linear_attn_block__glu_gated_glu__prompt'

def setup_inputs():

    _w = (lambda a: (lambda t: t.to(torch.bfloat16) if t.is_floating_point() else t)(torch.as_tensor(a)))
    def _A_setup():
        B, S, D = 1, 2048, 448
        return {
            "x": _w((lambda *s: torch.randn(*s, dtype=torch.bfloat16) * 0.05)(B, S, D)),
            "wqkv": _w((lambda *s: torch.randn(*s, dtype=torch.bfloat16) * 0.1)(D, 3 * D)),
            "wo": _w((lambda *s: torch.randn(*s, dtype=torch.bfloat16) * 0.05)(D, D)),
        }
    _A_in = _A_setup()

    def _B_setup():
        B, S, D, F = 1, 2048, 448, 1792
        return {
            "x": _w((lambda *s: torch.randn(*s, dtype=torch.bfloat16) * 0.05)(B, S, D)),
            "w_gate": _w((lambda *s: torch.randn(*s, dtype=torch.bfloat16) * 0.05)(D, F)),
            "w_up": _w((lambda *s: torch.randn(*s, dtype=torch.bfloat16) * 0.05)(D, F)),
            "w_down": _w((lambda *s: torch.randn(*s, dtype=torch.bfloat16) * 0.05)(F, D)),
        }
    _B_in = _B_setup()

    return {
        "A_x": _A_in["x"],
        "A_wqkv": _A_in["wqkv"],
        "A_wo": _A_in["wo"],
        "B_x": _B_in["x"],
        "B_w_gate": _B_in["w_gate"],
        "B_w_up": _B_in["w_up"],
        "B_w_down": _B_in["w_down"],
    }

def reference(A_x, A_wqkv, A_wo, B_x, B_w_gate, B_w_up, B_w_down):
    def _A_ref(x, wqkv, wo):
        B, S, D = x.shape
        H = 16; Dh = D // H
        qkv = (lambda x, *d: x.permute(*d))((x @ wqkv).reshape(B, S, 3, H, Dh), 2, 0, 3, 1, 4)
        q, k, v = qkv[0], qkv[1], qkv[2]
        phi = lambda t: torch.where(t > 0, t + 1, torch.exp(t)) + 1e-6
        pq, pk = phi(q), phi(k)
        kv = torch.einsum("bhsd,bhse->bhde", pk, v)
        z = torch.einsum("bhsd->bhd", pk)
        num = torch.einsum("bhqd,bhde->bhqe", pq, kv)
        den = torch.einsum("bhqd,bhd->bhq", pq, z)[..., None] + 1e-6
        o = num / den
        return (lambda x, *d: x.permute(*d))(o, 0, 2, 1, 3).reshape(B, S, D) @ wo

    def _B_ref(x, w_gate, w_up, w_down):
        g = torch.einsum("bsd,df->bsf", x, w_gate)
        u = torch.einsum("bsd,df->bsf", x, w_up)
        h = _sigmoid(g) * u
        return torch.einsum("bsf,fd->bsd", h, w_down)

    x = A_x
    h = x + _A_ref(_layernorm(x, axis=-1), A_wqkv, A_wo)
    h2 = h + _B_ref(_layernorm(h, axis=-1), B_w_gate, B_w_up, B_w_down)
    return h2
```

```cpp
#include <cuda_runtime.h>
#include <cuda_bf16.h>
#include <cuda.h>
#include <stdint.h>
#include <stdio.h>

#define SPIN_LIMIT (1 << 17)

namespace {

constexpr uint32_t sb = 1024;
constexpr int SEQ = 2048, DM = 448, FF = 1792;
constexpr int TILE = 14336;
constexpr int STG = 2 * TILE;
constexpr int SMEM_BAR = 8 * STG;
constexpr int SMEM_TOTAL = SMEM_BAR + 2048;
constexpr int OFF_GATH = 4 * STG, OFF_Q = 4 * STG, OFF_WO = 2 * STG;
constexpr int OFF_PK = 6 * STG, OFF_PV = OFF_PK + 16384, OFF_KVB = OFF_PK + 32768;
constexpr int B_FULL = 0, B_EMPTY = 8, B_KV = 16, B_Q = 20, B_WO = 21, B_GO = 22  , B_WB = 24  ,
              B_XFREE = 32, B_KFREE = 33, B_OFREE = 34, B_WOFREE = 35, B_HFREE = 36  , B_KVB = 40,
              B_ODONE = 41  , B_XB = 43  ;

constexpr int KVP_B = 8 * 16 * 8192;
constexpr int KVR_B = 8 * 8192;
constexpr int STAT_B = 16 * 128 * 64;
constexpr int FRAG_B = 16 * 4 * STG;
constexpr int PART_B = 128 * STG;
constexpr int A_KVP = 0, A_KVR = A_KVP + KVP_B, A_STAT = A_KVR + KVR_B, A_O = A_STAT + STAT_B, A_H = A_O + FRAG_B,
              A_PART = A_H + FRAG_B, A_TOTAL = A_PART + PART_B;
constexpr int HH_B = 128 * 2 * STG;

__device__ uint4 g_bufA[A_TOTAL / 16];
__device__ uint4 g_bufB[HH_B / 16];
__device__ unsigned g_epoch[128 * 32];
constexpr int C_KVP = 0, C_KVR = 8, C_ROW = 256, C_CTA = 768;
__device__ unsigned g_cnt[C_CTA + 128 * 8];
#define ENC_CHECK(x) (void)(x)
#define STAMP(i)
#define STAMPP(i)
#define DUMP(row)

__device__ __forceinline__ uint32_t smem_u32(const void* p) { return (uint32_t)__cvta_generic_to_shared(p); }
__device__ __forceinline__ void mbar_init(uint32_t bar, uint32_t cnt) {
  asm volatile("mbarrier.init.shared::cta.b64 [%0], %1;" ::"r"(bar), "r"(cnt) : "memory");
}
__device__ __forceinline__ void mbar_expect_tx(uint32_t bar, uint32_t bytes) {
  asm volatile("mbarrier.arrive.expect_tx.shared::cta.b64 _, [%0], %1;" ::"r"(bar), "r"(bytes) : "memory");
}
__device__ __forceinline__ void mbar_arrive(uint32_t bar) {
  asm volatile("mbarrier.arrive.shared::cta.b64 _, [%0];" ::"r"(bar) : "memory");
}
__device__ __forceinline__ void mbar_wait(uint32_t bar, uint32_t parity) {
  uint32_t ok;
  int it = 0;
  do {
    asm volatile("{\n.reg .pred p;\nmbarrier.try_wait.parity.shared::cta.b64 p, [%1], %2;\nselp.u32 %0, 1, 0, p;\n}"
                 : "=r"(ok) : "r"(bar), "r"(parity) : "memory");
    if (++it > SPIN_LIMIT) break;
  } while (!ok);
}
__device__ __forceinline__ void tma2d(uint32_t dst, const CUtensorMap* m, int c0, int c1, uint32_t bar) {
  asm volatile("cp.async.bulk.tensor.2d.shared::cluster.global.mbarrier::complete_tx::bytes [%0], [%1, {%3, %4}], [%2];"
               ::"r"(dst), "l"(m), "r"(bar), "r"(c0), "r"(c1) : "memory");
}
__device__ __forceinline__ void tma3d(uint32_t dst, const CUtensorMap* m, int c0, int c1, int c2, uint32_t bar) {
  asm volatile("cp.async.bulk.tensor.3d.shared::cluster.global.mbarrier::complete_tx::bytes [%0], [%1, {%3, %4, %5}], [%2];"
               ::"r"(dst), "l"(m), "r"(bar), "r"(c0), "r"(c1), "r"(c2) : "memory");
}
__device__ __forceinline__ void tma4d(uint32_t dst, const CUtensorMap* m, int c0, int c1, int c2, int c3, uint32_t bar) {
  asm volatile("cp.async.bulk.tensor.4d.shared::cluster.global.mbarrier::complete_tx::bytes [%0], [%1, {%3, %4, %5, %6}], [%2];"
               ::"r"(dst), "l"(m), "r"(bar), "r"(c0), "r"(c1), "r"(c2), "r"(c3) : "memory");
}
__device__ __forceinline__ void bulk_g2s(uint32_t dst, const void* src, uint32_t bytes, uint32_t bar) {
  asm volatile("cp.async.bulk.shared::cluster.global.mbarrier::complete_tx::bytes [%0], [%1], %2, [%3];"
               ::"r"(dst), "l"(src), "r"(bytes), "r"(bar) : "memory");
}
__device__ __forceinline__ void tma_store2d(const CUtensorMap* m, uint32_t src, int c0, int c1) {
  asm volatile("cp.async.bulk.tensor.2d.global.shared::cta.bulk_group [%0, {%2, %3}], [%1];"
               ::"l"(m), "r"(src), "r"(c0), "r"(c1) : "memory");
}
__device__ __forceinline__ void l2_prefetch(const void* p, uint32_t bytes) {
  asm volatile("cp.async.bulk.prefetch.L2.global [%0], %1;" ::"l"(p), "r"(bytes) : "memory");
}
__device__ __forceinline__ void prefetch_map(const CUtensorMap* m) {
  asm volatile("prefetch.tensormap [%0];" ::"l"(m) : "memory");
}
__device__ __forceinline__ void fence_async_smem() { asm volatile("fence.proxy.async.shared::cta;" ::: "memory"); }
template <int ID, int N> __device__ __forceinline__ void bar_sync() { asm volatile("bar.sync %0, %1;" ::"n"(ID), "n"(N) : "memory"); }
__device__ __forceinline__ void wg_fence() { asm volatile("wgmma.fence.sync.aligned;" ::: "memory"); }
__device__ __forceinline__ void wg_commit() { asm volatile("wgmma.commit_group.sync.aligned;" ::: "memory"); }
template <int N> __device__ __forceinline__ void wg_wait() { asm volatile("wgmma.wait_group.sync.aligned %0;" ::"n"(N) : "memory"); }
template <int N> __device__ __forceinline__ void acc_fence(float (&d)[N]) {
#pragma unroll
  for (int i = 0; i < N; i++) asm volatile("" : "+f"(d[i])::"memory");
}
__device__ __forceinline__ constexpr uint64_t mn_desc(uint32_t addr) {
  return (uint64_t)((addr & 0x3FFFF) >> 4) | ((uint64_t)(TILE >> 4) << 16) | ((uint64_t)64 << 32) | ((uint64_t)1 << 62);
}
__device__ __forceinline__ constexpr uint64_t mn_desc64(uint32_t addr) {
  return (uint64_t)((addr & 0x3FFFF) >> 4) | ((uint64_t)(TILE >> 4) << 16) | ((uint64_t)32 << 32) | ((uint64_t)2 << 62);
}
__device__ __forceinline__ uint4 ld_rlx4(const void* p) {
  uint4 v;
  asm volatile("ld.relaxed.gpu.global.v4.u32 {%0,%1,%2,%3}, [%4];" : "=r"(v.x), "=r"(v.y), "=r"(v.z), "=r"(v.w) : "l"(p) : "memory");
  return v;
}
__device__ __forceinline__ uint2 ld_rlx2(const void* p) {
  uint2 v;
  asm volatile("ld.relaxed.gpu.global.v2.u32 {%0,%1}, [%2];" : "=r"(v.x), "=r"(v.y) : "l"(p) : "memory");
  return v;
}
__device__ __forceinline__ uint32_t ld_rlx1(const void* p) {
  uint32_t v;
  asm volatile("ld.relaxed.gpu.global.u32 %0, [%1];" : "=r"(v) : "l"(p) : "memory");
  return v;
}
__device__ __forceinline__ void st_rlx4(void* p, uint32_t a, uint32_t b, uint32_t c, uint32_t d) {
  asm volatile("st.relaxed.gpu.global.v4.u32 [%0], {%1,%2,%3,%4};" ::"l"(p), "r"(a), "r"(b), "r"(c), "r"(d) : "memory");
}
__device__ __forceinline__ void st_rlx2(void* p, uint32_t a, uint32_t b) {
  asm volatile("st.relaxed.gpu.global.v2.u32 [%0], {%1,%2};" ::"l"(p), "r"(a), "r"(b) : "memory");
}
__device__ __forceinline__ void st_rlx1(void* p, uint32_t a) {
  asm volatile("st.relaxed.gpu.global.u32 [%0], %1;" ::"l"(p), "r"(a) : "memory");
}
__device__ __forceinline__ void red_inc(unsigned* p) {
  asm volatile("red.relaxed.gpu.global.add.u32 [%0], 1;" ::"l"(p) : "memory");
}
__device__ __forceinline__ void cnt_wait(const unsigned* p, uint32_t target) {
  int it = 0;
  while ((int)(ld_rlx1(p) - target) < 0)
    if (++it > SPIN_LIMIT) break;
}
__device__ __forceinline__ uint32_t tag(uint32_t w, uint32_t par) { return (w & ~1u) | par; }
__device__ __forceinline__ uint32_t tagf(float f, uint32_t par) { return tag(__float_as_uint(f), par); }
__device__ __forceinline__ void sts1(uint32_t a, uint32_t v) { asm volatile("st.shared.u32 [%0], %1;" ::"r"(a), "r"(v) : "memory"); }
__device__ __forceinline__ void sts4(uint32_t a, uint32_t x, uint32_t y, uint32_t z, uint32_t w) {
  asm volatile("st.shared.v4.u32 [%0], {%1,%2,%3,%4};" ::"r"(a), "r"(x), "r"(y), "r"(z), "r"(w) : "memory");
}
__device__ __forceinline__ uint32_t lds1(uint32_t a) {
  uint32_t v;
  asm volatile("ld.shared.u32 %0, [%1];" : "=r"(v) : "r"(a) : "memory");
  return v;
}
__device__ __forceinline__ uint2 lds2(uint32_t a) {
  uint2 v;
  asm volatile("ld.shared.v2.u32 {%0,%1}, [%2];" : "=r"(v.x), "=r"(v.y) : "r"(a) : "memory");
  return v;
}
__device__ __forceinline__ uint4 lds4(uint32_t a) {
  uint4 v;
  asm volatile("ld.shared.v4.u32 {%0,%1,%2,%3}, [%4];" : "=r"(v.x), "=r"(v.y), "=r"(v.z), "=r"(v.w) : "r"(a) : "memory");
  return v;
}
__device__ __forceinline__ uint4 ldsm4(uint32_t a) {
  uint4 v;
  asm volatile("ldmatrix.sync.aligned.m8n8.x4.shared.b16 {%0,%1,%2,%3}, [%4];" : "=r"(v.x), "=r"(v.y), "=r"(v.z), "=r"(v.w) : "r"(a) : "memory");
  return v;
}
__device__ __forceinline__ uint32_t pack2(float lo, float hi) {
  uint32_t r;
  asm("cvt.rn.bf16x2.f32 %0, %1, %2;" : "=r"(r) : "f"(hi), "f"(lo));
  return r;
}
__device__ __forceinline__ float bf_lo(uint32_t w) { return __uint_as_float(w << 16); }
__device__ __forceinline__ float bf_hi(uint32_t w) { return __uint_as_float(w & 0xFFFF0000u); }
__device__ __forceinline__ uint32_t sub2(uint32_t a, uint32_t b) {
  uint32_t r;
  asm("sub.rn.bf16x2 %0, %1, %2;" : "=r"(r) : "r"(a), "r"(b));
  return r;
}
__device__ __forceinline__ void mma16816(float (&c)[4], uint32_t a0, uint32_t a1, uint32_t a2, uint32_t a3, uint32_t b0, uint32_t b1) {
  asm("mma.sync.aligned.m16n8k16.row.col.f32.bf16.bf16.f32 {%0,%1,%2,%3}, {%4,%5,%6,%7}, {%8,%9}, {%0,%1,%2,%3};"
      : "+f"(c[0]), "+f"(c[1]), "+f"(c[2]), "+f"(c[3]) : "r"(a0), "r"(a1), "r"(a2), "r"(a3), "r"(b0), "r"(b1));
}
__device__ __forceinline__ float ex2f(float x) { float r; asm("ex2.approx.ftz.f32 %0, %1;" : "=f"(r) : "f"(x)); return r; }
__device__ __forceinline__ float tanhf_(float x) { float r; asm("tanh.approx.f32 %0, %1;" : "=f"(r) : "f"(x)); return r; }
__device__ __forceinline__ float rcpf(float x) { float r; asm("rcp.approx.ftz.f32 %0, %1;" : "=f"(r) : "f"(x)); return r; }
__device__ __forceinline__ float phi(float t) { return (t > 0.f ? t + 1.f : ex2f(t * 1.4426950408889634f)) + 1e-6f; }

__device__ __forceinline__ void wgmma_rs_n56(float (&d)[28], uint32_t a0, uint32_t a1, uint32_t a2, uint32_t a3, uint64_t bdesc, int scale_d) {
  asm volatile("{\n.reg .pred p;\nsetp.ne.b32 p, %33, 0;\n"
    "wgmma.mma_async.sync.aligned.m64n56k16.f32.bf16.bf16 {%0, %1, %2, %3, %4, %5, %6, %7, %8, %9, %10, %11, %12, %13, %14, %15, %16, %17, %18, %19, %20, %21, %22, %23, %24, %25, %26, %27}, {%28, %29, %30, %31}, %32, p, 1, 1, 1;\n}\n"
    : "+f"(d[0]), "+f"(d[1]), "+f"(d[2]), "+f"(d[3]), "+f"(d[4]), "+f"(d[5]), "+f"(d[6]), "+f"(d[7]), "+f"(d[8]), "+f"(d[9]), "+f"(d[10]), "+f"(d[11]), "+f"(d[12]), "+f"(d[13]), "+f"(d[14]), "+f"(d[15]), "+f"(d[16]), "+f"(d[17]), "+f"(d[18]), "+f"(d[19]), "+f"(d[20]), "+f"(d[21]), "+f"(d[22]), "+f"(d[23]), "+f"(d[24]), "+f"(d[25]), "+f"(d[26]), "+f"(d[27]) : "r"(a0), "r"(a1), "r"(a2), "r"(a3), "l"(bdesc), "r"(scale_d));
}
__device__ __forceinline__ void wgmma_rs_n64(float (&d)[32], uint32_t a0, uint32_t a1, uint32_t a2, uint32_t a3, uint64_t bdesc, int scale_d) {
  asm volatile("{\n.reg .pred p;\nsetp.ne.b32 p, %37, 0;\n"
    "wgmma.mma_async.sync.aligned.m64n64k16.f32.bf16.bf16 {%0, %1, %2, %3, %4, %5, %6, %7, %8, %9, %10, %11, %12, %13, %14, %15, %16, %17, %18, %19, %20, %21, %22, %23, %24, %25, %26, %27, %28, %29, %30, %31}, {%32, %33, %34, %35}, %36, p, 1, 1, 1;\n}\n"
    : "+f"(d[0]), "+f"(d[1]), "+f"(d[2]), "+f"(d[3]), "+f"(d[4]), "+f"(d[5]), "+f"(d[6]), "+f"(d[7]), "+f"(d[8]), "+f"(d[9]), "+f"(d[10]), "+f"(d[11]), "+f"(d[12]), "+f"(d[13]), "+f"(d[14]), "+f"(d[15]), "+f"(d[16]), "+f"(d[17]), "+f"(d[18]), "+f"(d[19]), "+f"(d[20]), "+f"(d[21]), "+f"(d[22]), "+f"(d[23]), "+f"(d[24]), "+f"(d[25]), "+f"(d[26]), "+f"(d[27]), "+f"(d[28]), "+f"(d[29]), "+f"(d[30]), "+f"(d[31]) : "r"(a0), "r"(a1), "r"(a2), "r"(a3), "l"(bdesc), "r"(scale_d));
}
__device__ __forceinline__ void wgmma_rs_n128(float (&d)[64], uint32_t a0, uint32_t a1, uint32_t a2, uint32_t a3, uint64_t bdesc, int scale_d) {
  asm volatile("{\n.reg .pred p;\nsetp.ne.b32 p, %69, 0;\n"
    "wgmma.mma_async.sync.aligned.m64n128k16.f32.bf16.bf16 {%0, %1, %2, %3, %4, %5, %6, %7, %8, %9, %10, %11, %12, %13, %14, %15, %16, %17, %18, %19, %20, %21, %22, %23, %24, %25, %26, %27, %28, %29, %30, %31, %32, %33, %34, %35, %36, %37, %38, %39, %40, %41, %42, %43, %44, %45, %46, %47, %48, %49, %50, %51, %52, %53, %54, %55, %56, %57, %58, %59, %60, %61, %62, %63}, {%64, %65, %66, %67}, %68, p, 1, 1, 1;\n}\n"
    : "+f"(d[0]), "+f"(d[1]), "+f"(d[2]), "+f"(d[3]), "+f"(d[4]), "+f"(d[5]), "+f"(d[6]), "+f"(d[7]), "+f"(d[8]), "+f"(d[9]), "+f"(d[10]), "+f"(d[11]), "+f"(d[12]), "+f"(d[13]), "+f"(d[14]), "+f"(d[15]), "+f"(d[16]), "+f"(d[17]), "+f"(d[18]), "+f"(d[19]), "+f"(d[20]), "+f"(d[21]), "+f"(d[22]), "+f"(d[23]), "+f"(d[24]), "+f"(d[25]), "+f"(d[26]), "+f"(d[27]), "+f"(d[28]), "+f"(d[29]), "+f"(d[30]), "+f"(d[31]), "+f"(d[32]), "+f"(d[33]), "+f"(d[34]), "+f"(d[35]), "+f"(d[36]), "+f"(d[37]), "+f"(d[38]), "+f"(d[39]), "+f"(d[40]), "+f"(d[41]), "+f"(d[42]), "+f"(d[43]), "+f"(d[44]), "+f"(d[45]), "+f"(d[46]), "+f"(d[47]), "+f"(d[48]), "+f"(d[49]), "+f"(d[50]), "+f"(d[51]), "+f"(d[52]), "+f"(d[53]), "+f"(d[54]), "+f"(d[55]), "+f"(d[56]), "+f"(d[57]), "+f"(d[58]), "+f"(d[59]), "+f"(d[60]), "+f"(d[61]), "+f"(d[62]), "+f"(d[63]) : "r"(a0), "r"(a1), "r"(a2), "r"(a3), "l"(bdesc), "r"(scale_d));
}
__device__ __forceinline__ void wgmma_ss_n32_ta(float (&d)[16], uint64_t adesc, uint64_t bdesc, int scale_d) {
  asm volatile("{\n.reg .pred p;\nsetp.ne.b32 p, %18, 0;\n"
    "wgmma.mma_async.sync.aligned.m64n32k16.f32.bf16.bf16 {%0, %1, %2, %3, %4, %5, %6, %7, %8, %9, %10, %11, %12, %13, %14, %15}, %16, %17, p, 1, 1, 1, 1;\n}\n"
    : "+f"(d[0]), "+f"(d[1]), "+f"(d[2]), "+f"(d[3]), "+f"(d[4]), "+f"(d[5]), "+f"(d[6]), "+f"(d[7]), "+f"(d[8]), "+f"(d[9]), "+f"(d[10]), "+f"(d[11]), "+f"(d[12]), "+f"(d[13]), "+f"(d[14]), "+f"(d[15]) : "l"(adesc), "l"(bdesc), "r"(scale_d));
}

__device__ __forceinline__ void publish7(char* blk, int p, int lane, const uint32_t (&P)[14], uint32_t par) {
  char* b = blk + (p >> 1) * STG + 1792 * (p & 1);
  if ((p & 1) == 0) {
    st_rlx4(b + 16 * lane, tag(P[0], par), P[1], P[2], P[3]);
    st_rlx4(b + 512 + 16 * lane, tag(P[4], par), P[5], P[6], P[7]);
    st_rlx4(b + 1024 + 16 * lane, tag(P[8], par), P[9], P[10], P[11]);
    st_rlx2(b + 1536 + 8 * lane, tag(P[12], par), P[13]);
  } else {
    st_rlx2(b + 8 * lane, tag(P[0], par), P[1]);
    st_rlx4(b + 256 + 16 * lane, tag(P[2], par), P[3], P[4], P[5]);
    st_rlx4(b + 768 + 16 * lane, tag(P[6], par), P[7], P[8], P[9]);
    st_rlx4(b + 1280 + 16 * lane, tag(P[10], par), P[11], P[12], P[13]);
  }
}
template <bool SPLIT>
__device__ __forceinline__ void load7(uint4* v, uint32_t s, const char* gsrc, int lane, uint32_t par) {
#pragma unroll
  for (int i = 0; i < 7; i++) {
    if (SPLIT && i == 3) {
      const uint2 a = lds2(s + 1536 + 8 * lane), b = lds2(s + 1792 + 8 * lane);
      v[3] = make_uint4(a.x, a.y, b.x, b.y);
    } else {
      v[i] = lds4(s + 512 * i + 16 * lane);
    }
  }
  int it = 0;
  while (true) {
    uint32_t bad = 0;
    if (SPLIT) { v[3].z ^= par; bad = v[3].z; }
#pragma unroll
    for (int i = 0; i < 7; i++) { v[i].x ^= par; bad |= v[i].x; }
    if (__builtin_expect(!(bad & 1), 1)) break;
#pragma unroll
    for (int i = 0; i < 7; i++) {
      if (SPLIT && i == 3) {
        const uint2 a = ld_rlx2(gsrc + 1536 + 8 * lane), b = ld_rlx2(gsrc + 1792 + 8 * lane);
        v[3] = make_uint4(a.x, a.y, b.x, b.y);
      } else {
        v[i] = ld_rlx4(gsrc + 512 * i + 16 * lane);
      }
    }
    if (++it > SPIN_LIMIT) break;
  }
  __syncwarp();
}
#define BAR(i) (sb + SMEM_BAR + 8 * (i))
#define MMA56(acc, a, desc, sc) wgmma_rs_n56(acc, (a).x, (a).y, (a).z, (a).w, desc, sc)

template <bool SWAP>
__global__ void __launch_bounds__(384, 1)
fused_block_kernel(const __grid_constant__ CUtensorMap map_x, const __grid_constant__ CUtensorMap map_kv,
                   const __grid_constant__ CUtensorMap map_q, const __grid_constant__ CUtensorMap map_wo,
                   const __grid_constant__ CUtensorMap map_gu, const __grid_constant__ CUtensorMap map_gu32,
                   const __grid_constant__ CUtensorMap map_d, const __grid_constant__ CUtensorMap map_out,
                   const char* __restrict__ wqkv, const char* __restrict__ wo,
                   const char* __restrict__ wg, const char* __restrict__ wu, const char* __restrict__ wd) {
  extern __shared__ __align__(1024) uint8_t smem[];
  const int tid = threadIdx.x, lane = tid & 31, warp = tid >> 5;
  const int cta = blockIdx.x, r = cta >> 3, p = cta & 7;
  const int kh = p & 1;
  char* const bufA = (char*)g_bufA;
  char* const bufB = (char*)g_bufB;
  const uint32_t epoch = ld_rlx1(&g_epoch[cta * 32]);
  const uint32_t par = (epoch + 1) & 1;

  if (warp >= 8) {
    asm volatile("setmaxnreg.dec.sync.aligned.u32 40;");
    const int wcol = 56 * p - 8 * kh;
    STAMP(0);
    if (tid == 256) {
      if (smem_u32(smem) != sb) __trap();
      for (int i = 0; i < 4; i++) mbar_init(BAR(B_KV + i), 1);
      asm volatile("fence.mbarrier_init.release.cluster;" ::: "memory");
      fence_async_smem();
      for (int j = 0; j < 4; j++) {
        mbar_expect_tx(BAR(B_KV + j), STG);
        tma3d(sb + j * STG, &map_kv, wcol, 112 * j, 1, BAR(B_KV + j));
      }
    } else if (tid == 288) {
      for (int i = 0; i < 8; i++) { mbar_init(BAR(B_FULL + i), 1); mbar_init(BAR(B_EMPTY + i), 8); }
      for (int i = B_Q; i < B_XFREE; i++) mbar_init(BAR(i), 1);
      for (int i = B_XFREE; i < B_KVB; i++) mbar_init(BAR(i), 8);
      for (int i = B_KVB; i < B_XB; i++) mbar_init(BAR(i), 4);
      asm volatile("fence.mbarrier_init.release.cluster;" ::: "memory");
      l2_prefetch(wqkv + cta * 9408, 9408);
    }
    bar_sync<0, 384>();
    const int ct = tid - 256;
    const uint32_t e1 = epoch + 1;
    mbar_wait(BAR(B_XFREE), 0);
    if (tid == 256) {
      mbar_expect_tx(BAR(B_Q), 2 * STG);
      tma2d(sb + OFF_Q, &map_q, wcol, 0, BAR(B_Q));
      tma2d(sb + OFF_Q + STG, &map_q, wcol, 224, BAR(B_Q));
      prefetch_map(&map_wo); prefetch_map(&map_gu);
      mbar_wait(BAR(B_KFREE), 0);
      mbar_expect_tx(BAR(B_WO), 2 * STG);
      tma2d(sb + OFF_WO, &map_wo, wcol, 0, BAR(B_WO));
      tma2d(sb + OFF_WO + STG, &map_wo, wcol, 224, BAR(B_WO));
      for (int u = 0; u < 2; u++) {
        mbar_expect_tx(BAR(B_FULL + u), STG);
        tma3d(sb + u * STG, &map_gu, 224 * p, 112 * u, 0, BAR(B_FULL + u));
      }
    } else if (tid == 288) {
      l2_prefetch(wo + cta * 3136, 3136);
      l2_prefetch(wg + cta * 12544, 12544);
      l2_prefetch(wu + cta * 12544, 12544);
      l2_prefetch(wd + cta * 12544, 12544);
      prefetch_map(&map_gu32); prefetch_map(&map_d); prefetch_map(&map_out);
    }
    __syncwarp();
#pragma unroll
    for (int i = 0; i < 4; i++) sts4(sb + OFF_KVB + i * 2048 + ct * 16, 0, 0, 0, 0);
    {
      cnt_wait(&g_cnt[C_KVP + p * 32], e1 * 64);
      if (ct == 0) STAMPP(1);
      const char* src = bufA + A_KVP + p * 16 * 8192 + (128 * r + ct) * 4;
      float sum;
      int it = 0;
      while (true) {
        uint32_t v[16], bad = 0;
#pragma unroll
        for (int s = 0; s < 16; s++) v[s] = ld_rlx1(src + s * 8192) ^ par;
        sum = 0.f;
#pragma unroll
        for (int s = 0; s < 16; s++) { bad |= v[s]; sum += __uint_as_float(v[s]); }
        if (!(bad & 1)) break;
        if (++it > SPIN_LIMIT) break;
      }
      st_rlx1(bufA + A_KVR + p * 8192 + (128 * r + ct) * 4, tagf(sum, par));
      __syncwarp();
      if (lane == 0) red_inc(&g_cnt[C_KVR + p * 32]);
      if (ct == 0) STAMPP(2);
    }
    bar_sync<2, 128>();
    {
      cnt_wait(&g_cnt[C_KVR + p * 32], e1 * 64);
      if (ct == 0) STAMPP(3);
      const char* src = bufA + A_KVR + p * 8192 + ct * 16;
      uint4 v[4];
      int it = 0;
      while (true) {
        uint32_t bad = 0;
#pragma unroll
        for (int i = 0; i < 4; i++) {
          v[i] = ld_rlx4(src + i * 2048);
          v[i].x ^= par; v[i].y ^= par; v[i].z ^= par; v[i].w ^= par;
          bad |= v[i].x | v[i].y | v[i].z | v[i].w;
        }
        if (!(bad & 1)) break;
        if (++it > SPIN_LIMIT) break;
      }
      const int d = 16 * (warp & 1) + (lane >> 2);
#pragma unroll
      for (int i = 0; i < 4; i++) {
        const int hh = i >> 1, e = 16 * (i & 1) + 8 * (ct >> 6) + 2 * (lane & 3);
#pragma unroll
        for (int half = 0; half < 2; half++) {
          const int dd = d + 8 * half;
          const float f0 = __uint_as_float(half ? v[i].z : v[i].x), f1 = __uint_as_float(half ? v[i].w : v[i].y);
          const int k = 28 * hh + dd;
          if (dd < 28) {
            if (e < 28) {
              const int n = 28 * hh + e;
              sts1(sb + OFF_KVB + k * 128 + (((n >> 3) ^ (k & 7)) << 4) + (n & 7) * 2, pack2(f0, f1));
            } else if (e == 28) {
              const uint32_t z = hh ? pack2(0.f, f0) : pack2(f0, 0.f);
              sts4(sb + OFF_KVB + k * 128 + ((7 ^ (k & 7)) << 4), z, z, z, z);
            }
          }
        }
      }
      fence_async_smem();
      __syncwarp();
      if (lane == 0) mbar_arrive(BAR(B_KVB));
      if (ct == 0) STAMPP(4);
    }
    if (lane == 0) {
      if (warp == 8) {
        for (int u = 2; u < 30; u++) {
          if (u >= 14 && !(u & 1)) continue;
          const int s = u & 7;
          if (u == 2) mbar_wait(BAR(B_WOFREE), 0);
          if (u >= 4 && u < 8) mbar_wait(BAR(B_HFREE + u - 4), 0);
          if (u >= 8) mbar_wait(BAR(B_EMPTY + s), ((u >> 3) - 1) & 1);
          STAMPP(20 + u);
          mbar_expect_tx(BAR(B_FULL + s), STG);
          if (u < 12) {
            tma3d(sb + s * STG, &map_gu, 224 * p + 64 * (u >> 2), 112 * (u & 3), 0, BAR(B_FULL + s));
          } else if (u < 14) {
            tma3d(sb + s * STG, &map_gu32, 224 * p + 192, 224 * (u - 12), 0, BAR(B_FULL + s));
          } else {
            const int j = u - 14, src = (p + 2 * ((j >> 1) & 3)) & 7;
            tma4d(sb + s * STG, &map_d, 0, 224 * src + 112 * (j >> 3), 0, p >> 1, BAR(B_FULL + s));
          }
        }
      } else if (warp == 11) {
        for (int j = 0; j < 16; j += 2) {
          const int u = 14 + j, s = u & 7;
          const int sc = (cta & ~7) + ((p + (j & 7)) & 7);
          cnt_wait(&g_cnt[C_CTA + sc * 8 + (j >> 3)], e1 * 8);
          mbar_wait(BAR(B_EMPTY + s), ((u >> 3) - 1) & 1);
          mbar_expect_tx(BAR(B_FULL + s), STG);
          bulk_g2s(sb + s * STG, bufB + (size_t)(sc * 2 + (j >> 3)) * STG, STG, BAR(B_FULL + s));
          STAMPP(8 + (j >> 1));
        }
        st_rlx1(&g_epoch[cta * 32], e1);
        DUMP(2);
      } else {
        const int g = warp - 9;
        const char* src = bufA + A_O + r * 4 * STG + g * TILE;
        for (int t = 0; t < 2; t++) {
          if (t == 1) mbar_wait(BAR(B_ODONE + g), 0);
          for (int q = 0; q < 4; q++) mbar_expect_tx(BAR(B_WB + 4 * g + q), TILE);
          if (t == 0) mbar_wait(BAR(B_OFREE), 0);
          cnt_wait(&g_cnt[C_ROW + r * 32 + 2 * t + g], e1 * 32);
          if (t == 1) mbar_arrive(BAR(B_GO + g));
          for (int q = 0; q < 4; q++)
            bulk_g2s(sb + OFF_GATH + q * STG + g * TILE, src + t * FRAG_B + q * STG, TILE, BAR(B_WB + 4 * g + q));
          if (g == 0) STAMPP(5 + t);
        }
      }
    }
  } else {
    asm volatile("setmaxnreg.inc.sync.aligned.u32 232;");
    STAMP(0);
    const int g = warp >> 2, gq = lane >> 2, tq = lane & 3;
    const int lrow = 16 * warp + gq;
    const uint32_t gath = sb + OFF_GATH + warp * TILE;
    uint4 A[28];
    if (lane == 0) {
      mbar_init(BAR(B_XB + warp), 1);
      asm volatile("fence.mbarrier_init.release.cluster;" ::: "memory");
      fence_async_smem();
      mbar_expect_tx(BAR(B_XB + warp), TILE);
      tma3d(gath, &map_x, 0, 128 * r + 16 * warp, 0, BAR(B_XB + warp));
    }
    bar_sync<0, 384>();

    float rs0, rs1;
    uint32_t R[14];
    float acc0[28], acc1[28];
    {
      mbar_wait(BAR(B_XB + warp), 0);
      STAMP(1);
      const uint32_t la = gath + (lane & 15) * 128;
#pragma unroll
      for (int ks = 0; ks < 28; ks++)
        A[ks] = ldsm4(la + (ks >> 2) * 2048 + (((2 * (ks & 3) + (lane >> 4)) ^ (lane & 7)) << 4));
#pragma unroll
      for (int j = 0; j < 7; j++) {
        const int G = 7 * p + j;
        const uint32_t a = gath + (G >> 3) * 2048 + gq * 128 + (((G & 7) ^ gq) << 4) + 4 * tq;
        R[2 * j] = lds1(a);
        R[2 * j + 1] = lds1(a + 1024);
      }
      float cs[4][4] = {};
#pragma unroll
      for (int ks = 0; ks < 28; ks++) mma16816(cs[ks & 3], A[ks].x, A[ks].y, A[ks].z, A[ks].w, 0x3F803F80u, 0x3F803F80u);
      const float m0 = ((cs[0][0] + cs[1][0]) + (cs[2][0] + cs[3][0])) * (1.f / DM);
      const float m1 = ((cs[0][2] + cs[1][2]) + (cs[2][2] + cs[3][2])) * (1.f / DM);
      const uint32_t mb0 = pack2(m0, m0), mb1 = pack2(m1, m1);
      asm volatile("" ::"r"(mb0), "r"(R[13]) : "memory");
      __syncwarp();
      if (lane == 0) mbar_arrive(BAR(B_XFREE));
#pragma unroll
      for (int ks = 0; ks < 28; ks++)
        A[ks] = make_uint4(sub2(A[ks].x, mb0), sub2(A[ks].y, mb1), sub2(A[ks].z, mb0), sub2(A[ks].w, mb1));
      STAMP(2);
      float q0 = 0.f, q1 = 0.f, q2 = 0.f, q3 = 0.f;
#pragma unroll
      for (int j = 0; j < 4; j++) {
        mbar_wait(BAR(B_KV + j), 0);
        wg_fence();
#pragma unroll
        for (int i = 0; i < 7; i++) {
          const int ks = 7 * j + i;
          MMA56(acc0, A[ks], mn_desc(sb + j * STG + i * 2048) + kh, j + i != 0);
          MMA56(acc1, A[ks], mn_desc(sb + j * STG + TILE + i * 2048) + kh, j + i != 0);
          float a;
          a = bf_lo(A[ks].x); q0 = fmaf(a, a, q0); a = bf_hi(A[ks].x); q2 = fmaf(a, a, q2);
          a = bf_lo(A[ks].y); q1 = fmaf(a, a, q1); a = bf_hi(A[ks].y); q3 = fmaf(a, a, q3);
          a = bf_lo(A[ks].z); q0 = fmaf(a, a, q0); a = bf_hi(A[ks].z); q2 = fmaf(a, a, q2);
          a = bf_lo(A[ks].w); q1 = fmaf(a, a, q1); a = bf_hi(A[ks].w); q3 = fmaf(a, a, q3);
          asm volatile("" : "+f"(q0), "+f"(q1), "+f"(q2), "+f"(q3));
        }
      }
      wg_commit();
      STAMP(3);
      q0 += q2; q1 += q3;
      q0 += __shfl_xor_sync(0xffffffffu, q0, 1); q1 += __shfl_xor_sync(0xffffffffu, q1, 1);
      q0 += __shfl_xor_sync(0xffffffffu, q0, 2); q1 += __shfl_xor_sync(0xffffffffu, q1, 2);
      const float d0 = m0 - bf_lo(mb0), d1 = m1 - bf_lo(mb1);
      rs0 = rsqrtf(fmaxf(q0 * (1.f / DM) - d0 * d0, 0.f) + 1e-5f);
      rs1 = rsqrtf(fmaxf(q1 * (1.f / DM) - d1 * d1, 0.f) + 1e-5f);
    }
    mbar_wait(BAR(B_XFREE), 0);
    wg_wait<0>();
    acc_fence(acc0); acc_fence(acc1);
    STAMP(4);
    if (lane == 0) mbar_arrive(BAR(B_KFREE));
    {
      const uint32_t rb = sb + lrow * 128;
#pragma unroll
      for (int j = 0; j < 7; j++) {
        const int c = 8 * j + 2 * tq;
        const int cc = (c < 28) ? c : c + 4;
        const uint32_t off = (((cc >> 3) ^ gq) << 4) + (cc & 7) * 2;
        sts1(rb + OFF_PK + off, pack2(phi(acc0[4 * j] * rs0), phi(acc0[4 * j + 1] * rs0)));
        sts1(rb + OFF_PK + 1024 + off, pack2(phi(acc0[4 * j + 2] * rs1), phi(acc0[4 * j + 3] * rs1)));
        sts1(rb + OFF_PV + off, pack2(acc1[4 * j] * rs0, acc1[4 * j + 1] * rs0));
        sts1(rb + OFF_PV + 1024 + off, pack2(acc1[4 * j + 2] * rs1, acc1[4 * j + 3] * rs1));
      }
      const uint32_t off1 = ((((tq & 1) ? 7 : 3) ^ gq) << 4) + 8 + ((tq >> 1) << 10);
      sts1(rb + OFF_PV + off1, 0x00003F80u);
    }
    fence_async_smem();
    bar_sync<1, 256>();
    STAMP(5);
    float kvacc[16];
    wg_fence();
#pragma unroll
    for (int i = 0; i < 8; i++)
      wgmma_ss_n32_ta(kvacc, mn_desc(sb + OFF_PK + i * 2048), mn_desc(sb + OFF_PV + i * 2048) + 4 * g, i != 0);
    wg_commit();
    wg_wait<0>();
    acc_fence(kvacc);
    if (((warp >> 1) & 1) == g) {
      char* dst = bufA + A_KVP + (p * 16 + r) * 8192 + g * 4096 + (tid & 63) * 16;
#pragma unroll
      for (int q = 0; q < 4; q++)
        st_rlx4(dst + q * 1024, tagf(kvacc[4 * q], par), tagf(kvacc[4 * q + 1], par), tagf(kvacc[4 * q + 2], par),
                tagf(kvacc[4 * q + 3], par));
      if (lane == 0) red_inc(&g_cnt[C_KVP + p * 32]);
    }
    STAMP(6);
    mbar_wait(BAR(B_Q), 0);
    wg_fence();
#pragma unroll
    for (int ks = 0; ks < 28; ks++) MMA56(acc0, A[ks], mn_desc(sb + OFF_Q + ks * 2048) + kh, ks != 0);
    wg_commit();
    wg_wait<0>();
    acc_fence(acc0);
    STAMP(7);
    uint32_t P[14];
#pragma unroll
    for (int j = 0; j < 7; j++) {
      P[2 * j] = pack2(phi(acc0[4 * j] * rs0), phi(acc0[4 * j + 1] * rs0));
      P[2 * j + 1] = pack2(phi(acc0[4 * j + 2] * rs1), phi(acc0[4 * j + 3] * rs1));
    }
    STAMP(8);
    mbar_wait(BAR(B_KVB), 0);
    STAMP(9);
    {
      float oacc[32];
      wg_fence();
      wgmma_rs_n64(oacc, P[0], P[1], P[2], P[3], mn_desc(sb + OFF_KVB), 0);
      wgmma_rs_n64(oacc, P[4], P[5], P[6], P[7], mn_desc(sb + OFF_KVB + 2048), 1);
      wgmma_rs_n64(oacc, P[8], P[9], P[10], P[11], mn_desc(sb + OFF_KVB + 4096), 1);
      wgmma_rs_n64(oacc, P[12], P[13], 0u, 0u, mn_desc(sb + OFF_KVB + 6144), 1);
      wg_commit();
      wg_wait<0>();
      acc_fence(oacc);
      STAMP(59);
      if (lane == 0) mbar_arrive(BAR(B_OFREE));
      const float ia0 = __fdividef(1.f, oacc[28] + 1e-6f), ib0 = __fdividef(1.f, oacc[29] + 1e-6f);
      const float ia1 = __fdividef(1.f, oacc[30] + 1e-6f), ib1 = __fdividef(1.f, oacc[31] + 1e-6f);
#pragma unroll
      for (int j = 0; j < 7; j++) {
        const bool first = (j < 3) || (j == 3 && tq < 2);
        const float s0 = first ? ia0 : ib0, s1 = first ? ia1 : ib1;
        P[2 * j] = pack2(oacc[4 * j] * s0, oacc[4 * j + 1] * s0);
        P[2 * j + 1] = pack2(oacc[4 * j + 2] * s1, oacc[4 * j + 3] * s1);
      }
    }
    char* const oblk = bufA + A_O + r * 4 * STG + warp * 3584;
    const uint32_t wsub = sb + warp * 3584;
    {
      publish7(oblk, p, lane, P, par);
      if (lane == 0) red_inc(&g_cnt[C_ROW + r * 32 + g]);
      STAMP(10);
      mbar_wait(BAR(B_WO), 0);
#pragma unroll
      for (int q = 0; q < 4; q++) {
        mbar_wait(BAR(B_WB + q) + 32 * g, 0);
        STAMP(26 + q);
        load7<true>(&A[7 * q], wsub + OFF_GATH + q * STG, oblk + q * STG, lane, par);
        if (q == 3 && lane == 0) mbar_arrive(BAR(B_ODONE) + 8 * g);
        wg_fence();
#pragma unroll
        for (int i = 0; i < 7; i++) MMA56(acc0, A[7 * q + i], mn_desc(sb + OFF_WO + (7 * q + i) * 2048) + kh, q + i != 0);
      }
      wg_commit();
      wg_wait<0>();
      acc_fence(acc0);
      STAMP(12);
      if (lane == 0) mbar_arrive(BAR(B_WOFREE));
#pragma unroll
      for (int j = 0; j < 7; j++) {
        R[2 * j] = pack2(acc0[4 * j] + bf_lo(R[2 * j]), acc0[4 * j + 1] + bf_hi(R[2 * j]));
        R[2 * j + 1] = pack2(acc0[4 * j + 2] + bf_lo(R[2 * j + 1]), acc0[4 * j + 3] + bf_hi(R[2 * j + 1]));
      }
      publish7(oblk + FRAG_B, p, lane, R, par);
      float s0 = 0.f, s1 = 0.f;
#pragma unroll
      for (int j = 0; j < 7; j++) {
        s0 += bf_lo(R[2 * j]) + bf_hi(R[2 * j]);
        s1 += bf_lo(R[2 * j + 1]) + bf_hi(R[2 * j + 1]);
      }
      s0 += __shfl_xor_sync(0xffffffffu, s0, 1); s1 += __shfl_xor_sync(0xffffffffu, s1, 1);
      s0 += __shfl_xor_sync(0xffffffffu, s0, 2); s1 += __shfl_xor_sync(0xffffffffu, s1, 2);
      s0 *= (1.f / 56); s1 *= (1.f / 56);
      float v0 = 0.f, v1 = 0.f;
#pragma unroll
      for (int j = 0; j < 7; j++) {
        float a = bf_lo(R[2 * j]) - s0, b = bf_hi(R[2 * j]) - s0;
        v0 += a * a + b * b;
        a = bf_lo(R[2 * j + 1]) - s1; b = bf_hi(R[2 * j + 1]) - s1;
        v1 += a * a + b * b;
      }
      v0 += __shfl_xor_sync(0xffffffffu, v0, 1); v1 += __shfl_xor_sync(0xffffffffu, v1, 1);
      v0 += __shfl_xor_sync(0xffffffffu, v0, 2); v1 += __shfl_xor_sync(0xffffffffu, v1, 2);
      if (tq == 0)
        st_rlx4(bufA + A_STAT + (r * 8 + warp) * 1024 + p * 128 + gq * 16, tagf(s0, par), __float_as_uint(v0),
                __float_as_uint(s1), __float_as_uint(v1));
      __syncwarp();
      if (lane == 0) red_inc(&g_cnt[C_ROW + r * 32 + 2 + g]);
    }
    STAMP(13);
    uint32_t mb0, mb1;
    {
      const char* st = bufA + A_STAT + (r * 8 + warp) * 1024 + tq * 256 + gq * 16;
      mbar_wait(BAR(B_GO) + 8 * g, 0);
      STAMP(11);
      uint4 t0, t1;
      int it = 0;
      do {
        t0 = ld_rlx4(st); t1 = ld_rlx4(st + 128);
        if (++it > SPIN_LIMIT) break;
        t0.x ^= par; t1.x ^= par;
      } while ((t0.x | t1.x) & 1);
      __syncwarp();
      STAMP(14);
      { uint32_t a = t0.z, b = t0.w; t0.z = t1.x; t0.w = t1.y; t1.x = a; t1.y = b; }
      float m0 = __uint_as_float(t0.x) + __uint_as_float(t0.z), m1 = __uint_as_float(t1.x) + __uint_as_float(t1.z);
      m0 += __shfl_xor_sync(0xffffffffu, m0, 1); m1 += __shfl_xor_sync(0xffffffffu, m1, 1);
      m0 += __shfl_xor_sync(0xffffffffu, m0, 2); m1 += __shfl_xor_sync(0xffffffffu, m1, 2);
      m0 *= 0.125f; m1 *= 0.125f;
      float a = __uint_as_float(t0.x) - m0, b = __uint_as_float(t0.z) - m0;
      float v0 = __uint_as_float(t0.y) + __uint_as_float(t0.w) + 56.f * (a * a + b * b);
      a = __uint_as_float(t1.x) - m1; b = __uint_as_float(t1.z) - m1;
      float v1 = __uint_as_float(t1.y) + __uint_as_float(t1.w) + 56.f * (a * a + b * b);
      v0 += __shfl_xor_sync(0xffffffffu, v0, 1); v1 += __shfl_xor_sync(0xffffffffu, v1, 1);
      v0 += __shfl_xor_sync(0xffffffffu, v0, 2); v1 += __shfl_xor_sync(0xffffffffu, v1, 2);
      rs0 = rsqrtf(v0 * (1.f / DM) + 1e-5f);
      rs1 = rsqrtf(v1 * (1.f / DM) + 1e-5f);
      mb0 = pack2(m0, m0); mb1 = pack2(m1, m1);
    }
    {
      char* const hdst = bufB + (size_t)cta * 2 * STG + warp * 3584 + lane * 16;
      const float e0 = 0.5f * rs0, e1 = 0.5f * rs1;
#define GLU(gt, up, rs, e) fmaf((up) * (e), tanhf_((gt) * (e)), (up) * (e))
      float acc[64];
#pragma unroll 1
      for (int c = 0; c < 3; c++) {
        const uint32_t half = (c & 1) * 4;
#pragma unroll
        for (int kq = 0; kq < 4; kq++) {
          if (c == 0) {
            mbar_wait(BAR(B_WB + kq) + 32 * g, 1);
            STAMP(30 + kq);
            load7<true>(&A[7 * kq], wsub + OFF_GATH + kq * STG, oblk + FRAG_B + kq * STG, lane, par);
            if (lane == 0) mbar_arrive(BAR(B_HFREE + kq));
#pragma unroll
            for (int i = 0; i < 7; i++) {
              uint4& a = A[7 * kq + i];
              a.x = sub2(a.x, mb0); a.y = sub2(a.y, mb1); a.z = sub2(a.z, mb0); a.w = sub2(a.w, mb1);
            }
          }
          STAMP(34 + 8 * c + 2 * kq);
          mbar_wait(BAR(B_FULL + kq) + 8 * half, c >> 1);
          STAMP(35 + 8 * c + 2 * kq);
          wg_fence();
#pragma unroll
          for (int i = 0; i < 7; i++) {
            const uint4& a = A[7 * kq + i];
            wgmma_rs_n128(acc, a.x, a.y, a.z, a.w, mn_desc(sb + kq * STG + i * 2048) + half * (STG >> 4), kq + i != 0);
          }
          wg_commit();
          if (kq > 0) {
            wg_wait<1>();
            if (lane == 0) mbar_arrive(BAR(B_EMPTY + kq - 1) + 8 * half);
          }
        }
        wg_wait<0>();
        acc_fence(acc);
        if (lane == 0) mbar_arrive(BAR(B_EMPTY + 3) + 8 * half);
        STAMP(15 + c);
        constexpr int GO = SWAP ? 32 : 0, UO = SWAP ? 0 : 32;
#pragma unroll
        for (int i = 0; i < 4; i++) {
          uint32_t w[4];
#pragma unroll
          for (int t = 0; t < 2; t++) {
            const int b = 8 * i + 4 * t;
            w[2 * t] = pack2(GLU(acc[GO + b], acc[UO + b], rs0, e0), GLU(acc[GO + b + 1], acc[UO + b + 1], rs0, e0));
            w[2 * t + 1] = pack2(GLU(acc[GO + b + 2], acc[UO + b + 2], rs1, e1), GLU(acc[GO + b + 3], acc[UO + b + 3], rs1, e1));
          }
          const int ks = 4 * c + i;
          st_rlx4(hdst + ks * 512 + (ks >= 7 ? STG - 3584 : 0), tag(w[0], par), w[1], w[2], w[3]);
        }
        if (c == 1 && lane == 0) red_inc(&g_cnt[C_CTA + cta * 8]);
      }
      float acct[32];
#pragma unroll
      for (int h = 0; h < 2; h++) {
        mbar_wait(BAR(B_FULL + 4 + h), 1);
        wg_fence();
#pragma unroll
        for (int i = 0; i < 14; i++) {
          const uint4& a = A[14 * h + i];
          wgmma_rs_n64(acct, a.x, a.y, a.z, a.w, mn_desc64(sb + (4 + h) * STG + i * 1024), h + i != 0);
        }
        wg_commit();
      }
      wg_wait<1>();
      if (lane == 0) mbar_arrive(BAR(B_EMPTY + 4));
      wg_wait<0>();
      acc_fence(acct);
      if (lane == 0) mbar_arrive(BAR(B_EMPTY + 5));
      STAMP(18);
      constexpr int GO = SWAP ? 16 : 0, UO = SWAP ? 0 : 16;
#pragma unroll
      for (int i = 0; i < 2; i++) {
        uint32_t w[4];
#pragma unroll
        for (int t = 0; t < 2; t++) {
          const int b = 8 * i + 4 * t;
          w[2 * t] = pack2(GLU(acct[GO + b], acct[UO + b], rs0, e0), GLU(acct[GO + b + 1], acct[UO + b + 1], rs0, e0));
          w[2 * t + 1] = pack2(GLU(acct[GO + b + 2], acct[UO + b + 2], rs1, e1), GLU(acct[GO + b + 3], acct[UO + b + 3], rs1, e1));
        }
        st_rlx4(hdst + STG + (5 + i) * 512, tag(w[0], par), w[1], w[2], w[3]);
      }
      if (lane == 0) red_inc(&g_cnt[C_CTA + cta * 8 + 1]);
    }
    STAMP(19);
    {
      const uint32_t dsend = (1 - kh) * ((TILE >> 4) + 1), dkeep = kh * ((TILE >> 4) + 1);
      const char* const hsrc = bufB + (size_t)(cta & ~7) * 2 * STG + warp * 3584;
#pragma unroll
      for (int q = 0; q < 4; q++) {
        const int sh = (6 + 2 * q) & 7, sw = (7 + 2 * q) & 7, ph = (q == 0) ? 1 : 0;
        mbar_wait(BAR(B_FULL + sh), ph);
        load7<false>(&A[7 * q], wsub + sh * STG, hsrc + ((p + 2 * q) & 7) * 2 * STG, lane, par);
        mbar_wait(BAR(B_FULL + sw), ph);
        wg_fence();
#pragma unroll
        for (int i = 0; i < 7; i++) {
          MMA56(acc0, A[7 * q + i], mn_desc(sb + sw * STG + i * 2048) + dsend, q + i != 0);
          MMA56(acc1, A[7 * q + i], mn_desc(sb + sw * STG + i * 2048) + dkeep, q + i != 0);
        }
        wg_commit();
        if (lane == 0) mbar_arrive(BAR(B_EMPTY + sh));
        if (q > 0) {
          wg_wait<1>();
          if (lane == 0) mbar_arrive(BAR(B_EMPTY + ((5 + 2 * q) & 7)));
        }
      }
      STAMP(20);
#pragma unroll
      for (int q = 0; q < 4; q++) {
        const int sh = (6 + 2 * q) & 7, sw = (7 + 2 * q) & 7, ph = (q == 0) ? 0 : 1;
        mbar_wait(BAR(B_FULL + sh), ph);
        load7<false>(&A[7 * q], wsub + sh * STG, hsrc + ((p + 2 * q) & 7) * 2 * STG + STG, lane, par);
        mbar_wait(BAR(B_FULL + sw), ph);
        wg_fence();
#pragma unroll
        for (int i = 0; i < 7; i++) MMA56(acc0, A[7 * q + i], mn_desc(sb + sw * STG + i * 2048) + dsend, 1);
        wg_commit();
        if (q == 0) {
          wg_wait<1>();
          if (lane == 0) mbar_arrive(BAR(B_EMPTY + 5));
        }
      }
#pragma unroll
      for (int q = 0; q < 4; q++) {
        const int sw = (7 + 2 * q) & 7;
#pragma unroll
        for (int i = 0; i < 7; i++) MMA56(acc1, A[7 * q + i], mn_desc(sb + sw * STG + i * 2048) + dkeep, 1);
      }
      wg_commit();
      wg_wait<1>();
      acc_fence(acc0);
      STAMP(21);
      char* pd = bufA + A_PART + cta * STG + warp * 3584 + lane * 16;
#pragma unroll
      for (int q = 0; q < 7; q++)
        st_rlx4(pd + q * 512, tagf(acc0[4 * q], par), __float_as_uint(acc0[4 * q + 1]),
                __float_as_uint(acc0[4 * q + 2]), __float_as_uint(acc0[4 * q + 3]));
      const char* ps = bufA + A_PART + (cta ^ 1) * STG + warp * 3584;
      if (lane == 0) {
        red_inc(&g_cnt[C_CTA + cta * 8 + 2 + g]);
        mbar_expect_tx(BAR(B_XB + warp), 3584);
        cnt_wait(&g_cnt[C_CTA + (cta ^ 1) * 8 + 2 + g], (epoch + 1) * 4);
        bulk_g2s(wsub + 6 * STG, ps, 3584, BAR(B_XB + warp));
      }
      __syncwarp();
      STAMP(22);
      wg_wait<0>();
      acc_fence(acc1);
      STAMP(23);
      uint4 pv[7];
      mbar_wait(BAR(B_XB + warp), 1);
      load7<false>(pv, wsub + 6 * STG, ps, lane, par);
      STAMP(24);
      const uint32_t ob = wsub + gq * 112 + 4 * tq;
#pragma unroll
      for (int j = 0; j < 7; j++) {
        sts1(ob + 16 * j, pack2(acc1[4 * j] + __uint_as_float(pv[j].x) + bf_lo(R[2 * j]),
                                acc1[4 * j + 1] + __uint_as_float(pv[j].y) + bf_hi(R[2 * j])));
        sts1(ob + 8 * 112 + 16 * j, pack2(acc1[4 * j + 2] + __uint_as_float(pv[j].z) + bf_lo(R[2 * j + 1]),
                                          acc1[4 * j + 3] + __uint_as_float(pv[j].w) + bf_hi(R[2 * j + 1])));
      }
      fence_async_smem();
      __syncwarp();
      if (lane == 0) {
        tma_store2d(&map_out, wsub, 56 * p, 128 * r + 16 * warp);
        asm volatile("cp.async.bulk.commit_group;" ::: "memory");
        asm volatile("cp.async.bulk.wait_group.read 0;" ::: "memory");
      }
      STAMP(25);
      if ((tid & 127) == 0) DUMP(g);
    }
  }
}

typedef CUresult (*EncodeFn)(CUtensorMap*, CUtensorMapDataType, cuuint32_t, void*, const cuuint64_t*, const cuuint64_t*,
                             const cuuint32_t*, const cuuint32_t*, CUtensorMapInterleave, CUtensorMapSwizzle,
                             CUtensorMapL2promotion, CUtensorMapFloatOOBfill);

void make_map(EncodeFn enc, CUtensorMap* m, const void* p, int rank, const cuuint64_t* gd, const cuuint64_t* gs,
              const cuuint32_t* bd, CUtensorMapSwizzle sw) {
  const cuuint32_t es[5] = {1, 1, 1, 1, 1};
  ENC_CHECK(enc(m, CU_TENSOR_MAP_DATA_TYPE_BFLOAT16, rank, (void*)p, gd, gs, bd, es, CU_TENSOR_MAP_INTERLEAVE_NONE, sw,
                CU_TENSOR_MAP_L2_PROMOTION_NONE, CU_TENSOR_MAP_FLOAT_OOB_FILL_NONE));
}

}

extern "C" void kernel_launch(void* const* d_in, const int* in_sizes, int n_in, void* d_out, int out_size) {
  (void)in_sizes; (void)n_in; (void)out_size;
  static EncodeFn enc = nullptr;
  if (!enc) {
    void* fn = nullptr;
    cudaDriverEntryPointQueryResult qr;
    cudaGetDriverEntryPoint("cuTensorMapEncodeTiled", &fn, cudaEnableDefault, &qr);
    enc = (EncodeFn)fn;
    cudaFuncSetAttribute(fused_block_kernel<false>, cudaFuncAttributeMaxDynamicSharedMemorySize, SMEM_TOTAL);
    cudaFuncSetAttribute(fused_block_kernel<true>, cudaFuncAttributeMaxDynamicSharedMemorySize, SMEM_TOTAL);
  }
  const CUtensorMapSwizzle S128 = CU_TENSOR_MAP_SWIZZLE_128B;
  CUtensorMap mx, mkv, mq, mwo, mgu, mgu32, md, mout;
  {
    cuuint64_t gd[3] = {64, SEQ, 7}, gs[2] = {DM * 2, 128};
    cuuint32_t bd[3] = {64, 16, 7};
    make_map(enc, &mx, d_in[0], 3, gd, gs, bd, S128);
  }
  {
    cuuint64_t gd[3] = {DM, DM, 3}, gs[2] = {3 * DM * 2, DM * 2};
    cuuint32_t bd[3] = {64, 112, 2};
    make_map(enc, &mkv, d_in[1], 3, gd, gs, bd, S128);
  }
  {
    cuuint64_t gd[2] = {DM, DM}, gs[1] = {3 * DM * 2};
    cuuint32_t bd[2] = {64, 224};
    make_map(enc, &mq, d_in[1], 2, gd, gs, bd, S128);
  }
  {
    cuuint64_t gd[2] = {DM, DM}, gs[1] = {DM * 2};
    cuuint32_t bd[2] = {64, 224};
    make_map(enc, &mwo, d_in[2], 2, gd, gs, bd, S128);
  }
  const char *wg = (const char*)d_in[4], *wu = (const char*)d_in[5];
  const bool swap = wu < wg;
  const char* gub = swap ? wu : wg;
  const cuuint64_t gud = swap ? (cuuint64_t)(wg - wu) : (cuuint64_t)(wu - wg);
  {
    cuuint64_t gd[3] = {FF, DM, 2}, gs[2] = {FF * 2, gud};
    cuuint32_t bd[3] = {64, 112, 2};
    make_map(enc, &mgu, gub, 3, gd, gs, bd, S128);
  }
  {
    cuuint64_t gd[3] = {FF, DM, 2}, gs[2] = {FF * 2, gud};
    cuuint32_t bd[3] = {32, 224, 2};
    make_map(enc, &mgu32, gub, 3, gd, gs, bd, CU_TENSOR_MAP_SWIZZLE_64B);
  }
  {
    cuuint64_t gd[4] = {64, FF, 2, 4}, gs[3] = {DM * 2, 96, 224};
    cuuint32_t bd[4] = {64, 112, 2, 1};
    make_map(enc, &md, d_in[6], 4, gd, gs, bd, S128);
  }
  {
    cuuint64_t gd[2] = {DM, SEQ}, gs[1] = {DM * 2};
    cuuint32_t bd[2] = {56, 16};
    make_map(enc, &mout, d_out, 2, gd, gs, bd, CU_TENSOR_MAP_SWIZZLE_NONE);
  }
  if (swap)
    fused_block_kernel<true><<<128, 384, SMEM_TOTAL>>>(mx, mkv, mq, mwo, mgu, mgu32, md, mout, (const char*)d_in[1],
                                                       (const char*)d_in[2], wg, wu, (const char*)d_in[6]);
  else
    fused_block_kernel<false><<<128, 384, SMEM_TOTAL>>>(mx, mkv, mq, mwo, mgu, mgu32, md, mout, (const char*)d_in[1],
                                                        (const char*)d_in[2], wg, wu, (const char*)d_in[6]);
}
```

```cpp
#include <cuda_runtime.h>
#include <cuda_bf16.h>
#include <cuda.h>
#include <stdint.h>
#include <stdio.h>
#include <utility>

#define SPIN_LIMIT (1 << 18)

namespace {

constexpr uint32_t sb = 1024;
constexpr int SEQ = 2048, DM = 448, FF = 1792;
constexpr int TILE = 14336;
constexpr int STG = 2 * TILE;
constexpr int SMEM_BAR = 8 * STG;
constexpr int SMEM_TOTAL = SMEM_BAR + 3072;
constexpr int OFF_GATH = 4 * STG, OFF_Q = 2 * STG, OFF_WO = 6 * STG, OFF_PK = 4 * STG, OFF_KVB = OFF_PK + 32768, OFF_E = SMEM_BAR + 512;
constexpr int B_XB = 0  , B_K = 8  , B_V = 12  , B_Q = 16, B_WO = 17, B_FULL = 18  , B_WB = 26  ,
              B_KVB = 34, B_WDOK = 35, B_WOK = 36, B_INIT = 37,
              B_KFREE = 38, B_OFREE = 39, B_OR0 = 40  , B_HFREE = 42  , B_EMPTY = 46  , B_XFREE = 54, B_VFREE = 55,
              B_OR1 = 56  , B_MFREE = 58;

constexpr int KVR_B = 11264;
constexpr int STAT_B = 16 * 8 * 512;
constexpr int FRAG_B = 16 * 4 * STG;
constexpr int A_CNT = 0, A_EPOCH = 8192, A_KVR = A_EPOCH + 16384, A_WBAR = A_KVR + 8 * KVR_B, A_STAT = A_WBAR + 2048, A_O = A_STAT + STAT_B, A_H = A_O + FRAG_B,
              A_HH = A_H + FRAG_B;
constexpr int HH_B = 128 * 2 * STG;
constexpr int A_PS = A_HH + HH_B;
constexpr int WDS = 25088;
constexpr int A_WD = A_PS + 128 * 3 * TILE;

__device__ uint4 g_buf[(A_WD + 64 * WDS) / 16];
#define g_epoch ((unsigned*)buf + A_EPOCH / 4)
constexpr int C_ROW = 0, C_WD = 512, C_PS = 1024;
#define g_cnt ((unsigned*)buf + A_CNT / 4)
#define ENC_CHECK(x) (void)(x)
#define STAMP(i)
#define GTIME(i)
#define STAMPP(i)
#define DUMP(row)

__device__ __forceinline__ uint32_t smem_u32(const void* p) { return (uint32_t)__cvta_generic_to_shared(p); }
__device__ __forceinline__ void mbar_init(uint32_t bar, uint32_t cnt) {
  asm volatile("mbarrier.init.shared::cta.b64 [%0], %1;" ::"r"(bar), "r"(cnt) : "memory");
}
__device__ __forceinline__ void mbar_expect_tx(uint32_t bar, uint32_t bytes) {
  asm volatile("mbarrier.arrive.expect_tx.shared::cta.b64 _, [%0], %1;" ::"r"(bar), "r"(bytes) : "memory");
}
__device__ __forceinline__ void mbar_arrive(uint32_t bar) {
  asm volatile("mbarrier.arrive.shared::cta.b64 _, [%0];" ::"r"(bar) : "memory");
}
__device__ __forceinline__ void mbar_wait(uint32_t bar, uint32_t parity, int& budget) {
  asm volatile("{\n.reg .pred p;\nW:\nmbarrier.try_wait.parity.shared::cta.b64 p, [%1], %2;\n"
               "add.s32 %0, %0, -1;\nsetp.gt.and.s32 p, %0, 0, !p;\n@p bra W;\n}"
               : "+r"(budget) : "r"(bar), "r"(parity) : "memory");
}
__device__ __forceinline__ bool elect() {
  uint32_t v;
  asm volatile("{\n.reg .pred p;\nelect.sync _|p, 0xffffffff;\nselp.u32 %0, 1, 0, p;\n}" : "=r"(v));
  return v;
}
__device__ __forceinline__ void tma2d(uint32_t dst, const CUtensorMap* m, int c0, int c1, uint32_t bar) {
  asm volatile("cp.async.bulk.tensor.2d.shared::cluster.global.mbarrier::complete_tx::bytes [%0], [%1, {%3, %4}], [%2];"
               ::"r"(dst), "l"(m), "r"(bar), "r"(c0), "r"(c1) : "memory");
}
__device__ __forceinline__ void tma3d(uint32_t dst, const CUtensorMap* m, int c0, int c1, int c2, uint32_t bar) {
  asm volatile("cp.async.bulk.tensor.3d.shared::cluster.global.mbarrier::complete_tx::bytes [%0], [%1, {%3, %4, %5}], [%2];"
               ::"r"(dst), "l"(m), "r"(bar), "r"(c0), "r"(c1), "r"(c2) : "memory");
}
__device__ __forceinline__ void tma4d(uint32_t dst, const CUtensorMap* m, int c0, int c1, int c2, int c3, uint32_t bar) {
  asm volatile("cp.async.bulk.tensor.4d.shared::cluster.global.mbarrier::complete_tx::bytes [%0], [%1, {%3, %4, %5, %6}], [%2];"
               ::"r"(dst), "l"(m), "r"(bar), "r"(c0), "r"(c1), "r"(c2), "r"(c3) : "memory");
}
__device__ __forceinline__ void bulk_g2s(uint32_t dst, const void* src, uint32_t bytes, uint32_t bar) {
  asm volatile("cp.async.bulk.shared::cluster.global.mbarrier::complete_tx::bytes [%0], [%1], %2, [%3];"
               ::"r"(dst), "l"(src), "r"(bytes), "r"(bar) : "memory");
}
__device__ __forceinline__ void tma_store2d(const CUtensorMap* m, uint32_t src, int c0, int c1) {
  asm volatile("cp.async.bulk.tensor.2d.global.shared::cta.bulk_group [%0, {%2, %3}], [%1];"
               ::"l"(m), "r"(src), "r"(c0), "r"(c1) : "memory");
}
__device__ __forceinline__ void l2_prefetch(const void* p, uint32_t bytes) {
  asm volatile("cp.async.bulk.prefetch.L2.global [%0], %1;" ::"l"(p), "r"(bytes) : "memory");
}
__device__ __forceinline__ void prefetch_map(const CUtensorMap* m) {
  asm volatile("prefetch.tensormap [%0];" ::"l"(m) : "memory");
}
__device__ __forceinline__ void fence_async_smem() { asm volatile("fence.proxy.async.shared::cta;" ::: "memory"); }
template <int ID, int N> __device__ __forceinline__ void bar_arrive() { asm volatile("bar.arrive %0, %1;" ::"n"(ID), "n"(N) : "memory"); }
__device__ __forceinline__ void bar_sync_wg(int id) { asm volatile("bar.sync %0, 128;" ::"r"(id) : "memory"); }
template <int ID, int N> __device__ __forceinline__ void bar_sync() { asm volatile("bar.sync %0, %1;" ::"n"(ID), "n"(N) : "memory"); }
__device__ __forceinline__ void wg_fence() { asm volatile("wgmma.fence.sync.aligned;" ::: "memory"); }
__device__ __forceinline__ void wg_commit() { asm volatile("wgmma.commit_group.sync.aligned;" ::: "memory"); }
template <int N> __device__ __forceinline__ void wg_wait() { asm volatile("wgmma.wait_group.sync.aligned %0;" ::"n"(N) : "memory"); }
template <int N> __device__ __forceinline__ void acc_fence(float (&d)[N]) {
#pragma unroll
  for (int i = 0; i < N; i++) asm volatile("" : "+f"(d[i])::"memory");
}
constexpr uint64_t mn_desc(uint32_t addr) {
  return (uint64_t)((addr & 0x3FFFF) >> 4) | ((uint64_t)(TILE >> 4) << 16) | ((uint64_t)64 << 32) | ((uint64_t)1 << 62);
}
constexpr uint64_t mn_desc64(uint32_t addr) {
  return (uint64_t)((addr & 0x3FFFF) >> 4) | ((uint64_t)(TILE >> 4) << 16) | ((uint64_t)32 << 32) | ((uint64_t)2 << 62);
}
constexpr uint64_t mn_desc0(uint32_t addr) {
  return (uint64_t)((addr & 0x3FFFF) >> 4) | ((uint64_t)(1792 >> 4) << 16) | ((uint64_t)8 << 32);
}
__device__ __forceinline__ uint4 ld_rlx4(const void* p) {
  uint4 v;
  asm volatile("ld.relaxed.gpu.global.v4.u32 {%0,%1,%2,%3}, [%4];" : "=r"(v.x), "=r"(v.y), "=r"(v.z), "=r"(v.w) : "l"(p) : "memory");
  return v;
}
__device__ __forceinline__ uint2 ld_rlx2(const void* p) {
  uint2 v;
  asm volatile("ld.relaxed.gpu.global.v2.u32 {%0,%1}, [%2];" : "=r"(v.x), "=r"(v.y) : "l"(p) : "memory");
  return v;
}
__device__ __forceinline__ uint32_t ld_rlx1(const void* p) {
  uint32_t v;
  asm volatile("ld.relaxed.gpu.global.u32 %0, [%1];" : "=r"(v) : "l"(p) : "memory");
  return v;
}
__device__ __forceinline__ void st_rlx4(void* p, uint32_t a, uint32_t b, uint32_t c, uint32_t d) {
  asm volatile("st.relaxed.gpu.global.v4.u32 [%0], {%1,%2,%3,%4};" ::"l"(p), "r"(a), "r"(b), "r"(c), "r"(d) : "memory");
}
__device__ __forceinline__ void st_rlx2(void* p, uint32_t a, uint32_t b) {
  asm volatile("st.relaxed.gpu.global.v2.u32 [%0], {%1,%2};" ::"l"(p), "r"(a), "r"(b) : "memory");
}
__device__ __forceinline__ void st_rlx1(void* p, uint32_t a) {
  asm volatile("st.relaxed.gpu.global.u32 [%0], %1;" ::"l"(p), "r"(a) : "memory");
}
__device__ __forceinline__ void red_inc(unsigned* p) {
  asm volatile("red.relaxed.gpu.global.inc.u32 [%0], 0xfffffffe;" ::"l"(p) : "memory");
}
__device__ __forceinline__ void red_add4(void* p, float a, float b, float c) {
  asm volatile("red.relaxed.gpu.global.add.v4.f32 [%0], {%1,%2,%3,%4};" ::"l"(p), "f"(a), "f"(b), "f"(c), "f"(1.f) : "memory");
}
__device__ __forceinline__ void red_add2(void* p, float a) {
  asm volatile("red.relaxed.gpu.global.add.v2.f32 [%0], {%1,%2};" ::"l"(p), "f"(a), "f"(1.f) : "memory");
}
__device__ __forceinline__ void eq_wait(const void* p, uint32_t target, int& budget) {
  asm volatile("{\n.reg .pred p;\n.reg .b32 v;\nW:\nld.relaxed.gpu.global.b32 v, [%1];\nadd.s32 %0, %0, -1;\n"
               "setp.gt.s32 p, %0, 0;\nsetp.ne.and.b32 p, v, %2, p;\n@p bra W;\n}"
               : "+r"(budget) : "l"(p), "r"(target) : "memory");
}
template <bool ACQ = false>
__device__ __forceinline__ void cnt_wait(const unsigned* p, uint32_t target, int& budget) {
  if (ACQ)
    asm volatile("{\n.reg .pred p;\n.reg .s32 v;\nW:\nld.acquire.gpu.global.s32 v, [%1];\nadd.s32 %0, %0, -1;\n"
                 "setp.gt.s32 p, %0, 0;\nsub.s32 v, v, %2;\nsetp.lt.and.s32 p, v, 0, p;\n@p bra W;\n}"
                 : "+r"(budget) : "l"(p), "r"(target) : "memory");
  else
  asm volatile("{\n.reg .pred p;\n.reg .s32 v;\nW:\nld.relaxed.gpu.global.s32 v, [%1];\nadd.s32 %0, %0, -1;\n"
               "setp.gt.s32 p, %0, 0;\nsub.s32 v, v, %2;\nsetp.lt.and.s32 p, v, 0, p;\n@p bra W;\n}"
               : "+r"(budget) : "l"(p), "r"(target) : "memory");
}
__device__ __forceinline__ uint32_t or3(uint32_t a, uint32_t b, uint32_t c) {
  uint32_t r;
  asm("lop3.b32 %0, %1, %2, %3, 0xfe;" : "=r"(r) : "r"(a), "r"(b), "r"(c));
  return r;
}
__device__ __forceinline__ uint32_t xor2(uint32_t a, uint32_t b, uint32_t f) {
  uint32_t r;
  asm("lop3.b32 %0, %1, %2, %3, 0x7e;" : "=r"(r) : "r"(a), "r"(b), "r"(f));
  return r;
}
__device__ __forceinline__ bool stale(uint32_t bad, int& budget, uint32_t mask = 1) {
  uint32_t v;
  asm volatile("{\n.reg .pred p;\n.reg .b32 t;\nand.b32 t, %2, %3;\nsetp.ne.u32 p, t, 0;\nadd.s32 %1, %1, -1;\n"
               "setp.gt.and.s32 p, %1, 0, p;\nvote.sync.any.pred p, p, 0xffffffff;\nselp.u32 %0, 1, 0, p;\n}"
               : "=r"(v), "+r"(budget) : "r"(bad), "r"(mask));
  return v;
}
__device__ __forceinline__ uint32_t tag(uint32_t w, uint32_t par) {
  uint32_t r;
  asm("lop3.b32 %0, %1, %2, 1, 0xd8;" : "=r"(r) : "r"(w), "r"(par));
  return r;
}
__device__ __forceinline__ uint32_t tagf(float f, uint32_t par) { return tag(__float_as_uint(f), par); }
__device__ __forceinline__ void sts1(uint32_t a, uint32_t v) { asm volatile("st.shared.u32 [%0], %1;" ::"r"(a), "r"(v) : "memory"); }
__device__ __forceinline__ void sts_h(uint32_t a, uint32_t v) { asm volatile("st.shared.u16 [%0], %1;" ::"r"(a), "h"((uint16_t)v) : "memory"); }
__device__ __forceinline__ void sts2(uint32_t a, uint32_t x, uint32_t y) {
  asm volatile("st.shared.v2.u32 [%0], {%1,%2};" ::"r"(a), "r"(x), "r"(y) : "memory");
}
__device__ __forceinline__ void sts4(uint32_t a, uint32_t x, uint32_t y, uint32_t z, uint32_t w) {
  asm volatile("st.shared.v4.u32 [%0], {%1,%2,%3,%4};" ::"r"(a), "r"(x), "r"(y), "r"(z), "r"(w) : "memory");
}
__device__ __forceinline__ uint32_t lds1(uint32_t a) {
  uint32_t v;
  asm volatile("ld.shared.u32 %0, [%1];" : "=r"(v) : "r"(a) : "memory");
  return v;
}
__device__ __forceinline__ uint2 lds2(uint32_t a) {
  uint2 v;
  asm volatile("ld.shared.v2.u32 {%0,%1}, [%2];" : "=r"(v.x), "=r"(v.y) : "r"(a) : "memory");
  return v;
}
__device__ __forceinline__ uint4 lds4(uint32_t a) {
  uint4 v;
  asm volatile("ld.shared.v4.u32 {%0,%1,%2,%3}, [%4];" : "=r"(v.x), "=r"(v.y), "=r"(v.z), "=r"(v.w) : "r"(a) : "memory");
  return v;
}
__device__ __forceinline__ uint4 ldsm4(uint32_t a) {
  uint4 v;
  asm volatile("ldmatrix.sync.aligned.m8n8.x4.shared.b16 {%0,%1,%2,%3}, [%4];" : "=r"(v.x), "=r"(v.y), "=r"(v.z), "=r"(v.w) : "r"(a) : "memory");
  return v;
}
__device__ __forceinline__ uint4 ldsm4t(uint32_t a) {
  uint4 v;
  asm volatile("ldmatrix.sync.aligned.m8n8.x4.trans.shared.b16 {%0,%1,%2,%3}, [%4];" : "=r"(v.x), "=r"(v.y), "=r"(v.z), "=r"(v.w) : "r"(a) : "memory");
  return v;
}
__device__ __forceinline__ uint32_t pack2(float lo, float hi) {
  uint32_t r;
  asm("cvt.rn.bf16x2.f32 %0, %1, %2;" : "=r"(r) : "f"(hi), "f"(lo));
  return r;
}
__device__ __forceinline__ float bf_lo(uint32_t w) { return __uint_as_float(w << 16); }
__device__ __forceinline__ float bf_hi(uint32_t w) { return __uint_as_float(w & 0xFFFF0000u); }
__device__ __forceinline__ uint32_t sub2(uint32_t a, uint32_t b) {
  uint32_t r;
  asm("sub.rn.bf16x2 %0, %1, %2;" : "=r"(r) : "r"(a), "r"(b));
  return r;
}
__device__ __forceinline__ uint32_t sq2(uint32_t a) {
  uint32_t r;
  asm volatile("mul.rn.bf16x2 %0, %1, %1;" : "=r"(r) : "r"(a));
  return r;
}
__device__ __forceinline__ uint32_t sq2(uint32_t a, uint32_t c) {
  uint32_t r;
  asm volatile("fma.rn.bf16x2 %0, %1, %1, %2;" : "=r"(r) : "r"(a), "r"(c));
  return r;
}
__device__ __forceinline__ uint4 ldg4(const void* p) {
  uint4 v;
  asm volatile("ld.global.nc.v4.u32 {%0,%1,%2,%3}, [%4];" : "=r"(v.x), "=r"(v.y), "=r"(v.z), "=r"(v.w) : "l"(p));
  return v;
}
__device__ __forceinline__ void mma16816(float (&c)[4], uint32_t a0, uint32_t a1, uint32_t a2, uint32_t a3, uint32_t b0, uint32_t b1) {
  asm("mma.sync.aligned.m16n8k16.row.col.f32.bf16.bf16.f32 {%0,%1,%2,%3}, {%4,%5,%6,%7}, {%8,%9}, {%0,%1,%2,%3};"
      : "+f"(c[0]), "+f"(c[1]), "+f"(c[2]), "+f"(c[3]) : "r"(a0), "r"(a1), "r"(a2), "r"(a3), "r"(b0), "r"(b1));
}
__device__ __forceinline__ void mma16816z(float (&c)[4], const uint4& a, uint32_t b0, uint32_t b1) {
  asm("mma.sync.aligned.m16n8k16.row.col.f32.bf16.bf16.f32 {%0,%1,%2,%3}, {%4,%5,%6,%7}, {%8,%9}, {%10,%10,%10,%10};"
      : "=f"(c[0]), "=f"(c[1]), "=f"(c[2]), "=f"(c[3]) : "r"(a.x), "r"(a.y), "r"(a.z), "r"(a.w), "r"(b0), "r"(b1), "f"(0.f));
}
__device__ __forceinline__ float ex2f(float x) { float r; asm("ex2.approx.ftz.f32 %0, %1;" : "=f"(r) : "f"(x)); return r; }
__device__ __forceinline__ float tanhf_(float x) { float r; asm("tanh.approx.f32 %0, %1;" : "=f"(r) : "f"(x)); return r; }
__device__ __forceinline__ float rsqf(float x) { float r; asm("rsqrt.approx.ftz.f32 %0, %1;" : "=f"(r) : "f"(x)); return r; }
__device__ __forceinline__ float lg2f(float x) { float r; asm("lg2.approx.ftz.f32 %0, %1;" : "=f"(r) : "f"(x)); return r; }
__device__ __forceinline__ float rcpf(float x) { float r; asm("rcp.approx.ftz.f32 %0, %1;" : "=f"(r) : "f"(x)); return r; }
__device__ __forceinline__ float phi(float a, const float4& c) {
  return ex2f(fmaf(fminf(a, 0.f), c.x, c.y)) + fmaf(fmaxf(a, 0.f), c.z, c.w);
}
__host__ __device__ constexpr long long koff(int i, int u) { return i < 3 ? 2 * i * u : i == 3 ? 6 * u + ((6ll * u) << 32) : (2 * i - 1) * u; }
__device__ __forceinline__ float shx(float v, int m) { return __shfl_xor_sync(0xffffffffu, v, m); }
template <int V> struct IC { __host__ __device__ constexpr operator int() const { return V; } };
template <class F, int... I> __device__ __forceinline__ void sfor_impl(F&& f, std::integer_sequence<int, I...>) {
  (f(IC<I>{}), ...);
}
template <int N, class F> __device__ __forceinline__ void sfor(F&& f) { sfor_impl(f, std::make_integer_sequence<int, N>{}); }

template <long long OFF, int RO = 0, int N>
__device__ __forceinline__ void wgmma_rs_n56(float (&d)[N], const uint4& a, uint64_t base, int scale_d) {
  asm volatile("{\n.reg .pred p;\n.reg .b64 t;\nsetp.ne.b32 p, %33, 0;\nadd.s64 t, %32, %34;\n"
    "wgmma.mma_async.sync.aligned.m64n56k16.f32.bf16.bf16 {%0, %1, %2, %3, %4, %5, %6, %7, %8, %9, %10, %11, %12, %13, %14, %15, %16, %17, %18, %19, %20, %21, %22, %23, %24, %25, %26, %27}, {%28, %29, %30, %31}, t, p, 1, 1, 1;\n}\n"
    : "+f"(d[RO + 0]), "+f"(d[RO + 1]), "+f"(d[RO + 2]), "+f"(d[RO + 3]), "+f"(d[RO + 4]), "+f"(d[RO + 5]), "+f"(d[RO + 6]), "+f"(d[RO + 7]), "+f"(d[RO + 8]), "+f"(d[RO + 9]), "+f"(d[RO + 10]), "+f"(d[RO + 11]), "+f"(d[RO + 12]), "+f"(d[RO + 13]), "+f"(d[RO + 14]), "+f"(d[RO + 15]), "+f"(d[RO + 16]), "+f"(d[RO + 17]), "+f"(d[RO + 18]), "+f"(d[RO + 19]), "+f"(d[RO + 20]), "+f"(d[RO + 21]), "+f"(d[RO + 22]), "+f"(d[RO + 23]), "+f"(d[RO + 24]), "+f"(d[RO + 25]), "+f"(d[RO + 26]), "+f"(d[RO + 27])
    : "r"(a.x), "r"(a.y), "r"(a.z), "r"(a.w), "l"(base), "r"(scale_d), "n"(OFF >> 4));
}
template <long long OFF, int RO = 0, int N>
__device__ __forceinline__ void wgmma_rs_n64(float (&d)[N], const uint4& a, uint64_t base, int scale_d) {
  asm volatile("{\n.reg .pred p;\n.reg .b64 t;\nsetp.ne.b32 p, %37, 0;\nadd.s64 t, %36, %38;\n"
    "wgmma.mma_async.sync.aligned.m64n64k16.f32.bf16.bf16 {%0, %1, %2, %3, %4, %5, %6, %7, %8, %9, %10, %11, %12, %13, %14, %15, %16, %17, %18, %19, %20, %21, %22, %23, %24, %25, %26, %27, %28, %29, %30, %31}, {%32, %33, %34, %35}, t, p, 1, 1, 1;\n}\n"
    : "+f"(d[RO + 0]), "+f"(d[RO + 1]), "+f"(d[RO + 2]), "+f"(d[RO + 3]), "+f"(d[RO + 4]), "+f"(d[RO + 5]), "+f"(d[RO + 6]), "+f"(d[RO + 7]), "+f"(d[RO + 8]), "+f"(d[RO + 9]), "+f"(d[RO + 10]), "+f"(d[RO + 11]), "+f"(d[RO + 12]), "+f"(d[RO + 13]), "+f"(d[RO + 14]), "+f"(d[RO + 15]), "+f"(d[RO + 16]), "+f"(d[RO + 17]), "+f"(d[RO + 18]), "+f"(d[RO + 19]), "+f"(d[RO + 20]), "+f"(d[RO + 21]), "+f"(d[RO + 22]), "+f"(d[RO + 23]), "+f"(d[RO + 24]), "+f"(d[RO + 25]), "+f"(d[RO + 26]), "+f"(d[RO + 27]), "+f"(d[RO + 28]), "+f"(d[RO + 29]), "+f"(d[RO + 30]), "+f"(d[RO + 31])
    : "r"(a.x), "r"(a.y), "r"(a.z), "r"(a.w), "l"(base), "r"(scale_d), "n"(OFF >> 4));
}
template <long long OFF, int RO = 0, int N>
__device__ __forceinline__ void wgmma_rs_n128(float (&d)[N], const uint4& a, uint64_t base, int scale_d) {
  asm volatile("{\n.reg .pred p;\n.reg .b64 t;\nsetp.ne.b32 p, %69, 0;\nadd.s64 t, %68, %70;\n"
    "wgmma.mma_async.sync.aligned.m64n128k16.f32.bf16.bf16 {%0, %1, %2, %3, %4, %5, %6, %7, %8, %9, %10, %11, %12, %13, %14, %15, %16, %17, %18, %19, %20, %21, %22, %23, %24, %25, %26, %27, %28, %29, %30, %31, %32, %33, %34, %35, %36, %37, %38, %39, %40, %41, %42, %43, %44, %45, %46, %47, %48, %49, %50, %51, %52, %53, %54, %55, %56, %57, %58, %59, %60, %61, %62, %63}, {%64, %65, %66, %67}, t, p, 1, 1, 1;\n}\n"
    : "+f"(d[RO + 0]), "+f"(d[RO + 1]), "+f"(d[RO + 2]), "+f"(d[RO + 3]), "+f"(d[RO + 4]), "+f"(d[RO + 5]), "+f"(d[RO + 6]), "+f"(d[RO + 7]), "+f"(d[RO + 8]), "+f"(d[RO + 9]), "+f"(d[RO + 10]), "+f"(d[RO + 11]), "+f"(d[RO + 12]), "+f"(d[RO + 13]), "+f"(d[RO + 14]), "+f"(d[RO + 15]), "+f"(d[RO + 16]), "+f"(d[RO + 17]), "+f"(d[RO + 18]), "+f"(d[RO + 19]), "+f"(d[RO + 20]), "+f"(d[RO + 21]), "+f"(d[RO + 22]), "+f"(d[RO + 23]), "+f"(d[RO + 24]), "+f"(d[RO + 25]), "+f"(d[RO + 26]), "+f"(d[RO + 27]), "+f"(d[RO + 28]), "+f"(d[RO + 29]), "+f"(d[RO + 30]), "+f"(d[RO + 31]), "+f"(d[RO + 32]), "+f"(d[RO + 33]), "+f"(d[RO + 34]), "+f"(d[RO + 35]), "+f"(d[RO + 36]), "+f"(d[RO + 37]), "+f"(d[RO + 38]), "+f"(d[RO + 39]), "+f"(d[RO + 40]), "+f"(d[RO + 41]), "+f"(d[RO + 42]), "+f"(d[RO + 43]), "+f"(d[RO + 44]), "+f"(d[RO + 45]), "+f"(d[RO + 46]), "+f"(d[RO + 47]), "+f"(d[RO + 48]), "+f"(d[RO + 49]), "+f"(d[RO + 50]), "+f"(d[RO + 51]), "+f"(d[RO + 52]), "+f"(d[RO + 53]), "+f"(d[RO + 54]), "+f"(d[RO + 55]), "+f"(d[RO + 56]), "+f"(d[RO + 57]), "+f"(d[RO + 58]), "+f"(d[RO + 59]), "+f"(d[RO + 60]), "+f"(d[RO + 61]), "+f"(d[RO + 62]), "+f"(d[RO + 63])
    : "r"(a.x), "r"(a.y), "r"(a.z), "r"(a.w), "l"(base), "r"(scale_d), "n"(OFF >> 4));
}
template <int OFFA, int OFFB>
__device__ __forceinline__ void wgmma_ss_n64(float (&d)[32], uint64_t basea, uint64_t baseb, int scale_d) {
  asm volatile("{\n.reg .pred p;\n.reg .b64 t, u;\nsetp.ne.b32 p, %34, 0;\nadd.s64 t, %32, %35;\nadd.s64 u, %33, %36;\n"
    "wgmma.mma_async.sync.aligned.m64n64k16.f32.bf16.bf16 {%0, %1, %2, %3, %4, %5, %6, %7, %8, %9, %10, %11, %12, %13, %14, %15, %16, %17, %18, %19, %20, %21, %22, %23, %24, %25, %26, %27, %28, %29, %30, %31}, t, u, p, 1, 1, 1, 1;\n}\n"
    : "+f"(d[0]), "+f"(d[1]), "+f"(d[2]), "+f"(d[3]), "+f"(d[4]), "+f"(d[5]), "+f"(d[6]), "+f"(d[7]), "+f"(d[8]), "+f"(d[9]), "+f"(d[10]), "+f"(d[11]), "+f"(d[12]), "+f"(d[13]), "+f"(d[14]), "+f"(d[15]), "+f"(d[16]), "+f"(d[17]), "+f"(d[18]), "+f"(d[19]), "+f"(d[20]), "+f"(d[21]), "+f"(d[22]), "+f"(d[23]), "+f"(d[24]), "+f"(d[25]), "+f"(d[26]), "+f"(d[27]), "+f"(d[28]), "+f"(d[29]), "+f"(d[30]), "+f"(d[31])
    : "l"(basea), "l"(baseb), "r"(scale_d), "n"(OFFA >> 4), "n"(OFFB >> 4));
}

__device__ __forceinline__ void publish7(char* b16, char* b8, const uint32_t (&P)[14], uint32_t par) {
  st_rlx4(b16, tag(P[0], par), P[1], P[2], P[3]);
  st_rlx4(b16 + 512, tag(P[4], par), P[5], P[6], P[7]);
  st_rlx4(b16 + 1024, tag(P[8], par), P[9], P[10], P[11]);
  st_rlx2(b8, tag(P[12], par), P[13]);
}
template <int SOFF, int GOFF>
__device__ __forceinline__ void load7(uint4* v, uint32_t s, const char* g, uint32_t par, int& budget) {
  asm volatile("{\n.reg .pred p;\n.reg .b32 t, i, w<4>;\n.reg .b64 ga;\nsetp.eq.s32 p, %28, 0;\nC:\n@!p bra.uni L;\n"
               "add.s32 %28, %28, -1;\nmov.u32 i, %29;\nmov.u64 ga, %30;\nadd.u32 t, i, 3584;\n"
               "R:\nld.relaxed.gpu.global.v4.u32 {w0,w1,w2,w3}, [ga+%33];\nst.shared.v4.u32 [i+%32], {w0,w1,w2,w3};\n"
               "add.u32 i, i, 512;\nadd.u64 ga, ga, 512;\nsetp.ne.u32 p, i, t;\n@p bra.uni R;\nbar.warp.sync 0xffffffff;\nL:\n"
               "ld.shared.v4.u32 {%0,%1,%2,%3}, [%29+%32+0];\n"
               "ld.shared.v4.u32 {%4,%5,%6,%7}, [%29+%32+512];\n"
               "ld.shared.v4.u32 {%8,%9,%10,%11}, [%29+%32+1024];\n"
               "ld.shared.v4.u32 {%12,%13,%14,%15}, [%29+%32+1536];\n"
               "ld.shared.v4.u32 {%16,%17,%18,%19}, [%29+%32+2048];\n"
               "ld.shared.v4.u32 {%20,%21,%22,%23}, [%29+%32+2560];\n"
               "ld.shared.v4.u32 {%24,%25,%26,%27}, [%29+%32+3072];\n"
               "xor.b32 %0, %0, %31;\nxor.b32 %4, %4, %31;\nxor.b32 %8, %8, %31;\nxor.b32 %12, %12, %31;\nxor.b32 %16, %16, %31;\nxor.b32 %20, %20, %31;\nxor.b32 %24, %24, %31;\n"
               "lop3.b32 t, %0, %4, %8, 0xfe;\nlop3.b32 t, t, %12, %16, 0xfe;\nlop3.b32 t, t, %20, %24, 0xfe;\n"
               "and.b32 t, t, 1;\n"
               "setp.ne.u32 p, t, 0;\nsetp.gt.and.s32 p, %28, 0, p;\nvote.sync.any.pred p, p, 0xffffffff;\n@p bra.uni C;\n}"
               : "=r"(v[0].x), "=r"(v[0].y), "=r"(v[0].z), "=r"(v[0].w), "=r"(v[1].x), "=r"(v[1].y), "=r"(v[1].z), "=r"(v[1].w), "=r"(v[2].x), "=r"(v[2].y), "=r"(v[2].z), "=r"(v[2].w), "=r"(v[3].x), "=r"(v[3].y), "=r"(v[3].z), "=r"(v[3].w), "=r"(v[4].x), "=r"(v[4].y), "=r"(v[4].z), "=r"(v[4].w), "=r"(v[5].x), "=r"(v[5].y), "=r"(v[5].z), "=r"(v[5].w), "=r"(v[6].x), "=r"(v[6].y), "=r"(v[6].z), "=r"(v[6].w), "+r"(budget)
               : "r"(s), "l"(g), "r"(par), "n"(SOFF), "n"(GOFF) : "memory");
}
template <int SOFF, int GOFF>
__device__ __forceinline__ void load7s(uint4* v, uint32_t s, uint32_t s8, const char* g, uint32_t par, int& budget) {
  asm volatile("{\n.reg .pred p;\n.reg .b32 t, i, w<4>;\n.reg .b64 ga;\nsetp.eq.s32 p, %28, 0;\nC:\n@!p bra.uni L;\n"
               "add.s32 %28, %28, -1;\nmov.u32 i, %29;\nmov.u64 ga, %30;\nadd.u32 t, i, 3584;\n"
               "R:\nld.relaxed.gpu.global.v4.u32 {w0,w1,w2,w3}, [ga+%33];\nst.shared.v4.u32 [i+%32], {w0,w1,w2,w3};\n"
               "add.u32 i, i, 512;\nadd.u64 ga, ga, 512;\nsetp.ne.u32 p, i, t;\n@p bra.uni R;\nbar.warp.sync 0xffffffff;\nL:\n"
               "ld.shared.v4.u32 {%0,%1,%2,%3}, [%29+%32+0];\n"
               "ld.shared.v4.u32 {%4,%5,%6,%7}, [%29+%32+512];\n"
               "ld.shared.v4.u32 {%8,%9,%10,%11}, [%29+%32+1024];\n"
               "ld.shared.v2.u32 {%12,%13}, [%34+%32+1536];\nld.shared.v2.u32 {%14,%15}, [%34+%32+1792];\n"
               "ld.shared.v4.u32 {%16,%17,%18,%19}, [%29+%32+2048];\n"
               "ld.shared.v4.u32 {%20,%21,%22,%23}, [%29+%32+2560];\n"
               "ld.shared.v4.u32 {%24,%25,%26,%27}, [%29+%32+3072];\n"
               "xor.b32 %0, %0, %31;\nxor.b32 %4, %4, %31;\nxor.b32 %8, %8, %31;\nxor.b32 %12, %12, %31;\nxor.b32 %16, %16, %31;\nxor.b32 %20, %20, %31;\nxor.b32 %24, %24, %31;\nxor.b32 %14, %14, %31;\n"
               "lop3.b32 t, %0, %4, %8, 0xfe;\nlop3.b32 t, t, %12, %16, 0xfe;\nlop3.b32 t, t, %20, %24, 0xfe;\n"
               "lop3.b32 t, t, %14, 1, 0xa8;\n"
               "setp.ne.u32 p, t, 0;\nsetp.gt.and.s32 p, %28, 0, p;\nvote.sync.any.pred p, p, 0xffffffff;\n@p bra.uni C;\n}"
               : "=r"(v[0].x), "=r"(v[0].y), "=r"(v[0].z), "=r"(v[0].w), "=r"(v[1].x), "=r"(v[1].y), "=r"(v[1].z), "=r"(v[1].w), "=r"(v[2].x), "=r"(v[2].y), "=r"(v[2].z), "=r"(v[2].w), "=r"(v[3].x), "=r"(v[3].y), "=r"(v[3].z), "=r"(v[3].w), "=r"(v[4].x), "=r"(v[4].y), "=r"(v[4].z), "=r"(v[4].w), "=r"(v[5].x), "=r"(v[5].y), "=r"(v[5].z), "=r"(v[5].w), "=r"(v[6].x), "=r"(v[6].y), "=r"(v[6].z), "=r"(v[6].w), "+r"(budget)
               : "r"(s), "l"(g), "r"(par), "n"(SOFF), "n"(GOFF), "r"(s8) : "memory");
}
#define BAR(i) (sb + SMEM_BAR + 8 * (i))
#define WAIT(b, ph) mbar_wait(b, ph, budget)

template <bool SWAP>
__global__ void __launch_bounds__(384, 1)
fused_block_kernel(char* const buf, const char* __restrict__ wo, const uint64_t d128, const uint64_t d64, const uint64_t d0,
                   const uint64_t dq, const uint64_t d1,
                   const char* __restrict__ wg, const char* __restrict__ wu, const char* __restrict__ wd,
                   const __grid_constant__ CUtensorMap map_x, const __grid_constant__ CUtensorMap map_qkv,
                   const __grid_constant__ CUtensorMap map_wo, const __grid_constant__ CUtensorMap map_gu,
                   const __grid_constant__ CUtensorMap map_gu32, const __grid_constant__ CUtensorMap map_out) {
  extern __shared__ __align__(1024) uint8_t smem[];
  const int tid = threadIdx.x, lane = tid & 31;
  const int warp = __shfl_sync(0xffffffffu, tid >> 5, 0);
#define RPK 1
#define STK 0
#define MAPV 2
  const int cta = (blockIdx.x & 56) * 2 + (blockIdx.x & 1) * 8 + (blockIdx.x & 6) + (blockIdx.x >> 6), r = cta >> 3, p = cta & 7;
  const int kh = p & 1;
  const int wcol = 56 * p - 8 * kh;
  int budget = SPIN_LIMIT;
  STAMP(0);
  if (warp < 8) {
    STAMP(60);
    bar_sync<0, 384>();
    STAMP(63);
    asm volatile("setmaxnreg.inc.sync.aligned.u32 224;");
    STAMP(61);
    uint32_t e1, par;
    const int g = warp >> 2, gq = lane >> 2, tq = lane & 3;
    const uint64_t dk = d128 + kh;
    uint4 A[28];
    float rs0, rs1, m0, m1;
    uint32_t R[14];
    float acc0[28], acc1[28];
    uint32_t mb0, mb1;
    {
      const uint32_t gath = sb + OFF_GATH + warp * TILE;
      STAMP(62);
      WAIT(BAR(B_XB + warp), 0);
      STAMP(1);
      const uint32_t la = gath + (lane & 15) * 128;
#pragma unroll
      for (int ks = 0; ks < 28; ks++)
        A[ks] = ldsm4(la + (ks >> 2) * 2048 + (((2 * (ks & 3) + (lane >> 4)) ^ (lane & 7)) << 4));
#pragma unroll
      for (int j = 0; j < 7; j++) {
        const int G = 7 * p + j;
        const uint32_t a = gath + (G >> 3) * 2048 + gq * 128 + (((G & 7) ^ gq) << 4) + 4 * tq;
        R[2 * j] = lds1(a);
        R[2 * j + 1] = lds1(a + 1024);
      }
      float cs[4][4] = {};
#pragma unroll
      for (int ks = 0; ks < 28; ks++) mma16816(cs[ks & 3], A[ks].x, A[ks].y, A[ks].z, A[ks].w, 0x3F803F80u, 0x3F803F80u);
      m0 = ((cs[0][0] + cs[1][0]) + (cs[2][0] + cs[3][0])) * (1.f / DM);
      m1 = ((cs[0][2] + cs[1][2]) + (cs[2][2] + cs[3][2])) * (1.f / DM);
      mb0 = pack2(m0, m0); mb1 = pack2(m1, m1);
      asm volatile("" ::"r"(mb0), "r"(R[13]) : "memory");
      __syncwarp();
      if (lane == 0) mbar_arrive(BAR(B_XFREE));
    }
    STAMP(2);
    uint32_t pa[7];
    {
      const uint32_t prow = sb + OFF_PK + warp * 4096 + gq * 128 + (gq << 4), t = tq >> 1;
      const uint32_t b2 = (prow + ((4 * tq + 8) & 15)) ^ (t << 4);
      pa[0] = prow + 4 * tq; pa[1] = pa[0] ^ 16; pa[2] = pa[0] ^ 32;
      pa[3] = (prow + 4 * (tq & 1)) ^ (48 + 16 * t);
      pa[4] = b2 ^ 64; pa[5] = b2 ^ 80 ^ (t << 5); pa[6] = b2 ^ 96;
#pragma unroll
      for (int j = 0; j < 7; j++) asm volatile("" : "+r"(pa[j]));
    }
    uint4 sq[4];
    sfor<4>([&](auto J) {
      constexpr int j = J;
      WAIT(BAR(B_K + j), 0);
      STAMP(26 + j);
#pragma unroll
      for (int ks = 7 * j; ks < 7 * j + 7; ks++)
        A[ks] = make_uint4(sub2(A[ks].x, mb0), sub2(A[ks].y, mb1), sub2(A[ks].z, mb0), sub2(A[ks].w, mb1));
      if (j == 0 && g) bar_sync<7, 256>();
      wg_fence();
      sfor<7>([&](auto I) { wgmma_rs_n56<2 * STG + (7 * j + I) * 2048>(acc0, A[7 * j + I], dk, j + I != 0); });
      if (j == 0 && !g) bar_arrive<7, 256>();
#pragma unroll
      for (int ks = 7 * j; ks < 7 * j + 7; ks++) {
        uint4& s = sq[j];
        if (ks == 7 * j) s = make_uint4(sq2(A[ks].x), sq2(A[ks].y), sq2(A[ks].z), sq2(A[ks].w));
        else s = make_uint4(sq2(A[ks].x, s.x), sq2(A[ks].y, s.y), sq2(A[ks].z, s.z), sq2(A[ks].w, s.w));
      }
    });
    wg_commit();
    STAMP(3);
    WAIT(BAR(B_V), 0);
    STAMP(10);
    wg_fence();
    sfor<7>([&](auto I) { wgmma_rs_n56<I * 2048>(acc1, A[I], dk, I != 0); });
    wg_commit();
    WAIT(BAR(B_XFREE), 0);
    uint32_t sdw;
    {
      float c[4];
      mma16816z(c, sq[0], 0x3F803F80u, 0x3F803F80u);
#pragma unroll
      for (int i = 1; i < 4; i++) mma16816(c, sq[i].x, sq[i].y, sq[i].z, sq[i].w, 0x3F803F80u, 0x3F803F80u);
      const float d0 = m0 - bf_lo(mb0), d1 = m1 - bf_lo(mb1);
      const float q0 = fmaxf(c[0] * (1.f / DM) - d0 * d0, 0.f) + 1e-5f;
      const float q1 = fmaxf(c[2] * (1.f / DM) - d1 * d1, 0.f) + 1e-5f;
      rs0 = rsqf(q0);
      rs1 = rsqf(q1);
      const float sd = (tq & 2 ? q1 * rs1 : q0 * rs0);
      sdw = pack2(sd, sd - bf_lo(pack2(sd, 0.f)));
    }
    const float4 c0 = make_float4(rs0 * 1.4426950408889634f, lg2f(rs0), rs0 * rs0, 1e-6f * rs0);
    const float4 c1 = make_float4(rs1 * 1.4426950408889634f, lg2f(rs1), rs1 * rs1, 1e-6f * rs1);
    wg_wait<1>();
    acc_fence(acc0);
    STAMP(4);
    if (lane == 0) mbar_arrive(BAR(B_KFREE));
    sfor<7>([&](auto J) {
      constexpr int j = J;
      sfor<3>([&](auto I) {
        constexpr int ks = 7 + 3 * j + I;
        if (ks % 7 == 0) { WAIT(BAR(B_V + ks / 7), 0); STAMP(49 + ks / 7); wg_fence(); }
        wgmma_rs_n56<ks * 2048>(acc1, A[ks], dk, 1);
      });
      sts1(pa[j], pack2(phi(acc0[4 * j], c0), phi(acc0[4 * j + 1], c0)));
      sts1(pa[j] + 1024, pack2(phi(acc0[4 * j + 2], c1), phi(acc0[4 * j + 3], c1)));
    });
    wg_commit();
    if (g == 1) bar_arrive<3, 256>();
    sts1(((pa[0] & ~15u) ^ (48 + 64 * (tq & 1))) + 2048 + 8 + ((tq >> 1) << 10), sdw);
    wg_wait<0>();
    acc_fence(acc1);
    STAMP(5);
#pragma unroll
    for (int j = 0; j < 7; j++) {
      sts1(pa[j] + 2048, pack2(acc1[4 * j], acc1[4 * j + 1]));
      sts1(pa[j] + 3072, pack2(acc1[4 * j + 2], acc1[4 * j + 3]));
    }
    fence_async_smem();
    if (lane == 0) mbar_arrive(BAR(B_VFREE));
    if (g == 0) {
      bar_arrive<1, 256>();
      bar_sync<3, 256>();
    } else {
      bar_sync<1, 256>();
      float kv[32];
      wg_fence();
      sfor<8>([&](auto I) {
        constexpr int o = OFF_PK + I * 4096;
        wgmma_ss_n64<o, o + 2048>(kv, d128, d128, I != 0);
      });
      wg_commit();
      WAIT(BAR(B_INIT), 0);
      char* dst = buf + (A_KVR + p * KVR_B) + (uint32_t)((tid - 128) * 16);
      wg_wait<0>();
      acc_fence(kv);
#define S(i) (warp & 2 ? kv[16 + i] : kv[i])
      red_add4(dst, S(0), S(1), S(4));
      red_add4(dst + 2048, S(5), S(8), S(9));
      red_add4(dst + 4096, S(2), S(3), S(6));
      red_add4(dst + 6144, S(7), S(10), S(11));
      red_add4(dst + 8192, S(12), S(13), S(14));
      red_add2(dst + 10240 - (tid - 128) * 8, S(15));
    }
    STAMP(6);
    WAIT(BAR(B_Q), 0);
    wg_fence();
    sfor<28>([&](auto I) { wgmma_rs_n56<I * 2048>(acc0, A[I], dq + kh, I != 0); });
    wg_commit();
    const uint32_t wb = BAR(B_WB) + 32 * g;
    if (lane == 0) mbar_expect_tx(BAR(B_WB + warp), TILE);
    char* const oblk = buf + (A_O + (r * 2 + g) * 2 * STG + (warp & 3) * 3584);
    char* const pub16 = oblk + ((p >> 1) * TILE + kh * 2048) + (uint32_t)(lane * 16);
    char* const pub8 = oblk + ((p >> 1) * TILE + 1536 + kh * 256) + (uint32_t)(lane * 8);
    const uint32_t gsub = sb + OFF_GATH + g * 2 * STG + (warp & 3) * 3584 + lane * 16, gsub8 = gsub - lane * 8;
    const char* const olane = oblk + (uint32_t)(lane * 16);
    auto gather = [&](int cnt, int off, uint32_t free) {
      cnt_wait(&g_cnt[C_ROW + r * 32 + cnt + g], e1 * 32, budget);
      WAIT(free, 0);
      if (elect()) {
#pragma unroll 1
        for (int q = 0; q < 4; q++)
          bulk_g2s(sb + (2 + cnt) * STG + (4 * g + q) * TILE, buf + (off + (r * 8 + 4 * g + q) * TILE), TILE, wb + 8 * q);
      }
    };
    wg_wait<0>();
    acc_fence(acc0);
    STAMP(7);
    {
      uint4 Q[4];
#pragma unroll
      for (int j = 0; j < 7; j++) {
        const uint32_t lo = pack2(phi(acc0[4 * j], c0), phi(acc0[4 * j + 1], c0));
        const uint32_t hi = pack2(phi(acc0[4 * j + 2], c1), phi(acc0[4 * j + 3], c1));
        if (j & 1) { Q[j >> 1].z = lo; Q[j >> 1].w = hi; } else { Q[j >> 1].x = lo; Q[j >> 1].y = hi; }
      }
      Q[3].z = 0; Q[3].w = 0;
      STAMP(8);
      WAIT(BAR(B_KVB), 0);
      STAMP(9);
      e1 = lds1(sb + OFF_E);
      par = e1 & 1;
      float o[32];
      wg_fence();
      sfor<4>([&](auto I) { wgmma_rs_n64<OFF_KVB + I * 2048>(o, Q[I], d128, I != 0); });
      wg_commit();
      wg_wait<0>();
      acc_fence(o);
      if (lane == 0) mbar_arrive(BAR(B_OFREE));
      const float da0 = rcpf(o[28] + c0.w), db0 = rcpf(o[29] + c0.w), da1 = rcpf(o[30] + c1.w), db1 = rcpf(o[31] + c1.w);
      uint32_t P[14];
#pragma unroll
      for (int j = 0; j < 7; j++) {
        const bool first = 8 * j + 2 * tq < 28;
        const float s0 = first ? da0 : db0, s1 = first ? da1 : db1;
        P[2 * j] = pack2(o[4 * j] * s0, o[4 * j + 1] * s0);
        P[2 * j + 1] = pack2(o[4 * j + 2] * s1, o[4 * j + 3] * s1);
      }
      publish7(pub16, pub8, P, par);
      if (lane == 0) red_inc(&g_cnt[C_ROW + r * 32 + g]);
      STAMP(11);
      if ((warp & 3) == 0) {
        if (g) bar_sync<6, 64>();
        gather(0, A_O, BAR(B_OFREE));
        if (!g) bar_arrive<6, 64>();
      }
      STAMP(12);
    }
    {
      float hacc[32];
      WAIT(BAR(B_WOK), 0);
      sfor<4>([&](auto Q) {
        constexpr int q = Q;
        WAIT(wb + 8 * q, 0);
        load7s<q * TILE - 2 * STG, q * TILE>(&A[7 * q], gsub, gsub8, olane, par, budget);
        if (lane == 0) mbar_arrive(BAR(B_OR0 + q / 2) + 8 * (B_OR1 - B_OR0) * g);
        STAMP(q == 0 ? 13 : 52 + q);
        wg_fence();
        sfor<7>([&](auto I) { wgmma_rs_n64<OFF_WO + q * TILE + koff(I, 1024)>(hacc, A[7 * q + I], d128, q + I != 0); });
      });
      wg_commit();
      if (lane == 0) mbar_expect_tx(BAR(B_WB + warp), TILE);
      wg_wait<0>();
      acc_fence(hacc);
      STAMP(14);
      if (lane == 0) mbar_arrive(BAR(B_MFREE));
      m0 += hacc[28] + hacc[29]; m1 += hacc[30] + hacc[31];
      uint32_t P[14];
      float v0 = 0.f, v1 = 0.f;
#pragma unroll
      for (int j = 0; j < 7; j++) {
        float a = hacc[4 * j] + bf_lo(R[2 * j]), b = hacc[4 * j + 1] + bf_hi(R[2 * j]);
        R[2 * j] = pack2(a, b);
        a -= m0; b -= m0;
        P[2 * j] = pack2(a, b);
        v0 = fmaf(a, a, v0); v0 = fmaf(b, b, v0);
        a = hacc[4 * j + 2] + bf_lo(R[2 * j + 1]); b = hacc[4 * j + 3] + bf_hi(R[2 * j + 1]);
        R[2 * j + 1] = pack2(a, b);
        a -= m1; b -= m1;
        P[2 * j + 1] = pack2(a, b);
        v1 = fmaf(a, a, v1); v1 = fmaf(b, b, v1);
      }
      publish7(pub16 + FRAG_B, pub8 + FRAG_B, P, par);
      if (lane == 0) red_inc(&g_cnt[C_ROW + r * 32 + 2 + g]);
      v0 += shx(v0, 1); v1 += shx(v1, 1);
      v0 += shx(v0, 2); v1 += shx(v1, 2);
      if (tq == 0) st_rlx2(buf + (A_STAT + (r * 8 + warp) * 512 + p * 64) + (uint32_t)(gq * 8), tagf(v0, par), __float_as_uint(v1));
      STAMP(15);
      if ((warp & 3) == 0) gather(2, A_H, BAR(B_OR1 + 1 + g));
      STAMP(16);
    }
    char* hdst = buf + (A_HH + cta * 2 * STG + warp * 3584) + (uint32_t)(lane * 16);
    {
#define GLU(gt, up, e) fmaf((up) * (e), tanhf_((gt) * (e)), (up) * (e))
      float acc[64];
      uint4 own[5];
#pragma unroll
      for (int i = 0; i < 5; i++) asm volatile("" : "=r"(own[i].x), "=r"(own[i].y), "=r"(own[i].z), "=r"(own[i].w));
      auto stats = [&] {
        const char* st = buf + (A_STAT + (r * 8 + warp) * 512) + (uint32_t)(tq * 128 + gq * 8);
        const uint2 t0 = ld_rlx2(st), t1 = ld_rlx2(st + 64);
        own[4] = make_uint4(t0.x, t0.y, t1.x, t1.y);
      };
#pragma unroll 1
      for (int c = 0; c < 3; c++) {
        const uint32_t half = (c & 1) * 4;
        const uint64_t dc = d128 + half * (STG >> 4);
        sfor<4>([&](auto KQ) {
          constexpr int kq = KQ;
          if (c == 0) {
            WAIT(wb + 8 * kq, 1);
            load7s<kq * TILE, FRAG_B + kq * TILE>(&A[7 * kq], gsub, gsub8, olane, par, budget);
            if (lane == 0) mbar_arrive(BAR(B_HFREE + kq / 2) + 16 * g);
            if (kq == STK) stats();
          }
          if (kq > 1) {
            wg_wait<1>();
            if (lane == 0) mbar_arrive(BAR(B_EMPTY + kq - 2) + 8 * half);
          }
          WAIT(BAR(B_FULL + kq) + 8 * half, c >> 1);
          STAMP(30 + 4 * c + kq);
          wg_fence();
          sfor<7>([&](auto I) { wgmma_rs_n128<kq * STG + koff(I, 1024)>(acc, A[7 * kq + I], dc, kq + I != 0); });
          wg_commit();
        });
        wg_wait<1>();
        if (lane == 0) mbar_arrive(BAR(B_EMPTY + 2) + 8 * half);
        if (c == 0) {
#pragma unroll 1
          while (stale(xor2(own[4].x, own[4].z, par), budget)) stats();
          float v0 = __uint_as_float(own[4].x ^ par) + __uint_as_float(own[4].z ^ par), v1 = __uint_as_float(own[4].y) + __uint_as_float(own[4].w);
          v0 += shx(v0, 1); v1 += shx(v1, 1);
          v0 += shx(v0, 2); v1 += shx(v1, 2);
          rs0 = 0.5f * rsqf(v0 * (1.f / DM) + 1e-5f);
          rs1 = 0.5f * rsqf(v1 * (1.f / DM) + 1e-5f);
        }
        wg_wait<0>();
        acc_fence(acc);
        if (lane == 0) mbar_arrive(BAR(B_EMPTY + 3) + 8 * half);
        STAMP(17 + c);
        constexpr int GO = SWAP ? 32 : 0, UO = SWAP ? 0 : 32;
        own[0] = own[4];
#pragma unroll
        for (int i = 0; i < 4; i++) {
          uint32_t w[4];
#pragma unroll
          for (int t = 0; t < 2; t++) {
            const int b = 8 * i + 4 * t;
            w[2 * t] = pack2(GLU(acc[GO + b], acc[UO + b], rs0), GLU(acc[GO + b + 1], acc[UO + b + 1], rs0));
            w[2 * t + 1] = pack2(GLU(acc[GO + b + 2], acc[UO + b + 2], rs1), GLU(acc[GO + b + 3], acc[UO + b + 3], rs1));
          }
          if (i == 3 && c == 1) hdst += STG - 3584;
          own[i + 1] = make_uint4(tag(w[0], par), w[1], w[2], w[3]);
          st_rlx4(hdst + i * 512, own[i + 1].x, w[1], w[2], w[3]);
        }
        hdst += 2048;
        if (c == 1 && lane == 0) red_inc(&g_cnt[C_ROW + r * 32 + 4 + 2 * (p & 6) + g]);
      }
      float acct[32];
      sfor<2>([&](auto H) {
        constexpr int h = H;
        WAIT(BAR(B_FULL + 4 + h), 1);
        wg_fence();
        sfor<14>([&](auto I) { wgmma_rs_n64<(4 + h) * STG + I / 7 * (TILE / 2) + koff(I % 7, 512)>(acct, A[14 * h + I], d64, h + I != 0); });
        wg_commit();
      });
      wg_wait<1>();
      if (lane == 0) mbar_arrive(BAR(B_EMPTY + 4));
      wg_wait<0>();
      acc_fence(acct);
      if (lane == 0) mbar_arrive(BAR(B_EMPTY + 5));
      STAMP(20);
      constexpr int GO = SWAP ? 16 : 0, UO = SWAP ? 0 : 16;
#pragma unroll
      for (int i = 0; i < 2; i++) {
        uint32_t w[4];
#pragma unroll
        for (int t = 0; t < 2; t++) {
          const int b = 8 * i + 4 * t;
          w[2 * t] = pack2(GLU(acct[GO + b], acct[UO + b], rs0), GLU(acct[GO + b + 1], acct[UO + b + 1], rs0));
          w[2 * t + 1] = pack2(GLU(acct[GO + b + 2], acct[UO + b + 2], rs1), GLU(acct[GO + b + 3], acct[UO + b + 3], rs1));
        }
        st_rlx4(hdst + i * 512, tag(w[0], par), w[1], w[2], w[3]);
        A[5 + i] = make_uint4(w[0], w[1], w[2], w[3]);
      }
      if (lane == 0) red_inc(&g_cnt[C_ROW + r * 32 + 6 + 2 * (p & 6) + g]);
#pragma unroll
      for (int i = 0; i < 5; i++) A[i] = make_uint4(own[i].x ^ par, own[i].y, own[i].z, own[i].w);
    }
    STAMP(21);
    {
      const uint32_t tiles = sb + (6 + g) * STG + (warp & 3) * 3584;
      const char* const hnb = hdst + (1 - 2 * kh) * 2 * STG;
      auto send = [&](float (&acc)[28], int x) {
        acc_fence(acc);
        char* const pd = buf + (A_PS + ((cta ^ 2 * x) * 6 + 3 * g + x - 1) * 7168 + (warp & 3) * 1792);
        uint32_t P[14];
#pragma unroll
        for (int j = 0; j < 14; j++) P[j] = pack2(acc[2 * j], acc[2 * j + 1]);
        publish7(pd + (uint32_t)(lane * 16), pd + 1536 + (uint32_t)(lane * 8), P, par);
        if (lane < 1 + x / 3) red_inc(&g_cnt[C_PS + (cta ^ 2 * x) * 8 + g + x / 3 * 2]);
      };
      sfor<4>([&](auto K) {
        constexpr int k = K;
        if (k > 1) {
          wg_wait<1>();
          if (lane == 0) mbar_arrive(BAR(B_EMPTY + k - 2));
        }
        if (k != 2) {
          constexpr int j = k - (k == 3);
          WAIT(wb + 8 * j, 0);
          load7<(j & 1) * TILE, -2560 - (j < 2) * STG>(&A[7 * j + 7], tiles + lane * 16, j ? hnb : hdst, par, budget);
          if (lane < 2) mbar_arrive(BAR(B_HFREE + (j & 1)) + 16 * g);
        }
        WAIT(BAR(B_FULL + k), 0);
        STAMP(42 + k);
        wg_fence();
        sfor<7>([&](auto I) { wgmma_rs_n56<k * STG + I * 3584>(acc0, A[7 * k + I], d0, k + I != 0); });
        if (k == 3) wg_commit();
        sfor<7>([&](auto I) { wgmma_rs_n56<k * STG + I * 3584 + 896>(acc1, A[7 * k + I], d0, k + I != 0); });
        wg_commit();
      });
      wg_wait<1>();
      send(acc0, 1);
      sfor<4>([&](auto K) {
        constexpr int k = K, s = (k + 4) % 6;
        WAIT(BAR(B_FULL + s), k >= 2);
        STAMP(46 + k);
        wg_fence();
        sfor<7>([&](auto I) { wgmma_rs_n56<s * STG + I * 3584>(acc0, A[7 * k + I], d1, k + I != 0); });
        wg_commit();
        if (k == 0) {
          wg_wait<1>();
          send(acc1, 2);
        }
      });
      if (g) bar_arrive<7, 256>();
      wg_wait<0>();
      STAMP(22);
      send(acc0, 3);
      if (!g) bar_sync<7, 256>();
      WAIT(BAR(B_FULL + 5), 0);
      wg_fence();
      sfor<28>([&](auto I) { wgmma_rs_n56<(I / 7 + 4) % 6 * STG + I % 7 * 3584 + 896>(acc1, A[I], d1, I != 0); });
      wg_commit();
      STAMP(23);
      const uint32_t pss = sb + (6 + g) * STG + (warp & 3) * 1792;
      uint32_t P[3][14];
      auto fetch = [&](int x) {
        const uint32_t a = pss + (x < 2 ? TILE + 7168 * x : 0);
#pragma unroll
        for (int i = 0; i < 3; i++) {
          const uint4 v = lds4(a + 512 * i + lane * 16);
          P[x][4 * i] = v.x; P[x][4 * i + 1] = v.y; P[x][4 * i + 2] = v.z; P[x][4 * i + 3] = v.w;
        }
        const uint2 v = lds2(a + 1536 + lane * 8);
        P[x][12] = v.x; P[x][13] = v.y;
        const char* const ps = buf + (A_PS + (cta * 6 + 3 * g + x) * 7168 + (warp & 3) * 1792);
#pragma unroll 1
        while (stale(xor2(P[x][0], P[x][4], par) | xor2(P[x][8], P[x][12], par), budget)) {
#pragma unroll
          for (int i = 0; i < 3; i++) {
            const uint4 v = ld_rlx4(ps + 512 * i + (uint32_t)(lane * 16));
            P[x][4 * i] = v.x; P[x][4 * i + 1] = v.y; P[x][4 * i + 2] = v.z; P[x][4 * i + 3] = v.w;
          }
          const uint2 v = ld_rlx2(ps + 1536 + (uint32_t)(lane * 8));
          P[x][12] = v.x; P[x][13] = v.y;
        }
      };
      WAIT(wb + 24, 0);
      fetch(0);
      fetch(1);
      STAMP(56);
#define LO(x, j) __uint_as_float((j & 3 ? P[x][j] : P[x][j] >> 1) << (j & 3 ? 16 : 17))
#pragma unroll
      for (int j = 0; j < 14; j++) {
        acc0[2 * j] = bf_lo(R[j]) + LO(0, j) + LO(1, j);
        acc0[2 * j + 1] = bf_hi(R[j]) + bf_hi(P[0][j]) + bf_hi(P[1][j]);
      }
      WAIT(wb, 1);
      STAMP(57);
      fetch(2);
      wg_wait<0>();
      acc_fence(acc1);
      STAMP(24);
      const uint32_t ob = pss + 7168 + gq * 112 + 4 * tq;
#pragma unroll
      for (int j = 0; j < 14; j++)
        sts1(ob + 896 * (j & 1) + 16 * (j >> 1), pack2(acc1[2 * j] + acc0[2 * j] + LO(2, j), acc1[2 * j + 1] + acc0[2 * j + 1] + bf_hi(P[2][j])));
      fence_async_smem();
      __syncwarp();
      if (elect()) {
        tma_store2d(&map_out, pss + 7168, 56 * p, 128 * r + 16 * warp);
        asm volatile("cp.async.bulk.commit_group;" ::: "memory");
        asm volatile("cp.async.bulk.wait_group.read 0;" ::: "memory");
      }
      STAMP(25);
      GTIME(1);
    }
  } else {
    {
      const uint32_t c = 0x100000 - (tid < 256 + B_KVB ? 1 : tid < 256 + B_KFREE ? 4 : 8);
      if (tid < 320) sts2(BAR(tid - 256), c << 1, c << 11);
      fence_async_smem();
      bar_arrive<0, 384>();
      bar_sync<2, 128>();
#pragma unroll
      for (int i = warp - 8; i < warp; i += 4) {
        if (elect()) {
          mbar_expect_tx(BAR(B_XB + i), TILE);
          tma3d(sb + OFF_GATH + i * TILE, &map_x, 0, 128 * r + 16 * i, 0, BAR(B_XB + i));
        }
      }
      prefetch_map(&map_qkv);
    }
    STAMPP(60);
    asm volatile("setmaxnreg.dec.sync.aligned.u32 56;");
    STAMPP(63);
    if (warp == 11) {
#pragma unroll 1
      for (int j = 0; j < 8; j++) {
        if (elect()) {
          mbar_expect_tx(BAR(B_K + j), TILE);
          tma2d(sb + (j ^ 4) * TILE, &map_qkv, wcol + DM + DM * (j >> 2), 112 * (j & 3), BAR(B_K + j));
        }
      }
    }
    STAMPP(59);
    const int w = warp - 8, t = tid - 256;
    STAMPP(61);
    char* const kvr = buf + (A_KVR + p * KVR_B);
    if (t < 44) st_rlx4(kvr + (uint32_t)((r * 44 + t) * 16), 0, r * 44 + t < 640 ? 0u : 0xC1800000u, 0, 0xC1800000u);
    const uint32_t e1 = ld_rlx1(&g_epoch[cta * 32]) + 1;
    const char* wrow = wo + (min(cta, 111) * 4 + w) * (DM * 2) + lane * 16;
    const uint4 u0 = ldg4(wrow);
    uint4 u1 = make_uint4(0, 0, 0, 0);
    if (lane < 24) u1 = ldg4(wrow + 512);
    GTIME(0);
    const uint32_t par = e1 & 1;
    sts1(sb + OFF_E, e1);
    STAMPP(62);
    {
      float c[4];
      mma16816z(c, u0, 0x3F803F80u, 0x3F803F80u);
      mma16816(c, u1.x, u1.y, u1.z, u1.w, 0x3F803F80u, 0x3F803F80u);
      float s = c[0] + c[2];
      s += shx(s, 4); s += shx(s, 8); s += shx(s, 16);
      s *= 1.f / DM;
      const float hi = bf_lo(tag(pack2(s, 0.f), par));
      if (lane == 0) st_rlx1(buf + (A_WBAR + cta * 16 + w * 4), pack2(hi, s - hi));
    }
    if (smem_u32(smem) != sb) __trap();
    STAMPP(19);
    WAIT(BAR(B_XFREE), 0);
    if (w == 0 && elect()) {
        asm volatile("cp.async.bulk.prefetch.tensor.2d.L2.global [%0, {%1, %2}];" ::"l"(&map_qkv), "r"(wcol), "r"(112 * (r & 3)) : "memory");
        mbar_expect_tx(BAR(B_WO), 2 * STG);
        tma2d(sb + OFF_WO, &map_wo, 56 * p, 0, BAR(B_WO));
        tma2d(sb + OFF_WO + STG, &map_wo, 56 * p, 224, BAR(B_WO));
    }
#pragma unroll
    for (int i = 0; i < 4; i++) sts4(sb + OFF_KVB + 2048 * i + t * 16, 0, 0, 0, 0);
    const char* const kvt = kvr + (uint32_t)(t * 16);
    const char* const kvt8 = kvr + 10240 + (uint32_t)(t * 8);
    {
      uint32_t c[6];
      auto counts = [&] {
#pragma unroll
        for (int i = 0; i < 5; i++) c[i] = ld_rlx1(kvt + 2048 * i + 12);
        c[5] = ld_rlx1(kvt8 + 4);
      };
      counts();
    if (w == 0) {
      WAIT(BAR(B_KFREE), 0);
      if (elect()) {
      mbar_expect_tx(BAR(B_Q), 2 * STG);
#pragma unroll 1
      for (int j = 0; j < 4; j++) tma2d(sb + OFF_Q + j * TILE, &map_qkv, wcol, 112 * j, BAR(B_Q));
      }
    }
#pragma unroll 1
      while (stale(~(c[0] & c[1] & c[2] & c[3] & c[4] & c[5]), budget, 0x80000000u)) counts();
    }
    if (lane == 0) mbar_arrive(BAR(B_INIT));
    STAMPP(1);
    if (w == 1 && elect()) {
      prefetch_map(&map_gu);
      l2_prefetch(wg + cta * 12544, 12544);
      l2_prefetch(wu + cta * 12544, 12544);
      l2_prefetch(wd + cta * 12544, 12544);
      prefetch_map(&map_gu32); prefetch_map(&map_out);
    }
    WAIT(BAR(B_VFREE), 0);
    uint4 m = ld_rlx4(buf + A_WBAR + (uint32_t)(t * 16));
    if (w == 0) {
#pragma unroll 1
      for (int u = 0; u < 2; u++) {
        if (elect()) {
          mbar_expect_tx(BAR(B_FULL + u), STG);
          tma3d(sb + u * STG, &map_gu, 224 * p + 32 * kh, 112 * u, 0, BAR(B_FULL + u));
        }
      }
    }
    bar_sync<2, 128>();
    eq_wait(kvr + 10240 + w * 256 + 4, 0, budget);
    STAMPP(2);
    {
      uint4 v[5];
      uint2 v5;
#pragma unroll 1
      do {
#pragma unroll
        for (int i = 0; i < 5; i++) v[i] = ld_rlx4(kvt + 2048 * i);
        v5 = ld_rlx2(kvt8);
      } while (stale(or3(v[0].w, v[1].w, v[2].w) | or3(v[3].w, v[4].w, v5.y), budget, ~0u));
      STAMPP(3);
      const int gq = lane >> 2, tq = lane & 3, k = 28 * (w >> 1) + 16 * (w & 1) + gq, n = 28 * (w >> 1) + 2 * tq;
      const uint32_t row = sb + OFF_KVB + k * 128, sw = (k & 7) << 4;
      const bool lo = !(w & 1) || gq < 4;
#define F(x) __uint_as_float(x)
      const uint32_t a[4] = {pack2(F(v[0].x), F(v[0].y)), pack2(F(v[0].z), F(v[1].x)), pack2(F(v[1].y), F(v[1].z)), pack2(F(v[4].x), F(v[4].y))};
      const uint32_t b[4] = {pack2(F(v[2].x), F(v[2].y)), pack2(F(v[2].z), F(v[3].x)), pack2(F(v[3].y), F(v[3].z)), pack2(F(v[4].z), F(v5.x))};
#pragma unroll
      for (int q = 0; q < 4; q++) {
        const uint32_t ad = row + ((2 * n + 16 * q) ^ sw);
        if (q < 3 || tq < 2) {
          sts1(ad, a[q]);
          if (lo) sts1(ad + 1024, b[q]);
        }
      }
      if (tq == 2) {
        const uint32_t z = pack2(F(v[4].x) + F(v[4].y), F(v[4].z) + F(v5.x));
        const uint32_t za = __byte_perm(z, 0, w & 2 ? 0x1044 : 0x4410), zb = __byte_perm(z, 0, w & 2 ? 0x3244 : 0x4432);
        sts4(row + (112 ^ sw), za, za, za, za);
        if (lo) sts4(row + 1024 + (112 ^ sw), zb, zb, zb, zb);
      }
      fence_async_smem();
      __syncwarp();
      if (lane == 0) mbar_arrive(BAR(B_KVB));
      STAMPP(4);
    }
    {
#pragma unroll 1
      while (stale(xor2(m.x, m.y, par) | xor2(m.z, m.w, par), budget)) m = ld_rlx4(buf + A_WBAR + (uint32_t)(t * 16));
      WAIT(BAR(B_WO), 0);
      const uint32_t wa = sb + OFF_WO + t * 512 + (112 ^ ((t & 1) << 6));
      if (t < 112) {
        sts4(wa, m.x, m.x, m.x, m.x);
        sts4(wa + 128 - 16, m.y, m.y, m.y, m.y);
        sts4(wa + 256 - 32, m.z, m.z, m.z, m.z);
        sts4(wa + 384 - 48, m.w, m.w, m.w, m.w);
      }
      fence_async_smem();
      __syncwarp();
      if (lane == 0) mbar_arrive(BAR(B_WOK));
      STAMPP(6);
    }
    if (w == 0) {
#pragma unroll 1
      for (int u = 2; u < 22; u++) {
        const int s = u < 14 ? u & 7 : u < 20 ? u - 14 : u - 20;
        if (u == 14) WAIT(BAR(B_WDOK), 0);
        WAIT(BAR(B_KFREE + s) + (u >= 8 ? 64 : 0), u >= 14 && u < 20);
        STAMPP(20 + u);
        if (elect()) {
          mbar_expect_tx(BAR(B_FULL + s), u < 14 ? STG : WDS);
          if (u < 12) tma3d(sb + s * STG, &map_gu, 224 * p + 32 * kh + 64 * (u >> 2), 112 * (u & 3), 0, BAR(B_FULL + s));
          else if (u < 14) tma3d(sb + s * STG, &map_gu32, 224 * p + 192 - 192 * kh, 224 * (u - 12), 0, BAR(B_FULL + s));
          else bulk_g2s(sb + s * STG, buf + (A_WD + (p * 8 + u - 14) * WDS), WDS, BAR(B_FULL + s));
        }
      }
    } else if (w >= 2) {
      const int g = w - 2;
      WAIT(BAR(B_HFREE + RPK), 0);
      if (t < 120) {
        const int src = p ^ (r >> 2 & 1), part = (r & 1) + (~(r ^ r >> 1) & 2);
        char* zp = buf + (uint32_t)(A_WD + (p * 16 + r) * (WDS / 2) + t * 16 - 1024);
#pragma unroll 1
        for (int x = 1 + (r >> 2 & 2);; x++, zp += 896) {
          const char* wp = wd + (uint32_t)((224 * src + 32 * (src & 1) + 56 * part + (t & 7)) * 896 + (p ^ 2 * x & 7) * 112 + (t & 56) * 2);
          uint4 z[7];
#pragma unroll
          for (int i = 0; i < 7; i++) {
            if (i == 3 && part + (src & 1) == 4) wp -= 224 * 896;
            z[i] = ldg4(wp + i * 8 * 896);
          }
#pragma unroll
          for (int i = 0; i < 7; i++) st_rlx4(zp + i * 1792, z[i].x, z[i].y, z[i].z, z[i].w);
          if (!(x & 1)) break;
        }
      }
      STAMPP(5);
      asm volatile("fence.proxy.async.global;" ::: "memory");
      __syncwarp();
      if (lane == 0) asm volatile("red.release.gpu.global.add.u32 [%0], 1;" ::"l"(&g_cnt[C_WD + p * 32]) : "memory");
      STAMPP(7);
      cnt_wait<true>(&g_cnt[C_WD + p * 32], e1 * 32, budget);
      STAMPP(18);
      asm volatile("fence.proxy.async.global;" ::: "memory");
      if (lane < 2) mbar_arrive(BAR(B_WDOK));
#pragma unroll 1
      for (int j = 0; j < 5; j++) {
        const uint32_t bar = BAR(B_WB + 4 * g + (j & 3)), bytes = j < 4 ? TILE : TILE / 2;
        const char* src = buf + (j < 3 ? A_HH + ((cta ^ (j > 0)) * 2 + (j >> 1)) * STG + g * TILE : A_PS + (cta * 6 + 3 * g + 2 * j - 6) * 7168);
        if (j != 1) cnt_wait(&g_cnt[(j < 3 ? C_ROW + r * 32 + 4 + 2 * (p & 6) + j : C_PS + cta * 8 + 2 * j - 6) + g], e1 * 8, budget);
        WAIT(j >= 2 ? BAR(B_HFREE + 2 * g + (j & 1)) : BAR(B_EMPTY + 6 + g), j >> 1 & 1);
        if (elect()) {
          mbar_expect_tx(bar, bytes);
          bulk_g2s(sb + (6 + g) * STG + (j & 1) * TILE, src, bytes, bar);
        }
        STAMPP(8 + 5 * g + j);
      }
      if (g) st_rlx1(&g_epoch[cta * 32], e1);
      if (g && lane == 0) DUMP(2);
    }
  }
}

typedef CUresult (*EncodeFn)(CUtensorMap*, CUtensorMapDataType, cuuint32_t, void*, const cuuint64_t*, const cuuint64_t*,
                             const cuuint32_t*, const cuuint32_t*, CUtensorMapInterleave, CUtensorMapSwizzle,
                             CUtensorMapL2promotion, CUtensorMapFloatOOBfill);

void make_map(EncodeFn enc, CUtensorMap* m, const void* p, int rank, const cuuint64_t* gd, const cuuint64_t* gs,
              const cuuint32_t* bd, CUtensorMapSwizzle sw) {
  const cuuint32_t es[5] = {1, 1, 1, 1, 1};
  ENC_CHECK(enc(m, CU_TENSOR_MAP_DATA_TYPE_BFLOAT16, rank, (void*)p, gd, gs, bd, es, CU_TENSOR_MAP_INTERLEAVE_NONE, sw,
                CU_TENSOR_MAP_L2_PROMOTION_NONE, CU_TENSOR_MAP_FLOAT_OOB_FILL_NONE));
}

}

extern "C" void kernel_launch(void* const* d_in, const int* in_sizes, int n_in, void* d_out, int out_size) {
  (void)in_sizes; (void)n_in; (void)out_size;
  static EncodeFn enc = nullptr;
  static char* buf = nullptr;
  if (!enc) {
    void* fn = nullptr;
    cudaDriverEntryPointQueryResult qr;
    cudaGetDriverEntryPoint("cuTensorMapEncodeTiled", &fn, cudaEnableDefault, &qr);
    enc = (EncodeFn)fn;
    cudaGetSymbolAddress((void**)&buf, g_buf);
    cudaFuncSetAttribute(fused_block_kernel<false>, cudaFuncAttributeMaxDynamicSharedMemorySize, SMEM_TOTAL);
    cudaFuncSetAttribute(fused_block_kernel<true>, cudaFuncAttributeMaxDynamicSharedMemorySize, SMEM_TOTAL);
  }
  const CUtensorMapSwizzle S128 = CU_TENSOR_MAP_SWIZZLE_128B;
  CUtensorMap mx, mqkv, mwor, mgu, mgu32, mout;
  {
    cuuint64_t gd[3] = {64, SEQ, 7}, gs[2] = {DM * 2, 128};
    cuuint32_t bd[3] = {64, 16, 7};
    make_map(enc, &mx, d_in[0], 3, gd, gs, bd, S128);
  }
  {
    cuuint64_t gd[2] = {3 * DM, DM}, gs[1] = {3 * DM * 2};
    cuuint32_t bd[2] = {64, 112};
    make_map(enc, &mqkv, d_in[1], 2, gd, gs, bd, S128);
  }
  {
    cuuint64_t gd[2] = {DM, DM}, gs[1] = {DM * 2};
    cuuint32_t bd[2] = {64, 224};
    make_map(enc, &mwor, d_in[2], 2, gd, gs, bd, S128);
  }
  const char *wg = (const char*)d_in[4], *wu = (const char*)d_in[5];
  const bool swap = wu < wg;
  const char* gub = swap ? wu : wg;
  const cuuint64_t gud = swap ? (cuuint64_t)(wg - wu) : (cuuint64_t)(wu - wg);
  {
    cuuint64_t gd[3] = {FF, DM, 2}, gs[2] = {FF * 2, gud};
    cuuint32_t bd[3] = {64, 112, 2};
    make_map(enc, &mgu, gub, 3, gd, gs, bd, S128);
  }
  {
    cuuint64_t gd[3] = {FF, DM, 2}, gs[2] = {FF * 2, gud};
    cuuint32_t bd[3] = {32, 224, 2};
    make_map(enc, &mgu32, gub, 3, gd, gs, bd, CU_TENSOR_MAP_SWIZZLE_64B);
  }
  {
    cuuint64_t gd[2] = {DM, SEQ}, gs[1] = {DM * 2};
    cuuint32_t bd[2] = {56, 16};
    make_map(enc, &mout, d_out, 2, gd, gs, bd, CU_TENSOR_MAP_SWIZZLE_NONE);
  }
  (swap ? fused_block_kernel<true> : fused_block_kernel<false>)<<<128, 384, SMEM_TOTAL>>>(
      buf, (const char*)d_in[2], mn_desc(sb), mn_desc64(sb), mn_desc0(sb), mn_desc(sb + OFF_Q), mn_desc0(sb), wg, wu, (const char*)d_in[6], mx, mqkv, mwor, mgu, mgu32, mout);
}
```

```cpp
#include <cuda_runtime.h>
#include <cuda_bf16.h>
#include <cuda.h>
#include <stdint.h>
#include <stdio.h>
#include <utility>

#define SPIN_LIMIT (1 << 18)

namespace {

constexpr uint32_t sb = 1024;
constexpr int SEQ = 2048, DM = 448, FF = 1792;
constexpr int TILE = 14336;
constexpr int STG = 2 * TILE;
constexpr int SMEM_BAR = 8 * STG;
constexpr int SMEM_TOTAL = SMEM_BAR + 3072;
constexpr int OFF_GATH = 4 * STG, OFF_Q = 2 * STG, OFF_WO = 6 * STG, OFF_PK = 4 * STG, OFF_KVB = OFF_PK + 32768, OFF_E = SMEM_BAR + 512;
constexpr int B_XB = 0  , B_K = 8  , B_V = 12  , B_Q = 16, B_WO = 17, B_FULL = 18  , B_WB = 26  ,
              B_KVB = 34, B_WDOK = 35, B_WOK = 36, B_INIT = 37,
              B_KFREE = 38, B_OFREE = 39, B_QFREE = 40  , B_HFREE = 42  , B_EMPTY = 46  , B_XFREE = 54, B_VFREE = 55,
              B_ORD = 56  , B_MFREE = 60, B_HP = 61  ;

constexpr int KVR_B = 11264;
constexpr int STAT_B = 16 * 8 * 512;
constexpr int FRAG_B = 16 * 4 * STG;
constexpr int A_CNT = 0, A_EPOCH = 8192, A_KVR = A_EPOCH + 16384, A_WBAR = A_KVR + 8 * KVR_B, A_STAT = A_WBAR + 2048, A_O = A_STAT + STAT_B, A_H = A_O + FRAG_B,
              A_HH = A_H + FRAG_B;
constexpr int HH_B = 128 * 2 * STG;
constexpr int A_PS = A_HH + HH_B;
constexpr int WDS = 25088;
constexpr int A_WD = A_PS + 128 * 3 * TILE;

__device__ uint4 g_buf[(A_WD + 64 * WDS) / 16];
#define g_epoch ((unsigned*)buf + A_EPOCH / 4)
constexpr int C_ROW = 0, C_WD = 512, C_PS = 1024;
#define g_cnt ((unsigned*)buf + A_CNT / 4)
#define ENC_CHECK(x) (void)(x)
#define STAMP(i)
#define STAMPX(i)
#define GTIME(i)
#define STAMPP(i)
#define STAMPD(i)
#define DUMP(row)

__device__ __forceinline__ uint32_t smem_u32(const void* p) { return (uint32_t)__cvta_generic_to_shared(p); }
__device__ __forceinline__ void mbar_init(uint32_t bar, uint32_t cnt) {
  asm volatile("mbarrier.init.shared::cta.b64 [%0], %1;" ::"r"(bar), "r"(cnt) : "memory");
}
__device__ __forceinline__ void mbar_expect_tx(uint32_t bar, uint32_t bytes) {
  asm volatile("mbarrier.arrive.expect_tx.shared::cta.b64 _, [%0], %1;" ::"r"(bar), "r"(bytes) : "memory");
}
__device__ __forceinline__ void mbar_arrive(uint32_t bar) {
  asm volatile("mbarrier.arrive.shared::cta.b64 _, [%0];" ::"r"(bar) : "memory");
}
__device__ __forceinline__ void mbar_wait(uint32_t bar, uint32_t parity, int& budget) {
  asm volatile("{\n.reg .pred p;\nW:\nmbarrier.try_wait.parity.shared::cta.b64 p, [%1], %2;\n"
               "add.s32 %0, %0, -1;\nsetp.gt.and.s32 p, %0, 0, !p;\n@p bra W;\n}"
               : "+r"(budget) : "r"(bar), "r"(parity) : "memory");
}
__device__ __forceinline__ bool elect() {
  uint32_t v;
  asm volatile("{\n.reg .pred p;\nelect.sync _|p, 0xffffffff;\nselp.u32 %0, 1, 0, p;\n}" : "=r"(v));
  return v;
}
__device__ __forceinline__ void tma2d(uint32_t dst, const CUtensorMap* m, int c0, int c1, uint32_t bar) {
  asm volatile("cp.async.bulk.tensor.2d.shared::cluster.global.mbarrier::complete_tx::bytes [%0], [%1, {%3, %4}], [%2];"
               ::"r"(dst), "l"(m), "r"(bar), "r"(c0), "r"(c1) : "memory");
}
__device__ __forceinline__ void tma3d(uint32_t dst, const CUtensorMap* m, int c0, int c1, int c2, uint32_t bar) {
  asm volatile("cp.async.bulk.tensor.3d.shared::cluster.global.mbarrier::complete_tx::bytes [%0], [%1, {%3, %4, %5}], [%2];"
               ::"r"(dst), "l"(m), "r"(bar), "r"(c0), "r"(c1), "r"(c2) : "memory");
}
__device__ __forceinline__ void tma4d(uint32_t dst, const CUtensorMap* m, int c0, int c1, int c2, int c3, uint32_t bar) {
  asm volatile("cp.async.bulk.tensor.4d.shared::cluster.global.mbarrier::complete_tx::bytes [%0], [%1, {%3, %4, %5, %6}], [%2];"
               ::"r"(dst), "l"(m), "r"(bar), "r"(c0), "r"(c1), "r"(c2), "r"(c3) : "memory");
}
__device__ __forceinline__ void bulk_g2s(uint32_t dst, const void* src, uint32_t bytes, uint32_t bar) {
  asm volatile("cp.async.bulk.shared::cluster.global.mbarrier::complete_tx::bytes [%0], [%1], %2, [%3];"
               ::"r"(dst), "l"(src), "r"(bytes), "r"(bar) : "memory");
}
__device__ __forceinline__ void tma_store2d(const CUtensorMap* m, uint32_t src, int c0, int c1) {
  asm volatile("cp.async.bulk.tensor.2d.global.shared::cta.bulk_group [%0, {%2, %3}], [%1];"
               ::"l"(m), "r"(src), "r"(c0), "r"(c1) : "memory");
}
__device__ __forceinline__ void l2_prefetch(const void* p, uint32_t bytes) {
  asm volatile("cp.async.bulk.prefetch.L2.global [%0], %1;" ::"l"(p), "r"(bytes) : "memory");
}
__device__ __forceinline__ void prefetch_map(const CUtensorMap* m) {
  asm volatile("prefetch.tensormap [%0];" ::"l"(m) : "memory");
}
__device__ __forceinline__ void fence_async_smem() { asm volatile("fence.proxy.async.shared::cta;" ::: "memory"); }
template <int ID, int N> __device__ __forceinline__ void bar_arrive() { asm volatile("bar.arrive %0, %1;" ::"n"(ID), "n"(N) : "memory"); }
__device__ __forceinline__ void bar_sync_wg(int id) { asm volatile("bar.sync %0, 128;" ::"r"(id) : "memory"); }
template <int ID, int N> __device__ __forceinline__ void bar_sync() { asm volatile("bar.sync %0, %1;" ::"n"(ID), "n"(N) : "memory"); }
__device__ __forceinline__ void wg_fence() { asm volatile("wgmma.fence.sync.aligned;" ::: "memory"); }
__device__ __forceinline__ void wg_commit() { asm volatile("wgmma.commit_group.sync.aligned;" ::: "memory"); }
template <int N> __device__ __forceinline__ void wg_wait() { asm volatile("wgmma.wait_group.sync.aligned %0;" ::"n"(N) : "memory"); }
template <int N> __device__ __forceinline__ void acc_fence(float (&d)[N]) {
#pragma unroll
  for (int i = 0; i < N; i++) asm volatile("" : "+f"(d[i])::"memory");
}
constexpr uint64_t mn_desc(uint32_t addr) {
  return (uint64_t)((addr & 0x3FFFF) >> 4) | ((uint64_t)(TILE >> 4) << 16) | ((uint64_t)64 << 32) | ((uint64_t)1 << 62);
}
constexpr uint64_t mn_desc64(uint32_t addr) {
  return (uint64_t)((addr & 0x3FFFF) >> 4) | ((uint64_t)(TILE >> 4) << 16) | ((uint64_t)32 << 32) | ((uint64_t)2 << 62);
}
constexpr uint64_t mn_desc0(uint32_t addr) {
  return (uint64_t)((addr & 0x3FFFF) >> 4) | ((uint64_t)(1792 >> 4) << 16) | ((uint64_t)8 << 32);
}
__device__ __forceinline__ uint4 ld_rlx4(const void* p) {
  uint4 v;
  asm volatile("ld.relaxed.gpu.global.v4.u32 {%0,%1,%2,%3}, [%4];" : "=r"(v.x), "=r"(v.y), "=r"(v.z), "=r"(v.w) : "l"(p) : "memory");
  return v;
}
__device__ __forceinline__ uint2 ld_rlx2(const void* p) {
  uint2 v;
  asm volatile("ld.relaxed.gpu.global.v2.u32 {%0,%1}, [%2];" : "=r"(v.x), "=r"(v.y) : "l"(p) : "memory");
  return v;
}
__device__ __forceinline__ uint32_t ld_rlx1(const void* p) {
  uint32_t v;
  asm volatile("ld.relaxed.gpu.global.u32 %0, [%1];" : "=r"(v) : "l"(p) : "memory");
  return v;
}
__device__ __forceinline__ void st_rlx4(void* p, uint32_t a, uint32_t b, uint32_t c, uint32_t d) {
  asm volatile("st.relaxed.gpu.global.v4.u32 [%0], {%1,%2,%3,%4};" ::"l"(p), "r"(a), "r"(b), "r"(c), "r"(d) : "memory");
}
__device__ __forceinline__ void st_rlx2(void* p, uint32_t a, uint32_t b) {
  asm volatile("st.relaxed.gpu.global.v2.u32 [%0], {%1,%2};" ::"l"(p), "r"(a), "r"(b) : "memory");
}
__device__ __forceinline__ void st_rlx1(void* p, uint32_t a) {
  asm volatile("st.relaxed.gpu.global.u32 [%0], %1;" ::"l"(p), "r"(a) : "memory");
}
__device__ __forceinline__ void red_inc(unsigned* p) {
  asm volatile("red.relaxed.gpu.global.inc.u32 [%0], 0xfffffffe;" ::"l"(p) : "memory");
}
__device__ __forceinline__ void red_add4(void* p, float a, float b, float c) {
  asm volatile("red.relaxed.gpu.global.add.v4.f32 [%0], {%1,%2,%3,%4};" ::"l"(p), "f"(a), "f"(b), "f"(c), "f"(1.f) : "memory");
}
__device__ __forceinline__ void red_add2(void* p, float a) {
  asm volatile("red.relaxed.gpu.global.add.v2.f32 [%0], {%1,%2};" ::"l"(p), "f"(a), "f"(1.f) : "memory");
}
__device__ __forceinline__ void eq_wait(const void* p, uint32_t target, int& budget) {
  asm volatile("{\n.reg .pred p;\n.reg .b32 v;\nW:\nld.relaxed.gpu.global.b32 v, [%1];\nadd.s32 %0, %0, -1;\n"
               "setp.gt.s32 p, %0, 0;\nsetp.ne.and.b32 p, v, %2, p;\n@p bra W;\n}"
               : "+r"(budget) : "l"(p), "r"(target) : "memory");
}
template <bool ACQ = false>
__device__ __forceinline__ void cnt_wait(const unsigned* p, uint32_t target, int& budget) {
  if (ACQ)
    asm volatile("{\n.reg .pred p;\n.reg .s32 v;\nW:\nld.acquire.gpu.global.s32 v, [%1];\nadd.s32 %0, %0, -1;\n"
                 "setp.gt.s32 p, %0, 0;\nsub.s32 v, v, %2;\nsetp.lt.and.s32 p, v, 0, p;\n@p bra W;\n}"
                 : "+r"(budget) : "l"(p), "r"(target) : "memory");
  else
  asm volatile("{\n.reg .pred p;\n.reg .s32 v;\nW:\nld.relaxed.gpu.global.s32 v, [%1];\nadd.s32 %0, %0, -1;\n"
               "setp.gt.s32 p, %0, 0;\nsub.s32 v, v, %2;\nsetp.lt.and.s32 p, v, 0, p;\n@p bra W;\n}"
               : "+r"(budget) : "l"(p), "r"(target) : "memory");
}
__device__ __forceinline__ uint32_t or3(uint32_t a, uint32_t b, uint32_t c) {
  uint32_t r;
  asm("lop3.b32 %0, %1, %2, %3, 0xfe;" : "=r"(r) : "r"(a), "r"(b), "r"(c));
  return r;
}
__device__ __forceinline__ uint32_t xor2(uint32_t a, uint32_t b, uint32_t f) {
  uint32_t r;
  asm("lop3.b32 %0, %1, %2, %3, 0x7e;" : "=r"(r) : "r"(a), "r"(b), "r"(f));
  return r;
}
__device__ __forceinline__ bool stale(uint32_t bad, int& budget, uint32_t mask = 1) {
  uint32_t v;
  asm volatile("{\n.reg .pred p;\n.reg .b32 t;\nand.b32 t, %2, %3;\nsetp.ne.u32 p, t, 0;\nadd.s32 %1, %1, -1;\n"
               "setp.gt.and.s32 p, %1, 0, p;\nvote.sync.any.pred p, p, 0xffffffff;\nselp.u32 %0, 1, 0, p;\n}"
               : "=r"(v), "+r"(budget) : "r"(bad), "r"(mask));
  return v;
}
__device__ __forceinline__ uint32_t tag(uint32_t w, uint32_t par) {
  uint32_t r;
  asm("lop3.b32 %0, %1, %2, 1, 0xd8;" : "=r"(r) : "r"(w), "r"(par));
  return r;
}
__device__ __forceinline__ uint32_t tagf(float f, uint32_t par) { return tag(__float_as_uint(f), par); }
__device__ __forceinline__ void sts1(uint32_t a, uint32_t v) { asm volatile("st.shared.u32 [%0], %1;" ::"r"(a), "r"(v) : "memory"); }
__device__ __forceinline__ void sts_h(uint32_t a, uint32_t v) { asm volatile("st.shared.u16 [%0], %1;" ::"r"(a), "h"((uint16_t)v) : "memory"); }
__device__ __forceinline__ void sts2(uint32_t a, uint32_t x, uint32_t y) {
  asm volatile("st.shared.v2.u32 [%0], {%1,%2};" ::"r"(a), "r"(x), "r"(y) : "memory");
}
__device__ __forceinline__ void sts4(uint32_t a, uint32_t x, uint32_t y, uint32_t z, uint32_t w) {
  asm volatile("st.shared.v4.u32 [%0], {%1,%2,%3,%4};" ::"r"(a), "r"(x), "r"(y), "r"(z), "r"(w) : "memory");
}
__device__ __forceinline__ uint32_t lds1(uint32_t a) {
  uint32_t v;
  asm volatile("ld.shared.u32 %0, [%1];" : "=r"(v) : "r"(a) : "memory");
  return v;
}
__device__ __forceinline__ uint2 lds2(uint32_t a) {
  uint2 v;
  asm volatile("ld.shared.v2.u32 {%0,%1}, [%2];" : "=r"(v.x), "=r"(v.y) : "r"(a) : "memory");
  return v;
}
__device__ __forceinline__ uint4 lds4(uint32_t a) {
  uint4 v;
  asm volatile("ld.shared.v4.u32 {%0,%1,%2,%3}, [%4];" : "=r"(v.x), "=r"(v.y), "=r"(v.z), "=r"(v.w) : "r"(a) : "memory");
  return v;
}
__device__ __forceinline__ uint4 ldsm4(uint32_t a) {
  uint4 v;
  asm volatile("ldmatrix.sync.aligned.m8n8.x4.shared.b16 {%0,%1,%2,%3}, [%4];" : "=r"(v.x), "=r"(v.y), "=r"(v.z), "=r"(v.w) : "r"(a) : "memory");
  return v;
}
__device__ __forceinline__ uint4 ldsm4t(uint32_t a) {
  uint4 v;
  asm volatile("ldmatrix.sync.aligned.m8n8.x4.trans.shared.b16 {%0,%1,%2,%3}, [%4];" : "=r"(v.x), "=r"(v.y), "=r"(v.z), "=r"(v.w) : "r"(a) : "memory");
  return v;
}
__device__ __forceinline__ uint32_t pack2(float lo, float hi) {
  uint32_t r;
  asm("cvt.rn.bf16x2.f32 %0, %1, %2;" : "=r"(r) : "f"(hi), "f"(lo));
  return r;
}
__device__ __forceinline__ float bf_lo(uint32_t w) { return __uint_as_float(w << 16); }
__device__ __forceinline__ float bf_hi(uint32_t w) { return __uint_as_float(w & 0xFFFF0000u); }
__device__ __forceinline__ uint32_t sub2(uint32_t a, uint32_t b) {
  uint32_t r;
  asm volatile("sub.rn.bf16x2 %0, %1, %2;" : "=r"(r) : "r"(a), "r"(b));
  return r;
}
__device__ __forceinline__ uint32_t add2(uint32_t a, uint32_t b) {
  uint32_t r;
  asm("add.rn.bf16x2 %0, %1, %2;" : "=r"(r) : "r"(a), "r"(b));
  return r;
}
__device__ __forceinline__ uint32_t sq2(uint32_t a) {
  uint32_t r;
  asm volatile("mul.rn.bf16x2 %0, %1, %1;" : "=r"(r) : "r"(a));
  return r;
}
__device__ __forceinline__ uint32_t sq2(uint32_t a, uint32_t c) {
  uint32_t r;
  asm volatile("fma.rn.bf16x2 %0, %1, %1, %2;" : "=r"(r) : "r"(a), "r"(c));
  return r;
}
__device__ __forceinline__ uint4 ldg4(const void* p) {
  uint4 v;
  asm volatile("ld.global.nc.v4.u32 {%0,%1,%2,%3}, [%4];" : "=r"(v.x), "=r"(v.y), "=r"(v.z), "=r"(v.w) : "l"(p));
  return v;
}
__device__ __forceinline__ void mma16816(float (&c)[4], uint32_t a0, uint32_t a1, uint32_t a2, uint32_t a3, uint32_t b0, uint32_t b1) {
  asm("mma.sync.aligned.m16n8k16.row.col.f32.bf16.bf16.f32 {%0,%1,%2,%3}, {%4,%5,%6,%7}, {%8,%9}, {%0,%1,%2,%3};"
      : "+f"(c[0]), "+f"(c[1]), "+f"(c[2]), "+f"(c[3]) : "r"(a0), "r"(a1), "r"(a2), "r"(a3), "r"(b0), "r"(b1));
}
__device__ __forceinline__ void mma16816z(float (&c)[4], const uint4& a, uint32_t b0, uint32_t b1) {
  asm("mma.sync.aligned.m16n8k16.row.col.f32.bf16.bf16.f32 {%0,%1,%2,%3}, {%4,%5,%6,%7}, {%8,%9}, {%10,%10,%10,%10};"
      : "=f"(c[0]), "=f"(c[1]), "=f"(c[2]), "=f"(c[3]) : "r"(a.x), "r"(a.y), "r"(a.z), "r"(a.w), "r"(b0), "r"(b1), "f"(0.f));
}
__device__ __forceinline__ float ex2f(float x) { float r; asm("ex2.approx.ftz.f32 %0, %1;" : "=f"(r) : "f"(x)); return r; }
__device__ __forceinline__ float tanhf_(float x) { float r; asm("tanh.approx.f32 %0, %1;" : "=f"(r) : "f"(x)); return r; }
__device__ __forceinline__ float rsqf(float x) { float r; asm("rsqrt.approx.ftz.f32 %0, %1;" : "=f"(r) : "f"(x)); return r; }
__device__ __forceinline__ float lg2f(float x) { float r; asm("lg2.approx.ftz.f32 %0, %1;" : "=f"(r) : "f"(x)); return r; }
__device__ __forceinline__ float rcpf(float x) { float r; asm("rcp.approx.ftz.f32 %0, %1;" : "=f"(r) : "f"(x)); return r; }
__device__ __forceinline__ float phi(float a, const float4& c) {
  return ex2f(fmaf(fminf(a, 0.f), c.x, c.y)) + fmaf(fmaxf(a, 0.f), c.z, c.w);
}
__host__ __device__ constexpr long long koff(int i, int u) { return i < 3 ? 2 * i * u : i == 3 ? 6 * u + ((6ll * u) << 32) : (2 * i - 1) * u; }
__device__ __forceinline__ float shx(float v, int m) { return __shfl_xor_sync(0xffffffffu, v, m); }
template <int V> struct IC { __host__ __device__ constexpr operator int() const { return V; } };
template <class F, int... I> __device__ __forceinline__ void sfor_impl(F&& f, std::integer_sequence<int, I...>) {
  (f(IC<I>{}), ...);
}
template <int N, class F> __device__ __forceinline__ void sfor(F&& f) { sfor_impl(f, std::make_integer_sequence<int, N>{}); }

template <long long OFF, int RO = 0, int N>
__device__ __forceinline__ void wgmma_rs_n56(float (&d)[N], const uint4& a, uint64_t base, int scale_d) {
  asm volatile("{\n.reg .pred p;\n.reg .b64 t;\nsetp.ne.b32 p, %33, 0;\nadd.s64 t, %32, %34;\n"
    "wgmma.mma_async.sync.aligned.m64n56k16.f32.bf16.bf16 {%0, %1, %2, %3, %4, %5, %6, %7, %8, %9, %10, %11, %12, %13, %14, %15, %16, %17, %18, %19, %20, %21, %22, %23, %24, %25, %26, %27}, {%28, %29, %30, %31}, t, p, 1, 1, 1;\n}\n"
    : "+f"(d[RO + 0]), "+f"(d[RO + 1]), "+f"(d[RO + 2]), "+f"(d[RO + 3]), "+f"(d[RO + 4]), "+f"(d[RO + 5]), "+f"(d[RO + 6]), "+f"(d[RO + 7]), "+f"(d[RO + 8]), "+f"(d[RO + 9]), "+f"(d[RO + 10]), "+f"(d[RO + 11]), "+f"(d[RO + 12]), "+f"(d[RO + 13]), "+f"(d[RO + 14]), "+f"(d[RO + 15]), "+f"(d[RO + 16]), "+f"(d[RO + 17]), "+f"(d[RO + 18]), "+f"(d[RO + 19]), "+f"(d[RO + 20]), "+f"(d[RO + 21]), "+f"(d[RO + 22]), "+f"(d[RO + 23]), "+f"(d[RO + 24]), "+f"(d[RO + 25]), "+f"(d[RO + 26]), "+f"(d[RO + 27])
    : "r"(a.x), "r"(a.y), "r"(a.z), "r"(a.w), "l"(base), "r"(scale_d), "n"(OFF >> 4));
}
template <long long OFF, int RO = 0, int N>
__device__ __forceinline__ void wgmma_rs_n64(float (&d)[N], const uint4& a, uint64_t base, int scale_d) {
  asm volatile("{\n.reg .pred p;\n.reg .b64 t;\nsetp.ne.b32 p, %37, 0;\nadd.s64 t, %36, %38;\n"
    "wgmma.mma_async.sync.aligned.m64n64k16.f32.bf16.bf16 {%0, %1, %2, %3, %4, %5, %6, %7, %8, %9, %10, %11, %12, %13, %14, %15, %16, %17, %18, %19, %20, %21, %22, %23, %24, %25, %26, %27, %28, %29, %30, %31}, {%32, %33, %34, %35}, t, p, 1, 1, 1;\n}\n"
    : "+f"(d[RO + 0]), "+f"(d[RO + 1]), "+f"(d[RO + 2]), "+f"(d[RO + 3]), "+f"(d[RO + 4]), "+f"(d[RO + 5]), "+f"(d[RO + 6]), "+f"(d[RO + 7]), "+f"(d[RO + 8]), "+f"(d[RO + 9]), "+f"(d[RO + 10]), "+f"(d[RO + 11]), "+f"(d[RO + 12]), "+f"(d[RO + 13]), "+f"(d[RO + 14]), "+f"(d[RO + 15]), "+f"(d[RO + 16]), "+f"(d[RO + 17]), "+f"(d[RO + 18]), "+f"(d[RO + 19]), "+f"(d[RO + 20]), "+f"(d[RO + 21]), "+f"(d[RO + 22]), "+f"(d[RO + 23]), "+f"(d[RO + 24]), "+f"(d[RO + 25]), "+f"(d[RO + 26]), "+f"(d[RO + 27]), "+f"(d[RO + 28]), "+f"(d[RO + 29]), "+f"(d[RO + 30]), "+f"(d[RO + 31])
    : "r"(a.x), "r"(a.y), "r"(a.z), "r"(a.w), "l"(base), "r"(scale_d), "n"(OFF >> 4));
}
template <long long OFF, int RO = 0, int N>
__device__ __forceinline__ void wgmma_rs_n128(float (&d)[N], const uint4& a, uint64_t base, int scale_d) {
  asm volatile("{\n.reg .pred p;\n.reg .b64 t;\nsetp.ne.b32 p, %69, 0;\nadd.s64 t, %68, %70;\n"
    "wgmma.mma_async.sync.aligned.m64n128k16.f32.bf16.bf16 {%0, %1, %2, %3, %4, %5, %6, %7, %8, %9, %10, %11, %12, %13, %14, %15, %16, %17, %18, %19, %20, %21, %22, %23, %24, %25, %26, %27, %28, %29, %30, %31, %32, %33, %34, %35, %36, %37, %38, %39, %40, %41, %42, %43, %44, %45, %46, %47, %48, %49, %50, %51, %52, %53, %54, %55, %56, %57, %58, %59, %60, %61, %62, %63}, {%64, %65, %66, %67}, t, p, 1, 1, 1;\n}\n"
    : "+f"(d[RO + 0]), "+f"(d[RO + 1]), "+f"(d[RO + 2]), "+f"(d[RO + 3]), "+f"(d[RO + 4]), "+f"(d[RO + 5]), "+f"(d[RO + 6]), "+f"(d[RO + 7]), "+f"(d[RO + 8]), "+f"(d[RO + 9]), "+f"(d[RO + 10]), "+f"(d[RO + 11]), "+f"(d[RO + 12]), "+f"(d[RO + 13]), "+f"(d[RO + 14]), "+f"(d[RO + 15]), "+f"(d[RO + 16]), "+f"(d[RO + 17]), "+f"(d[RO + 18]), "+f"(d[RO + 19]), "+f"(d[RO + 20]), "+f"(d[RO + 21]), "+f"(d[RO + 22]), "+f"(d[RO + 23]), "+f"(d[RO + 24]), "+f"(d[RO + 25]), "+f"(d[RO + 26]), "+f"(d[RO + 27]), "+f"(d[RO + 28]), "+f"(d[RO + 29]), "+f"(d[RO + 30]), "+f"(d[RO + 31]), "+f"(d[RO + 32]), "+f"(d[RO + 33]), "+f"(d[RO + 34]), "+f"(d[RO + 35]), "+f"(d[RO + 36]), "+f"(d[RO + 37]), "+f"(d[RO + 38]), "+f"(d[RO + 39]), "+f"(d[RO + 40]), "+f"(d[RO + 41]), "+f"(d[RO + 42]), "+f"(d[RO + 43]), "+f"(d[RO + 44]), "+f"(d[RO + 45]), "+f"(d[RO + 46]), "+f"(d[RO + 47]), "+f"(d[RO + 48]), "+f"(d[RO + 49]), "+f"(d[RO + 50]), "+f"(d[RO + 51]), "+f"(d[RO + 52]), "+f"(d[RO + 53]), "+f"(d[RO + 54]), "+f"(d[RO + 55]), "+f"(d[RO + 56]), "+f"(d[RO + 57]), "+f"(d[RO + 58]), "+f"(d[RO + 59]), "+f"(d[RO + 60]), "+f"(d[RO + 61]), "+f"(d[RO + 62]), "+f"(d[RO + 63])
    : "r"(a.x), "r"(a.y), "r"(a.z), "r"(a.w), "l"(base), "r"(scale_d), "n"(OFF >> 4));
}
template <int OFFA, int OFFB>
__device__ __forceinline__ void wgmma_ss_n64(float (&d)[32], uint64_t basea, uint64_t baseb, int scale_d) {
  asm volatile("{\n.reg .pred p;\n.reg .b64 t, u;\nsetp.ne.b32 p, %34, 0;\nadd.s64 t, %32, %35;\nadd.s64 u, %33, %36;\n"
    "wgmma.mma_async.sync.aligned.m64n64k16.f32.bf16.bf16 {%0, %1, %2, %3, %4, %5, %6, %7, %8, %9, %10, %11, %12, %13, %14, %15, %16, %17, %18, %19, %20, %21, %22, %23, %24, %25, %26, %27, %28, %29, %30, %31}, t, u, p, 1, 1, 1, 1;\n}\n"
    : "+f"(d[0]), "+f"(d[1]), "+f"(d[2]), "+f"(d[3]), "+f"(d[4]), "+f"(d[5]), "+f"(d[6]), "+f"(d[7]), "+f"(d[8]), "+f"(d[9]), "+f"(d[10]), "+f"(d[11]), "+f"(d[12]), "+f"(d[13]), "+f"(d[14]), "+f"(d[15]), "+f"(d[16]), "+f"(d[17]), "+f"(d[18]), "+f"(d[19]), "+f"(d[20]), "+f"(d[21]), "+f"(d[22]), "+f"(d[23]), "+f"(d[24]), "+f"(d[25]), "+f"(d[26]), "+f"(d[27]), "+f"(d[28]), "+f"(d[29]), "+f"(d[30]), "+f"(d[31])
    : "l"(basea), "l"(baseb), "r"(scale_d), "n"(OFFA >> 4), "n"(OFFB >> 4));
}

#define PSL 60

__device__ __forceinline__ void publish7(char* b16, char* b8, const uint32_t (&P)[14], uint32_t par) {
  st_rlx4(b16, tag(P[0], par), P[1], P[2], P[3]);
  st_rlx4(b16 + 512, tag(P[4], par), P[5], P[6], P[7]);
  st_rlx4(b16 + 1024, tag(P[8], par), P[9], P[10], P[11]);
  st_rlx2(b8, tag(P[12], par), P[13]);
}
template <int GOFF>
__device__ __forceinline__ void fix7(uint4* v, const char* g, uint32_t par, int& budget) {
  asm volatile("{\n.reg .pred p;\n.reg .b32 t, w<4>;\nsetp.eq.s32 p, %28, 0;\nC:\n@!p bra.uni L;\nadd.s32 %28, %28, -1;\n"
               "ld.relaxed.gpu.global.v4.u32 {%0,%1,%2,%3}, [%29+%31+0];\n"
               "ld.relaxed.gpu.global.v4.u32 {%4,%5,%6,%7}, [%29+%31+512];\n"
               "ld.relaxed.gpu.global.v4.u32 {%8,%9,%10,%11}, [%29+%31+1024];\n"
               "ld.relaxed.gpu.global.v4.u32 {%12,%13,%14,%15}, [%29+%31+1536];\n"
               "ld.relaxed.gpu.global.v4.u32 {%16,%17,%18,%19}, [%29+%31+2048];\n"
               "ld.relaxed.gpu.global.v4.u32 {%20,%21,%22,%23}, [%29+%31+2560];\n"
               "ld.relaxed.gpu.global.v4.u32 {%24,%25,%26,%27}, [%29+%31+3072];\n"
               "L:\nlop3.b32 w0, %0, %4, %30, 0x7e;\nlop3.b32 w1, %8, %12, %30, 0x7e;\nlop3.b32 w2, %16, %20, %30, 0x7e;\nxor.b32 w3, %24, %30;\n"
               "lop3.b32 t, w0, w1, w2, 0xfe;\nlop3.b32 t, t, w3, 1, 0xa8;\n"
               "setp.ne.u32 p, t, 0;\nsetp.gt.and.s32 p, %28, 0, p;\nvote.sync.any.pred p, p, 0xffffffff;\n@p bra.uni C;\n}"
               : "+r"(v[0].x), "+r"(v[0].y), "+r"(v[0].z), "+r"(v[0].w), "+r"(v[1].x), "+r"(v[1].y), "+r"(v[1].z), "+r"(v[1].w), "+r"(v[2].x), "+r"(v[2].y), "+r"(v[2].z), "+r"(v[2].w), "+r"(v[3].x), "+r"(v[3].y), "+r"(v[3].z), "+r"(v[3].w), "+r"(v[4].x), "+r"(v[4].y), "+r"(v[4].z), "+r"(v[4].w), "+r"(v[5].x), "+r"(v[5].y), "+r"(v[5].z), "+r"(v[5].w), "+r"(v[6].x), "+r"(v[6].y), "+r"(v[6].z), "+r"(v[6].w), "+r"(budget)
               : "l"(g), "r"(par), "n"(GOFF) : "memory");
}
template <int SOFF>
__device__ __forceinline__ void load7s(uint4* v, uint32_t s, uint32_t s8) {
  asm volatile("ld.shared.v4.u32 {%0,%1,%2,%3}, [%28+%30+0];\n"
               "ld.shared.v4.u32 {%4,%5,%6,%7}, [%28+%30+512];\n"
               "ld.shared.v4.u32 {%8,%9,%10,%11}, [%28+%30+1024];\n"
               "ld.shared.v2.u32 {%12,%13}, [%29+%30+1536];\nld.shared.v2.u32 {%14,%15}, [%29+%30+1792];\n"
               "ld.shared.v4.u32 {%16,%17,%18,%19}, [%28+%30+2048];\n"
               "ld.shared.v4.u32 {%20,%21,%22,%23}, [%28+%30+2560];\n"
               "ld.shared.v4.u32 {%24,%25,%26,%27}, [%28+%30+3072];\n"
               : "=r"(v[0].x), "=r"(v[0].y), "=r"(v[0].z), "=r"(v[0].w), "=r"(v[1].x), "=r"(v[1].y), "=r"(v[1].z), "=r"(v[1].w), "=r"(v[2].x), "=r"(v[2].y), "=r"(v[2].z), "=r"(v[2].w), "=r"(v[3].x), "=r"(v[3].y), "=r"(v[3].z), "=r"(v[3].w), "=r"(v[4].x), "=r"(v[4].y), "=r"(v[4].z), "=r"(v[4].w), "=r"(v[5].x), "=r"(v[5].y), "=r"(v[5].z), "=r"(v[5].w), "=r"(v[6].x), "=r"(v[6].y), "=r"(v[6].z), "=r"(v[6].w)
               : "r"(s), "r"(s8), "n"(SOFF) : "memory");
}
template <int GOFF>
__device__ __forceinline__ void fix7s(uint4* v, const char* g, uint32_t par, int& budget) {
  asm volatile("{\n.reg .pred p;\n.reg .b32 t, w<4>;\n.reg .b64 h;\nsetp.eq.s32 p, %28, 0;\nC:\n@!p bra.uni L;\n"
               "add.s32 %28, %28, -1;\nmov.u32 t, %%laneid;\nmad.wide.s32 h, t, -8, %29;\n"
               "ld.relaxed.gpu.global.v4.u32 {%0,%1,%2,%3}, [%29+%31+0];\n"
               "ld.relaxed.gpu.global.v4.u32 {%4,%5,%6,%7}, [%29+%31+512];\n"
               "ld.relaxed.gpu.global.v4.u32 {%8,%9,%10,%11}, [%29+%31+1024];\n"
               "ld.relaxed.gpu.global.v2.u32 {%12,%13}, [h+%31+1536];\nld.relaxed.gpu.global.v2.u32 {%14,%15}, [h+%31+1792];\n"
               "ld.relaxed.gpu.global.v4.u32 {%16,%17,%18,%19}, [%29+%31+2048];\n"
               "ld.relaxed.gpu.global.v4.u32 {%20,%21,%22,%23}, [%29+%31+2560];\n"
               "ld.relaxed.gpu.global.v4.u32 {%24,%25,%26,%27}, [%29+%31+3072];\nL:\n"
               "lop3.b32 w0, %0, %4, %30, 0x7e;\nlop3.b32 w1, %8, %12, %30, 0x7e;\nlop3.b32 w2, %14, %16, %30, 0x7e;\nlop3.b32 w3, %20, %24, %30, 0x7e;\n"
               "lop3.b32 t, w0, w1, w2, 0xfe;\nlop3.b32 t, t, w3, 1, 0xa8;\n"
               "setp.ne.u32 p, t, 0;\nsetp.gt.and.s32 p, %28, 0, p;\nvote.sync.any.pred p, p, 0xffffffff;\n@p bra.uni C;\n}"
               : "+r"(v[0].x), "+r"(v[0].y), "+r"(v[0].z), "+r"(v[0].w), "+r"(v[1].x), "+r"(v[1].y), "+r"(v[1].z), "+r"(v[1].w), "+r"(v[2].x), "+r"(v[2].y), "+r"(v[2].z), "+r"(v[2].w), "+r"(v[3].x), "+r"(v[3].y), "+r"(v[3].z), "+r"(v[3].w), "+r"(v[4].x), "+r"(v[4].y), "+r"(v[4].z), "+r"(v[4].w), "+r"(v[5].x), "+r"(v[5].y), "+r"(v[5].z), "+r"(v[5].w), "+r"(v[6].x), "+r"(v[6].y), "+r"(v[6].z), "+r"(v[6].w), "+r"(budget)
               : "l"(g), "r"(par), "n"(GOFF) : "memory");
}
__device__ __forceinline__ void cnt_wait_async(const unsigned* line, uint32_t slot, uint32_t word, uint32_t target, int& budget) {
  asm volatile("{\n.reg .pred p, e;\n.reg .s32 v;\nelect.sync _|e, 0xffffffff;\nW:\n@e cp.async.cg.shared.global [%2], [%1], 16;\n"
               "ld.volatile.shared.s32 v, [%3];\nadd.s32 %0, %0, -1;\nsetp.gt.s32 p, %0, 0;\n"
               "sub.s32 v, v, %4;\nsetp.lt.and.s32 p, v, 0, p;\n@p bra.uni W;\n}"
               : "+r"(budget) : "l"(line), "r"(slot), "r"(word), "r"(target) : "memory");
}
#define BAR(i) (sb + SMEM_BAR + 8 * (i))
#define WAIT(b, ph) mbar_wait(b, ph, budget)

template <bool SWAP>
__global__ void __launch_bounds__(384, 1)
fused_block_kernel(char* const buf, const char* __restrict__ wo, const uint64_t d128, const uint64_t d64, const uint64_t d0,
                   const uint64_t dq, const uint64_t d1,
                   const char* __restrict__ wg, const char* __restrict__ wu, const char* __restrict__ wd, const char* __restrict__ wq, char* __restrict__ out,
                   const __grid_constant__ CUtensorMap map_x, const __grid_constant__ CUtensorMap map_qkv,
                   const __grid_constant__ CUtensorMap map_wo, const __grid_constant__ CUtensorMap map_gu,
                   const __grid_constant__ CUtensorMap map_gu32, const __grid_constant__ CUtensorMap map_out) {
  extern __shared__ __align__(1024) uint8_t smem[];
  const int tid = threadIdx.x, lane = tid & 31;
  const int warp = __shfl_sync(0xffffffffu, tid >> 5, 0);
#define QPF 1
#define WDL 0
#define HSPLIT 4
#define GSPLIT 6
#define ODLY 500
#define GEARLY 0
#define W4G 1
#define CH23 1
#define W23 2
#define CRED 1
#define NPOLL 1
#define PST 200
#define HD 100
#define OD 200
#define HORD 1
#define GORD 4
#define GGATE 1
#define SQV 1
#define NBK 2
#define PA 21
#define PF 21
#define OUTV 1
#define KSCH 1
#define SJ 2
#define W01 0
#define FL 0
#define WOPOS 0
#define EARLY 0
#define KVP 2
#define RPK 1
#define STK 1
#define MAPV 2
  const int cta = (blockIdx.x & 56) * 2 + (blockIdx.x & 1) * 8 + (blockIdx.x & 6) + (blockIdx.x >> 6), r = cta >> 3, p = cta & 7;
  const int kh = p & 1;
  const int wcol = 56 * p - 8 * kh;
  int budget = SPIN_LIMIT;
  STAMP(0);
  if (warp < 8) {
    STAMP(60);
    const uint32_t par = ~ld_rlx1(&g_epoch[cta * 32]) & 1;
    bar_sync<0, 384>();
    STAMP(63);
    asm volatile("setmaxnreg.inc.sync.aligned.u32 224;");
    STAMP(61);
    const int g = warp >> 2, gq = lane >> 2, tq = lane & 3;
    const uint64_t dk = d128 + kh;
    uint4 A[28];
    float rs0, rs1, m0, m1;
    uint32_t R[14];
    float acc0[28], acc1[28];
    uint32_t mb0, mb1;
    {
      const uint32_t gath = sb + OFF_GATH + warp * TILE;
      STAMP(62);
      WAIT(BAR(B_XB + warp), 0);
      STAMP(1);
      const uint32_t la = gath + (lane & 15) * 128;
#pragma unroll
      for (int ks = 0; ks < 28; ks++)
        A[ks] = ldsm4(la + (ks >> 2) * 2048 + (((2 * (ks & 3) + (lane >> 4)) ^ (lane & 7)) << 4));
#pragma unroll
      for (int j = 0; j < 7; j++) {
        const int G = 7 * p + j;
        const uint32_t a = gath + (G >> 3) * 2048 + gq * 128 + (((G & 7) ^ gq) << 4) + 4 * tq;
        R[2 * j] = lds1(a);
        R[2 * j + 1] = lds1(a + 1024);
      }
      float cs[4][4] = {};
#pragma unroll
      for (int ks = 0; ks < 28; ks++) mma16816(cs[ks & 3], A[ks].x, A[ks].y, A[ks].z, A[ks].w, 0x3F803F80u, 0x3F803F80u);
      m0 = ((cs[0][0] + cs[1][0]) + (cs[2][0] + cs[3][0])) * (1.f / DM);
      m1 = ((cs[0][2] + cs[1][2]) + (cs[2][2] + cs[3][2])) * (1.f / DM);
      mb0 = pack2(m0, m0); mb1 = pack2(m1, m1);
      asm volatile("" ::"r"(mb0), "r"(R[13]) : "memory");
      __syncwarp();
      if (lane == 0) mbar_arrive(BAR(B_XFREE));
    }
    STAMP(2);
    uint32_t pa[7];
    {
      const uint32_t prow = sb + OFF_PK + warp * 4096 + gq * 128 + (gq << 4), t = tq >> 1;
      const uint32_t b2 = (prow + ((4 * tq + 8) & 15)) ^ (t << 4);
      pa[0] = prow + 4 * tq; pa[1] = pa[0] ^ 16; pa[2] = pa[0] ^ 32;
      pa[3] = (prow + 4 * (tq & 1)) ^ (48 + 16 * t);
      pa[4] = b2 ^ 64; pa[5] = b2 ^ 80 ^ (t << 5); pa[6] = b2 ^ 96;
#pragma unroll
      for (int j = 0; j < 7; j++) asm volatile("" : "+r"(pa[j]));
    }
    auto sqs = [&](int q) {
      uint4 s;
#pragma unroll
      for (int ks = 7 * q; ks < 7 * q + 7; ks++) {
        if (ks % 7 == 0) s = make_uint4(sq2(A[ks].x), sq2(A[ks].y), sq2(A[ks].z), sq2(A[ks].w));
        else s = make_uint4(sq2(A[ks].x, s.x), sq2(A[ks].y, s.y), sq2(A[ks].z, s.z), sq2(A[ks].w, s.w));
      }
      s.x = add2(s.x, s.z);
      s.y = add2(s.y, s.w);
      rs0 = (q ? rs0 : 0.f) + (bf_lo(s.x) + bf_hi(s.x));
      rs1 = (q ? rs1 : 0.f) + (bf_lo(s.y) + bf_hi(s.y));
      if (q == 3) {
        rs0 += shx(rs0, 1); rs1 += shx(rs1, 1);
        rs0 += shx(rs0, 2); rs1 += shx(rs1, 2);
      }
      asm volatile("" : "+f"(rs0), "+f"(rs1));
    };
    auto sub = [&](int q) {
#pragma unroll
      for (int ks = 7 * q; ks < 7 * q + 7; ks++)
        A[ks] = make_uint4(sub2(A[ks].x, mb0), sub2(A[ks].y, mb1), sub2(A[ks].z, mb0), sub2(A[ks].w, mb1));
    };
    uint32_t sdw;
    float4 c0, c1;
    auto stats = [&] {
      const float d0 = m0 - bf_lo(mb0), d1 = m1 - bf_lo(mb1);
      const float q0 = fmaxf(rs0 * (1.f / DM) - d0 * d0, 0.f) + 1e-5f;
      const float q1 = fmaxf(rs1 * (1.f / DM) - d1 * d1, 0.f) + 1e-5f;
      rs0 = rsqf(q0);
      rs1 = rsqf(q1);
      const float sd = (tq & 2 ? q1 * rs1 : q0 * rs0);
      sdw = pack2(sd, sd - bf_lo(pack2(sd, 0.f)));
      c0 = make_float4(rs0 * 1.4426950408889634f, lg2f(rs0), rs0 * rs0, 1e-6f * rs0);
      c1 = make_float4(rs1 * 1.4426950408889634f, lg2f(rs1), rs1 * rs1, 1e-6f * rs1);
      asm volatile("" : "+r"(sdw), "+f"(c0.x), "+f"(c0.y), "+f"(c0.z), "+f"(c0.w), "+f"(c1.x), "+f"(c1.y), "+f"(c1.z), "+f"(c1.w));
    };
    sub(0);
    sub(1);
    sqs(0);
    if (KSCH >= 2) { sub(2); sqs(1); }
    if (KSCH >= 3) { sub(3); sqs(2); }
    if (KSCH >= 4) { sqs(3); stats(); }
    sfor<4>([&](auto J) {
      constexpr int j = J;
      WAIT(BAR(B_K + j), 0);
      STAMP(26 + j);
      if (j == 0 && g) bar_sync<7, 256>();
      wg_fence();
      sfor<7>([&](auto I) { wgmma_rs_n56<2 * STG + (7 * j + I) * 2048>(acc0, A[7 * j + I], dk, j + I != 0); });
      if (j == 0 && !g) bar_arrive<7, 256>();
      if (j + KSCH < 3) sub(j + KSCH + 1);
      if (j + KSCH < 4) sqs(j + KSCH);
      if (j + KSCH == 3) stats();
    });
    wg_commit();
    STAMP(3);
    WAIT(BAR(B_V), 0);
    STAMP(10);
    wg_fence();
    sfor<7>([&](auto I) { wgmma_rs_n56<I * 2048>(acc1, A[I], dk, I != 0); });
    wg_commit();
    WAIT(BAR(B_XFREE), 0);
    wg_wait<1>();
    acc_fence(acc0);
    STAMP(4);
    if (lane == 0) mbar_arrive(BAR(B_KFREE));
    sfor<7>([&](auto J) {
      constexpr int j = J;
      sfor<3>([&](auto I) {
        constexpr int ks = 7 + 3 * j + I;
        if (ks % 7 == 0) { WAIT(BAR(B_V + ks / 7), 0); STAMP(49 + ks / 7); wg_fence(); }
        wgmma_rs_n56<ks * 2048>(acc1, A[ks], dk, 1);
      });
      sts1(pa[j], pack2(phi(acc0[4 * j], c0), phi(acc0[4 * j + 1], c0)));
      sts1(pa[j] + 1024, pack2(phi(acc0[4 * j + 2], c1), phi(acc0[4 * j + 3], c1)));
    });
    wg_commit();
    if (g == 1) bar_arrive<3, 256>();
    sts1(((pa[0] & ~15u) ^ (48 + 64 * (tq & 1))) + 2048 + 8 + ((tq >> 1) << 10), sdw);
    wg_wait<0>();
    acc_fence(acc1);
    STAMP(5);
#pragma unroll
    for (int j = 0; j < 7; j++) {
      sts1(pa[j] + 2048, pack2(acc1[4 * j], acc1[4 * j + 1]));
      sts1(pa[j] + 3072, pack2(acc1[4 * j + 2], acc1[4 * j + 3]));
    }
    fence_async_smem();
    if (lane == 0) mbar_arrive(BAR(B_VFREE));
    if (g == 0) {
      bar_arrive<1, 256>();
      bar_sync<3, 256>();
    } else {
      bar_sync<1, 256>();
      float kv[32];
      wg_fence();
      sfor<8>([&](auto I) {
        constexpr int o = OFF_PK + I * 4096;
        wgmma_ss_n64<o, o + 2048>(kv, d128, d128, I != 0);
      });
      wg_commit();
      WAIT(BAR(B_INIT), 0);
      char* dst = buf + (A_KVR + p * KVR_B) + (uint32_t)((tid - 128) * 16);
      wg_wait<0>();
      acc_fence(kv);
#define S(i) (warp & 2 ? kv[16 + i] : kv[i])
      red_add4(dst, S(0), S(1), S(4));
      red_add4(dst + 2048, S(5), S(8), S(9));
      red_add4(dst + 4096, S(2), S(3), S(6));
      red_add4(dst + 6144, S(7), S(10), S(11));
      red_add4(dst + 8192, S(12), S(13), S(14));
      red_add2(dst + 10240 - (tid - 128) * 8, S(15));
    }
    STAMP(6);
    WAIT(BAR(B_Q), 0);
    wg_fence();
    sfor<28>([&](auto I) { wgmma_rs_n56<I * 2048>(acc0, A[I], dq + kh, I != 0); });
    wg_commit();
    const uint32_t wb = BAR(B_WB) + 32 * g;
    char* const oblk = buf + (A_O + (r * 2 + g) * 2 * STG + (warp & 3) * 3584);
    char* const pub16 = oblk + ((p >> 1) * TILE + kh * 2048) + (uint32_t)(lane * 16);
    char* const pub8 = oblk + ((p >> 1) * TILE + 1536 + kh * 256) + (uint32_t)(lane * 8);
    uint32_t gsub = sb + OFF_GATH + (warp & 3) * 3584 + lane * 16, gsub8 = gsub - lane * 8;
    const char* const olane = oblk + (uint32_t)(lane * 16);
    wg_wait<0>();
    acc_fence(acc0);
    STAMP(7);
    if (lane < 2) mbar_arrive(BAR(B_QFREE + lane));
    {
      uint4 Q[4];
#pragma unroll
      for (int j = 0; j < 7; j++) {
        const uint32_t lo = pack2(phi(acc0[4 * j], c0), phi(acc0[4 * j + 1], c0));
        const uint32_t hi = pack2(phi(acc0[4 * j + 2], c1), phi(acc0[4 * j + 3], c1));
        if (j & 1) { Q[j >> 1].z = lo; Q[j >> 1].w = hi; } else { Q[j >> 1].x = lo; Q[j >> 1].y = hi; }
      }
      Q[3].z = 0; Q[3].w = 0;
      STAMP(8);
      WAIT(BAR(B_KVB), 0);
      STAMP(9);
      if (!CRED && lane == 0) mbar_arrive(BAR(B_MFREE));
      if (CRED == 2 && lane == 0) red_inc(&g_cnt[C_ROW + r * 32]);
      float o[32];
      wg_fence();
      sfor<4>([&](auto I) { wgmma_rs_n64<OFF_KVB + I * 2048>(o, Q[I], d128, I != 0); });
      wg_commit();
      wg_wait<0>();
      acc_fence(o);
      if (lane == 0) mbar_arrive(BAR(B_OFREE));
      if (CRED == 1 && lane == 0) red_inc(&g_cnt[C_ROW + r * 32]);
      const float da0 = rcpf(o[28] + c0.w), db0 = rcpf(o[29] + c0.w), da1 = rcpf(o[30] + c1.w), db1 = rcpf(o[31] + c1.w);
      uint32_t P[14];
#pragma unroll
      for (int j = 0; j < 7; j++) {
        const bool first = 8 * j + 2 * tq < 28;
        const float s0 = first ? da0 : db0, s1 = first ? da1 : db1;
        P[2 * j] = pack2(o[4 * j] * s0, o[4 * j + 1] * s0);
        P[2 * j + 1] = pack2(o[4 * j + 2] * s1, o[4 * j + 3] * s1);
      }
      if (g) {
        const uint32_t t0 = clock();
        while ((uint32_t)clock() - t0 < ODLY);
      }
      publish7(pub16, pub8, P, par);
      STAMP(11);
    }
    {
      float hacc[32];
#pragma unroll
      for (int j = 0; j < 14; j++) {
        hacc[2 * j] = bf_lo(R[j]) - (j & 1 ? m1 : m0);
        hacc[2 * j + 1] = bf_hi(R[j]) - (j & 1 ? m1 : m0);
      }
      hacc[28] = hacc[29] = hacc[30] = hacc[31] = 0.f;
      acc_fence(hacc);
      WAIT(wb, 0);
      STAMP(12);
      load7s<0>(A, gsub, gsub8);
      sfor<4>([&](auto Q) {
        constexpr int q = Q;
        if (HORD < 2 && q < 3 && (q || !HORD)) {
          WAIT(wb + 8 * q + 8, 0);
          load7s<(q + 1) * TILE>(&A[7 * (q + 1) % 28], gsub, gsub8);
        }
        fix7s<q * TILE>(&A[7 * q], olane, par, budget);
        if (lane < 2) mbar_arrive(BAR(B_ORD + q));
        if (HORD == 2 && q < 3) {
          WAIT(wb + 8 * q + 8, 0);
          load7s<(q + 1) * TILE>(&A[7 * (q + 1) % 28], gsub, gsub8);
        }
        STAMP(q == 0 ? 13 : 52 + q);
        wg_fence();
        sfor<7>([&](auto I) { wgmma_rs_n64<OFF_WO + q * TILE + koff(I, 1024)>(hacc, A[7 * q + I], d128, 1); });
        if (HORD == 1 && q == 0) {
          WAIT(wb + 8, 0);
          load7s<TILE>(&A[7], gsub, gsub8);
        }
      });
      wg_commit();
      if (g) bar_sync<6, 160>();
      if (!CRED && lane < 2) mbar_arrive(BAR(B_HP + g));
      if (CRED && lane == 0) red_inc(&g_cnt[C_ROW + r * 32 + 2 + g]);
      wg_wait<0>();
      acc_fence(hacc);
      STAMP(14);
      if (lane == 0) mbar_arrive(BAR(B_OFREE));
      const float dm0 = hacc[28] + hacc[29], dm1 = hacc[30] + hacc[31];
      uint32_t P[14];
#pragma unroll
      for (int j = 0; j < 28; j++) hacc[j] -= j & 2 ? dm1 : dm0;
#pragma unroll
      for (int j = 0; j < 14; j++) P[j] = pack2(hacc[2 * j], hacc[2 * j + 1]);
      publish7(pub16 + FRAG_B, pub8 + FRAG_B, P, par);
      STAMP(15);
      WAIT(BAR(B_KVB), 0);
      acc_fence(hacc);
      m0 += dm0; m1 += dm1;
#pragma unroll
      for (int j = 0; j < 14; j++) R[j] = pack2(hacc[2 * j] + (j & 1 ? m1 : m0), hacc[2 * j + 1] + (j & 1 ? m1 : m0));
      STAMP(16);
    }
    char* hdst = buf + (A_HH + cta * 2 * STG + warp * 3584) + (uint32_t)(lane * 16);
    {
#define GLU(gt, up, e) fmaf((up) * (e), tanhf_((gt) * (e)), (up) * (e))
      float acc[64];
      uint4 own[5];
#pragma unroll
      for (int i = 0; i < 5; i++) asm volatile("" : "=r"(own[i].x), "=r"(own[i].y), "=r"(own[i].z), "=r"(own[i].w));
      gsub += g * 2 * STG;
      gsub8 += g * 2 * STG;
      WAIT(wb, 1);
      STAMP(58);
      load7s<0>(A, gsub, gsub8);
#pragma unroll 1
      for (int c = 0; c < 3; c++) {
        const uint32_t half = (c & 1) * 4;
        const uint64_t dc = d128 + half * (STG >> 4);
        if (GGATE && c == 1) WAIT(BAR(B_HFREE + 3), 0);
        sfor<4>([&](auto KQ) {
          constexpr int kq = KQ;
          auto ld = [&](auto Q) {
            WAIT(wb + 8 * Q, 1);
            load7s<Q * TILE>(&A[7 * Q], gsub, gsub8);
          };
          auto fx = [&](auto Q) {
            fix7s<FRAG_B + Q * TILE>(&A[7 * Q], olane, par, budget);
            if (Q & 1) if (lane < 1 + g) mbar_arrive(BAR(B_HFREE + Q / 2) + 16 * g);
          };
          if (GORD < 2 && c == 0 && kq < 2) {
            if (kq == GORD) ld(IC<1>{});
            if (kq == 1 && GORD == 0) { ld(IC<2>{}); ld(IC<3>{}); }
            fx(KQ);
          }
          if (GORD >= 4 && c == 0) {
            if (GORD == 4 || kq < 3) fx(KQ);
            if (GORD == 5 && kq == 2) fx(IC<3>{});
            if (kq < (GORD != 5 ? 3 : 2)) ld(IC<(kq + 1) % 4>{});
            if (GORD == 5 && kq == 1) ld(IC<3>{});
            if (W4G == 2 + kq && g && lane < 2) mbar_arrive(BAR(B_HFREE + lane));
          }
          if ((GORD == 2 || GORD == 3) && c == 0 && kq < 3) {
            ld(IC<kq + 1>{});
            if (W4G == 2 + kq && g && lane < 2) mbar_arrive(BAR(B_HFREE + lane));
            if (kq && GORD == 2) sqs(kq - 1);
            fx(KQ);
            if (kq == 2) fx(IC<3>{});
          }
          WAIT(BAR(B_FULL + kq) + 8 * half, c >> 1);
          STAMPD(30 + 4 * c + kq);
          wg_fence();
          sfor<7>([&](auto I) { wgmma_rs_n128<kq * STG + koff(I, 1024)>(acc, A[7 * kq + I], dc, kq + I != 0); });
          wg_commit();
          if (GORD < 2 && c == 0 && kq == 1) {
            if (GORD == 1) { ld(IC<2>{}); ld(IC<3>{}); }
            fx(IC<2>{});
            fx(IC<3>{});
          }
          if (c == 0 && (SQV || kq > (GORD == 2 ? 2 : 1))) {
            if (GORD == 6 && kq == 2) fx(IC<3>{});
            if (SQV == 1) sqs(kq);
            else if (SQV == 2) { if (kq == 0) sqs(0); if (kq == 3) { sqs(1); sqs(2); sqs(3); } }
            else {
              sqs(2 * kq - 4);
              sqs(2 * kq - 3);
            }
            if (kq == 3) {
              rs0 = 0.5f * rsqf(rs0 * (1.f / DM) + 1e-5f);
              rs1 = 0.5f * rsqf(rs1 * (1.f / DM) + 1e-5f);
            }
          }
          if (kq > 0) {
            wg_wait<1>();
            if (lane == 0) mbar_arrive(BAR(B_EMPTY + kq - 1) + 8 * half);
          }
        });
        wg_wait<0>();
        acc_fence(acc);
        if (lane == 0) mbar_arrive(BAR(B_EMPTY + 3) + 8 * half);
        STAMPD(17 + c);
        constexpr int GO = SWAP ? 32 : 0, UO = SWAP ? 0 : 32;
        own[0] = own[4];
#pragma unroll
        for (int i = 0; i < 4; i++) {
          uint32_t w[4];
#pragma unroll
          for (int t = 0; t < 2; t++) {
            const int b = 8 * i + 4 * t;
            w[2 * t] = pack2(GLU(acc[GO + b], acc[UO + b], rs0), GLU(acc[GO + b + 1], acc[UO + b + 1], rs0));
            w[2 * t + 1] = pack2(GLU(acc[GO + b + 2], acc[UO + b + 2], rs1), GLU(acc[GO + b + 3], acc[UO + b + 3], rs1));
          }
          if (i == 3 && c == 1) hdst += STG - 3584;
          own[i + 1] = make_uint4(tag(w[0], par), w[1], w[2], w[3]);
          st_rlx4(hdst + i * 512, own[i + 1].x, w[1], w[2], w[3]);
        }
        hdst += 2048;
        if (c == 1 && lane == 0) red_inc(&g_cnt[C_ROW + r * 32 + 4 + 2 * (p & 6) + g]);
      }
      float acct[32];
      sfor<2>([&](auto H) {
        constexpr int h = H;
        WAIT(BAR(B_FULL + 4 + h), 1);
        wg_fence();
        sfor<14>([&](auto I) { wgmma_rs_n64<(4 + h) * STG + I / 7 * (TILE / 2) + koff(I % 7, 512)>(acct, A[14 * h + I], d64, h + I != 0); });
        wg_commit();
      });
      wg_wait<1>();
      if (lane == 0) mbar_arrive(BAR(B_EMPTY + 4));
      wg_wait<0>();
      acc_fence(acct);
      if (lane == 0) mbar_arrive(BAR(B_EMPTY + 5));
      STAMP(20);
      constexpr int GO = SWAP ? 16 : 0, UO = SWAP ? 0 : 16;
#pragma unroll
      for (int i = 0; i < 2; i++) {
        uint32_t w[4];
#pragma unroll
        for (int t = 0; t < 2; t++) {
          const int b = 8 * i + 4 * t;
          w[2 * t] = pack2(GLU(acct[GO + b], acct[UO + b], rs0), GLU(acct[GO + b + 1], acct[UO + b + 1], rs0));
          w[2 * t + 1] = pack2(GLU(acct[GO + b + 2], acct[UO + b + 2], rs1), GLU(acct[GO + b + 3], acct[UO + b + 3], rs1));
        }
        st_rlx4(hdst + i * 512, tag(w[0], par), w[1], w[2], w[3]);
        A[5 + i] = make_uint4(w[0], w[1], w[2], w[3]);
      }
#pragma unroll
      for (int i = 0; i < 5; i++) A[i] = own[i];
    }
    STAMP(21);
    {
      const char* const hnb = hdst + (1 - 2 * kh) * 2 * STG;
      auto send = [&](float (&acc)[28], int x) {
        acc_fence(acc);
        char* const pd = buf + (A_PS + ((cta ^ 2 * x) * 6 + 3 * g + x - 1) * 7168 + (warp & 3) * 1792);
        uint32_t P[14];
#pragma unroll
        for (int j = 0; j < 14; j++) P[j] = pack2(acc[2 * j], acc[2 * j + 1]);
        publish7(pd + (uint32_t)(lane * 16), pd + 1536 + (uint32_t)(lane * 8), P, par);
        if (x < 3 && lane == 0) red_inc(&g_cnt[C_PS + (cta ^ 2 * x) * 8 + g]);
      };
      sfor<4>([&](auto K) {
        constexpr int k = K;
        if (k > 1) {
          wg_wait<1>();
          if (lane == 0) mbar_arrive(BAR(B_EMPTY + k - 2));
        }
        if (k) fix7<-2560 - (k < 3) * STG>(&A[7 * k], k > 1 ? hnb : hdst, par, budget);
        if (k == 2 && lane < 2) mbar_arrive(BAR(B_HFREE + 1) + 16 * g);
        if (k < 2) {
          WAIT(wb + 8 * k, 0);
#pragma unroll
          for (int i = 0; i < 7; i++) A[7 * k + 7 + i] = lds4(gsub + (2 - g) * STG + k * TILE + i * 512);
        }
        if (k == NBK) {
#pragma unroll
          for (int i = 0; i < 7; i++) A[21 + i] = ld_rlx4(hnb - 2560 + 512 * i);
        }
        WAIT(BAR(B_FULL + k), 0);
        STAMP(42 + k);
        wg_fence();
        sfor<7>([&](auto I) { wgmma_rs_n56<k * STG + I * 3584>(acc0, A[7 * k + I], d0, k + I != 0); });
        if (k == 3) wg_commit();
        sfor<7>([&](auto I) { wgmma_rs_n56<k * STG + I * 3584 + 896>(acc1, A[7 * k + I], d0, k + I != 0); });
        wg_commit();
      });
      wg_wait<1>();
      send(acc0, 1);
      sfor<4>([&](auto K) {
        constexpr int k = K, s = (k + 4) % 6;
        WAIT(BAR(B_FULL + s), k >= 2);
        STAMP(46 + k);
        wg_fence();
        sfor<7>([&](auto I) { wgmma_rs_n56<s * STG + I * 3584>(acc0, A[7 * k + I], d1, k + I != 0); });
        wg_commit();
        if (k == 0) {
          wg_wait<1>();
          send(acc1, 2);
        }
      });
      if (g) bar_arrive<7, 256>();
      wg_wait<0>();
      STAMP(22);
      send(acc0, 3);
      if (!g) bar_sync<7, 256>();
      uint32_t P[3][14];
      const char* const ps = buf + (A_PS + (cta * 6 + 3 * g) * 7168 + (warp & 3) * 1792) + (uint32_t)(lane * 16);
      auto fetch = [&](int x) {
#pragma unroll
        for (int i = 0; i < 3; i++) {
          const uint4 v = ld_rlx4(ps + 7168 * x + 512 * i);
          P[x][4 * i] = v.x; P[x][4 * i + 1] = v.y; P[x][4 * i + 2] = v.z; P[x][4 * i + 3] = v.w;
        }
        const uint2 v = ld_rlx2(ps + 7168 * x + 1536 - lane * 8);
        P[x][12] = v.x; P[x][13] = v.y;
      };
      const uint32_t pss = sb + (6 + g) * STG + (warp & 3) * 1792;
      auto fetchs = [&] {
        WAIT(wb + 24, 0);
#pragma unroll
        for (int x = 0; x < 2; x++) {
          const uint32_t a = pss + TILE + 7168 * x;
#pragma unroll
          for (int i = 0; i < 3; i++) {
            const uint4 v = lds4(a + 512 * i + lane * 16);
            P[x][4 * i] = v.x; P[x][4 * i + 1] = v.y; P[x][4 * i + 2] = v.z; P[x][4 * i + 3] = v.w;
          }
          const uint2 v = lds2(a + 1536 + lane * 8);
          P[x][12] = v.x; P[x][13] = v.y;
        }
      };
      WAIT(BAR(B_FULL + 5), 0);
      wg_fence();
      sfor<28>([&](auto I) {
        if (I == PA) fetchs();
        if (I == PF && PF != PA) WAIT(BAR(B_FULL + 5), 0);
        if (I == PF) fetch(2);
        if (I == PA || I == PF) wg_fence();
        wgmma_rs_n56<(I / 7 + 4) % 6 * STG + I % 7 * 3584 + 896>(acc1, A[I], d1, I != 0);
      });
      wg_commit();
      STAMP(23);
      if (PA == 28) fetchs();
      else WAIT(BAR(B_FULL + 5), 0);
      if (PF == 28) fetch(2);
      auto check = [&](int x) {
#pragma unroll 1
        while (stale(xor2(P[x][0], P[x][4], par) | xor2(P[x][8], P[x][12], par), budget)) fetch(x);
      };
      uint32_t ob = pss + 7168 + (lane & 15) * 112 + (lane & 16);
      uint32_t eye = tq == gq >> 1 ? 0x3F80u << (16 * (gq & 1)) : 0;
      asm volatile("" : "+r"(ob), "+r"(eye));
      auto add = [&](const uint32_t (&v)[14]) {
#pragma unroll
        for (int j = 0; j < 7; j++)
          asm("mma.sync.aligned.m16n8k8.row.col.f32.bf16.bf16.f32 {%0,%1,%2,%3}, {%4,%5}, {%6}, {%0,%1,%2,%3};"
              : "+f"(acc1[4 * j]), "+f"(acc1[4 * j + 1]), "+f"(acc1[4 * j + 2]), "+f"(acc1[4 * j + 3]) : "r"(v[2 * j]), "r"(v[2 * j + 1]), "r"(eye));
      };
      check(0);
      check(1);
      wg_wait<0>();
      acc_fence(acc1);
      STAMP(24);
      add(R);
      add(P[0]);
      add(P[1]);
      acc_fence(acc1);
      WAIT(BAR(B_FULL + 5), 0);
      check(2);
      STAMP(57);
      add(P[2]);
      uint32_t o[14];
#pragma unroll
      for (int j = 0; j < 14; j++) o[j] = pack2(acc1[2 * j], acc1[2 * j + 1]);
#pragma unroll
      for (int i = 0; i < 3; i++)
        asm volatile("stmatrix.sync.aligned.m8n8.x4.shared.b16 [%0], {%1,%2,%3,%4};" ::"r"(ob + 32 * i), "r"(o[4 * i]), "r"(o[4 * i + 1]), "r"(o[4 * i + 2]), "r"(o[4 * i + 3]) : "memory");
      asm volatile("stmatrix.sync.aligned.m8n8.x2.shared.b16 [%0], {%1,%2};" ::"r"(ob + 96), "r"(o[12]), "r"(o[13]) : "memory");
      __syncwarp();
      {
        char* const op = out + (uint32_t)((128 * r + 16 * warp + (lane >> 3)) * 896 + 112 * p + (lane & 7) * 16);
        const uint32_t ia = pss + 7168 + (lane >> 3) * 112 + (lane & 7) * 16;
        uint4 v[4];
#pragma unroll
        for (int i = 0; i < 4; i++) v[i] = lds4(ia + 448 * i);
        if ((lane & 7) < 7) {
#pragma unroll
          for (int i = 0; i < 4; i++) *(uint4*)(op + 3584 * i) = v[i];
        }
      }
      STAMP(25);
      GTIME(1);
    }
  } else {
    {
      const uint32_t c = 0x100000 - (tid < 256 + B_KVB ? 1 : tid < 256 + B_KFREE ? 4 : 8);
      if (tid < 320) sts2(BAR(tid - 256), c << 1, c << 11);
      fence_async_smem();
      bar_arrive<0, 384>();
      bar_sync<2, 128>();
#pragma unroll
      for (int i = warp - 8; i < warp; i += 4) {
        if (elect()) {
          mbar_expect_tx(BAR(B_XB + i), TILE);
          tma3d(sb + OFF_GATH + i * TILE, &map_x, 0, 128 * r + 16 * i, 0, BAR(B_XB + i));
        }
      }
      prefetch_map(&map_qkv);
    }
    STAMPP(60);
    asm volatile("setmaxnreg.dec.sync.aligned.u32 56;");
    STAMPP(63);
    if (warp == 11) {
#pragma unroll 1
      for (int j = 0; j < 8; j++) {
        if (elect()) {
          mbar_expect_tx(BAR(B_K + j), TILE);
          tma2d(sb + (j ^ 4) * TILE, &map_qkv, wcol + DM + DM * (j >> 2), 112 * (j & 3), BAR(B_K + j));
        }
      }
    }
    STAMPP(59);
    const int w = warp - 8, t = tid - 256;
    STAMPP(61);
    char* const kvr = buf + (A_KVR + p * KVR_B);
    if (t < 44) st_rlx4(kvr + (uint32_t)((r * 44 + t) * 16), 0, r * 44 + t < 640 ? 0u : 0xC1800000u, 0, 0xC1800000u);
    const uint32_t e1 = ld_rlx1(&g_epoch[cta * 32]) + 1;
    const char* wrow = wo + (min(cta, 111) * 4 + w) * (DM * 2) + lane * 16;
    const uint4 u0 = ldg4(wrow);
    uint4 u1 = make_uint4(0, 0, 0, 0);
    if (lane < 24) u1 = ldg4(wrow + 512);
    if (QPF >= 1 && lane < (QPF == 1 ? 7 : 21)) asm volatile("prefetch.global.L2 [%0];" ::"l"(wq + (min(cta, 111) * 4 + w) * (DM * 6) + lane * 128));
    GTIME(0);
    const uint32_t par = e1 & 1;
    sts2(sb + OFF_E, e1, 0);
    STAMPP(62);
    {
      float c[4];
      mma16816z(c, u0, 0x3F803F80u, 0x3F803F80u);
      mma16816(c, u1.x, u1.y, u1.z, u1.w, 0x3F803F80u, 0x3F803F80u);
      float s = c[0] + c[2];
      s += shx(s, 4); s += shx(s, 8); s += shx(s, 16);
      s *= 1.f / DM;
      const float hi = bf_lo(tag(pack2(s, 0.f), par));
      if (lane == 0) st_rlx1(buf + (A_WBAR + cta * 16 + w * 4), pack2(hi, s - hi));
    }
    if (smem_u32(smem) != sb) __trap();
    STAMPP(19);
    auto load_wo = [&] {
      mbar_expect_tx(BAR(B_WO), 2 * STG);
      tma2d(sb + OFF_WO, &map_wo, 56 * p, 0, BAR(B_WO));
      tma2d(sb + OFF_WO + STG, &map_wo, 56 * p, 224, BAR(B_WO));
    };
    auto flood = [&] {
      prefetch_map(&map_gu);
      l2_prefetch(wg + cta * 12544, 12544);
      l2_prefetch(wu + cta * 12544, 12544);
      if (!WDL) l2_prefetch(wd + cta * 12544, 12544);
      prefetch_map(&map_gu32); prefetch_map(&map_out);
    };
    WAIT(BAR(B_XFREE), 0);
    if (FL == 2 && w == 1 && elect()) flood();
    if (w == 0 && elect()) {
        if (QPF == 0) asm volatile("cp.async.bulk.prefetch.tensor.2d.L2.global [%0, {%1, %2}];" ::"l"(&map_qkv), "r"(wcol), "r"(112 * (r & 3)) : "memory");
        if (WOPOS == 0) load_wo();
    }
#pragma unroll
    for (int i = 0; i < 4; i++) sts4(sb + OFF_KVB + 2048 * i + t * 16, 0, 0, 0, 0);
    const char* const kvt = kvr + (uint32_t)(t * 16);
    const char* const kvt8 = kvr + 10240 + (uint32_t)(t * 8);
    {
      uint32_t c[6];
      auto counts = [&] {
#pragma unroll
        for (int i = 0; i < 5; i++) c[i] = ld_rlx1(kvt + 2048 * i + 12);
        c[5] = ld_rlx1(kvt8 + 4);
      };
      counts();
    if (w == 0) {
      WAIT(BAR(B_KFREE), 0);
      if (elect()) {
      mbar_expect_tx(BAR(B_Q), 2 * STG);
#pragma unroll 1
      for (int j = 0; j < 4; j++) tma2d(sb + OFF_Q + j * TILE, &map_qkv, wcol, 112 * j, BAR(B_Q));
      if (WOPOS == 2) load_wo();
      }
    }
#pragma unroll 1
      while (stale(~(c[0] & c[1] & c[2] & c[3] & c[4] & c[5]), budget, 0x80000000u)) counts();
    }
    if (lane == 0) mbar_arrive(BAR(B_INIT));
    STAMPP(1);
    if (FL == 0 && w == 1 && elect()) flood();
    uint4 m = ld_rlx4(buf + A_WBAR + (uint32_t)(t * 16));
    WAIT(BAR(B_VFREE), 0);
    if (WOPOS == 1 && w == 0 && elect()) load_wo();
    auto load_w = [&](int u0) {
#pragma unroll 1
      for (int u = u0; u < u0 + 2; u++) {
        if (elect()) {
          mbar_expect_tx(BAR(B_FULL + u), STG);
          tma3d(sb + u * STG, &map_gu, 224 * p + 32 * kh, 112 * u, 0, BAR(B_FULL + u));
        }
      }
    };
    if (w == 0) load_w(0);
    {
#pragma unroll 1
      while (stale(xor2(m.x, m.y, par) | xor2(m.z, m.w, par), budget)) m = ld_rlx4(buf + A_WBAR + (uint32_t)(t * 16));
      WAIT(BAR(B_WO), 0);
      const uint32_t wa = sb + OFF_WO + t * 512 + (112 ^ ((t & 1) << 6));
      if (t < 112) {
        sts4(wa, m.x, m.x, m.x, m.x);
        sts4(wa + 128 - 16, m.y, m.y, m.y, m.y);
        sts4(wa + 256 - 32, m.z, m.z, m.z, m.z);
        sts4(wa + 384 - 48, m.w, m.w, m.w, m.w);
      }
      STAMPP(6);
    }
    bar_sync<2, 128>();
    eq_wait(kvr + KVP * 2048 + w * 512 + 12, 0, budget);
    STAMPX(2);
    {
      uint4 v[5];
      uint2 v5;
#pragma unroll 1
      do {
#pragma unroll
        for (int i = 0; i < 5; i++) v[i] = ld_rlx4(kvt + 2048 * i);
        v5 = ld_rlx2(kvt8);
      } while (stale(or3(v[0].w, v[1].w, v[2].w) | or3(v[3].w, v[4].w, v5.y), budget, ~0u));
      STAMPX(3);
      if (W23 == 1 && w == 0) { WAIT(BAR(B_QFREE), 0); load_w(2); }
      if (FL == 1 && w == 1 && elect()) flood();
      const int gq = lane >> 2, tq = lane & 3, k = 28 * (w >> 1) + 16 * (w & 1) + gq, n = 28 * (w >> 1) + 2 * tq;
      const uint32_t row = sb + OFF_KVB + k * 128, sw = (k & 7) << 4;
      const bool lo = !(w & 1) || gq < 4;
#define F(x) __uint_as_float(x)
      const uint32_t a[4] = {pack2(F(v[0].x), F(v[0].y)), pack2(F(v[0].z), F(v[1].x)), pack2(F(v[1].y), F(v[1].z)), pack2(F(v[4].x), F(v[4].y))};
      const uint32_t b[4] = {pack2(F(v[2].x), F(v[2].y)), pack2(F(v[2].z), F(v[3].x)), pack2(F(v[3].y), F(v[3].z)), pack2(F(v[4].z), F(v5.x))};
#pragma unroll
      for (int q = 0; q < 4; q++) {
        const uint32_t ad = row + ((2 * n + 16 * q) ^ sw);
        if (q < 3 || tq < 2) {
          sts1(ad, a[q]);
          if (lo) sts1(ad + 1024, b[q]);
        }
      }
      if (tq == 2) {
        const uint32_t z = pack2(F(v[4].x) + F(v[4].y), F(v[4].z) + F(v5.x));
        const uint32_t za = __byte_perm(z, 0, w & 2 ? 0x1044 : 0x4410), zb = __byte_perm(z, 0, w & 2 ? 0x3244 : 0x4432);
        sts4(row + (112 ^ sw), za, za, za, za);
        if (lo) sts4(row + 1024 + (112 ^ sw), zb, zb, zb, zb);
      }
      fence_async_smem();
      __syncwarp();
      if (lane == 0) mbar_arrive(BAR(B_KVB));
      STAMPP(4);
      if (W23 == 2 && w == 0) { WAIT(BAR(B_QFREE), 0); load_w(2); }
    }
    if (w == 0) {
#pragma unroll 1
      for (int u = W23 ? 4 : 2; u < 22; u++) {
        const int s = u < 14 ? u & 7 : u < 20 ? u - 14 : u - 20;
        if (u == 14) WAIT(BAR(B_WDOK), 0);
        WAIT(BAR(B_KFREE + s) + (u >= 8 ? 64 : 0), u >= 14 && u < 20);
        STAMPP(20 + u);
        if (elect()) {
          mbar_expect_tx(BAR(B_FULL + s), u < 14 ? STG : WDS);
          if (u < 12) tma3d(sb + s * STG, &map_gu, 224 * p + 32 * kh + 64 * (u >> 2), 112 * (u & 3), 0, BAR(B_FULL + s));
          else if (u < 14) tma3d(sb + s * STG, &map_gu32, 224 * p + 192 - 192 * kh, 224 * (u - 12), 0, BAR(B_FULL + s));
          else bulk_g2s(sb + s * STG, buf + (A_WD + (p * 8 + u - 14) * WDS), WDS, BAR(B_FULL + s));
        }
      }
    } else {
#pragma unroll 1
      for (int j = 0; j < (w <= NPOLL ? 4 : 0); j++) {
        const char* src = buf + (A_O + (j >> 1) * FRAG_B + (r * 2 + (j & 1)) * 2 * STG);
        const uint32_t dst = sb + OFF_GATH + (j == 3 ? 2 * STG : 0), full = BAR(B_WB + 4 * (j & 1));
        if (j != 1) {
          if (NPOLL > 1) {
            const uint32_t t0 = clock();
            while ((uint32_t)clock() - t0 < (w - 1) * PST);
          }
          cnt_wait(&g_cnt[C_ROW + r * 32 + j], e1 * (j ? 32 : 64), budget);
          uint32_t old = 0;
          if (NPOLL > 1 && lane == 0) asm volatile("atom.shared.or.b32 %0, [%1], %2;" : "=r"(old) : "r"(sb + OFF_E + 4), "r"(1 << j) : "memory");
          if (NPOLL > 1 && __any_sync(0xffffffffu, old >> j & 1)) {
            j += j == 0;
            continue;
          }
          if (j != 2) WAIT(BAR(B_OFREE), j & 1);
        }
        STAMPX(50 + 2 * j);
#pragma unroll
        for (int q = 0; q < 4; q++) {
          if (j + 1 & 2) WAIT(BAR(B_ORD + q), j >> 1);
          if (elect()) {
            mbar_expect_tx(full + 8 * q, TILE);
            bulk_g2s(dst + q * TILE, src + q * TILE, TILE, full + 8 * q);
          }
        }
        if (j == 2) bar_arrive<6, 160>();
        if (W4G == 1 && j == 3 && lane < 8) mbar_arrive(BAR(B_HFREE + (lane >> 2)));
        STAMPP(51 + 2 * j);
      }
      if (w == 1) return;
      const int g = w - 2;
      WAIT(BAR(B_HFREE + RPK), 0);
      if (t < 120) {
        const int src = p ^ (r >> 2 & 1), part = (r & 1) + (~(r ^ r >> 1) & 2);
        char* zp = buf + (uint32_t)(A_WD + (p * 16 + r) * (WDS / 2) + t * 16 - 1024);
#pragma unroll 1
        for (int x = 1 + (r >> 2 & 2);; x++, zp += 896) {
          const char* wp = wd + (uint32_t)((224 * src + 32 * (src & 1) + 56 * part + (t & 7)) * 896 + (p ^ 2 * x & 7) * 112 + (t & 56) * 2);
          uint4 z[7];
#pragma unroll
          for (int i = 0; i < 7; i++) {
            if (i == 3 && part + (src & 1) == 4) wp -= 224 * 896;
            z[i] = ldg4(wp + i * 8 * 896);
          }
#pragma unroll
          for (int i = 0; i < 7; i++) st_rlx4(zp + i * 1792, z[i].x, z[i].y, z[i].z, z[i].w);
          if (!(x & 1)) break;
        }
      }
      STAMPP(5);
      asm volatile("fence.proxy.async.global;" ::: "memory");
      __syncwarp();
      if (lane == 0) asm volatile("red.release.gpu.global.add.u32 [%0], 1;" ::"l"(&g_cnt[C_WD + p * 32]) : "memory");
      STAMPP(7);
      cnt_wait<true>(&g_cnt[C_WD + p * 32], e1 * 32, budget);
      STAMPP(18);
      asm volatile("fence.proxy.async.global;" ::: "memory");
      if (lane < 2) mbar_arrive(BAR(B_WDOK));
#pragma unroll 1
      for (int j = 0; j < 4; j += j + 1) {
        const uint32_t bar = BAR(B_WB + 4 * g + j);
        const char* src = buf + (j < 3 ? A_HH + (cta ^ j) * 2 * STG + g * TILE : A_PS + (cta * 6 + 3 * g) * 7168);
        if (j != 1) cnt_wait(&g_cnt[(j < 3 ? C_ROW + r * 32 + 4 + 2 * (p & 6) : C_PS + cta * 8) + g], e1 * 8, budget);
        WAIT(j >= 2 ? BAR(B_HFREE + 2 * g + 1) : BAR(B_EMPTY + 6 + g), j >> 1);
        if (elect()) {
          mbar_expect_tx(bar, TILE);
          bulk_g2s(sb + (6 + g) * STG + (j & 1) * TILE, src, TILE, bar);
        }
      }
      if (g) st_rlx1(&g_epoch[cta * 32], e1);
      if (g && lane == 0) DUMP(2);
    }
  }
}

typedef CUresult (*EncodeFn)(CUtensorMap*, CUtensorMapDataType, cuuint32_t, void*, const cuuint64_t*, const cuuint64_t*,
                             const cuuint32_t*, const cuuint32_t*, CUtensorMapInterleave, CUtensorMapSwizzle,
                             CUtensorMapL2promotion, CUtensorMapFloatOOBfill);

void make_map(EncodeFn enc, CUtensorMap* m, const void* p, int rank, const cuuint64_t* gd, const cuuint64_t* gs,
              const cuuint32_t* bd, CUtensorMapSwizzle sw) {
  const cuuint32_t es[5] = {1, 1, 1, 1, 1};
  ENC_CHECK(enc(m, CU_TENSOR_MAP_DATA_TYPE_BFLOAT16, rank, (void*)p, gd, gs, bd, es, CU_TENSOR_MAP_INTERLEAVE_NONE, sw,
                CU_TENSOR_MAP_L2_PROMOTION_NONE, CU_TENSOR_MAP_FLOAT_OOB_FILL_NONE));
}

}

extern "C" void kernel_launch(void* const* d_in, const int* in_sizes, int n_in, void* d_out, int out_size) {
  (void)in_sizes; (void)n_in; (void)out_size;
  static EncodeFn enc = nullptr;
  static char* buf = nullptr;
  if (!enc) {
    void* fn = nullptr;
    cudaDriverEntryPointQueryResult qr;
    cudaGetDriverEntryPoint("cuTensorMapEncodeTiled", &fn, cudaEnableDefault, &qr);
    enc = (EncodeFn)fn;
    cudaGetSymbolAddress((void**)&buf, g_buf);
    cudaFuncSetAttribute(fused_block_kernel<false>, cudaFuncAttributeMaxDynamicSharedMemorySize, SMEM_TOTAL);
    cudaFuncSetAttribute(fused_block_kernel<true>, cudaFuncAttributeMaxDynamicSharedMemorySize, SMEM_TOTAL);
  }
  const CUtensorMapSwizzle S128 = CU_TENSOR_MAP_SWIZZLE_128B;
  CUtensorMap mx, mqkv, mwor, mgu, mgu32, mout;
  {
    cuuint64_t gd[3] = {64, SEQ, 7}, gs[2] = {DM * 2, 128};
    cuuint32_t bd[3] = {64, 16, 7};
    make_map(enc, &mx, d_in[0], 3, gd, gs, bd, S128);
  }
  {
    cuuint64_t gd[2] = {3 * DM, DM}, gs[1] = {3 * DM * 2};
    cuuint32_t bd[2] = {64, 112};
    make_map(enc, &mqkv, d_in[1], 2, gd, gs, bd, S128);
  }
  {
    cuuint64_t gd[2] = {DM, DM}, gs[1] = {DM * 2};
    cuuint32_t bd[2] = {64, 224};
    make_map(enc, &mwor, d_in[2], 2, gd, gs, bd, S128);
  }
  const char *wg = (const char*)d_in[4], *wu = (const char*)d_in[5];
  const bool swap = wu < wg;
  const char* gub = swap ? wu : wg;
  const cuuint64_t gud = swap ? (cuuint64_t)(wg - wu) : (cuuint64_t)(wu - wg);
  {
    cuuint64_t gd[3] = {FF, DM, 2}, gs[2] = {FF * 2, gud};
    cuuint32_t bd[3] = {64, 112, 2};
    make_map(enc, &mgu, gub, 3, gd, gs, bd, S128);
  }
  {
    cuuint64_t gd[3] = {FF, DM, 2}, gs[2] = {FF * 2, gud};
    cuuint32_t bd[3] = {32, 224, 2};
    make_map(enc, &mgu32, gub, 3, gd, gs, bd, CU_TENSOR_MAP_SWIZZLE_64B);
  }
  {
    cuuint64_t gd[2] = {DM, SEQ}, gs[1] = {DM * 2};
    cuuint32_t bd[2] = {56, 16};
    make_map(enc, &mout, d_out, 2, gd, gs, bd, CU_TENSOR_MAP_SWIZZLE_NONE);
  }
  (swap ? fused_block_kernel<true> : fused_block_kernel<false>)<<<128, 384, SMEM_TOTAL>>>(
      buf, (const char*)d_in[2], mn_desc(sb), mn_desc64(sb), mn_desc0(sb), mn_desc(sb + OFF_Q), mn_desc0(sb), wg, wu, (const char*)d_in[6], (const char*)d_in[1], (char*)d_out, mx, mqkv, mwor, mgu, mgu32, mout);
}
```

```cpp
#include <cuda_runtime.h>
#include <cuda_bf16.h>
#include <cuda.h>
#include <stdint.h>
#include <stdio.h>
#include <utility>

#define SPIN_LIMIT (1 << 18)

namespace {

constexpr uint32_t sb = 1024;
constexpr int SEQ = 2048, DM = 448, FF = 1792;
constexpr int TILE = 14336;
constexpr int STG = 2 * TILE;
constexpr int SMEM_BAR = 8 * STG;
constexpr int SMEM_TOTAL = SMEM_BAR + 3072;
constexpr int OFF_X = 4 * STG, OFF_Q = 2 * STG, OFF_WO = 4 * STG, OFF_G = 6 * STG, OFF_PK = 6 * STG, OFF_KVB = OFF_PK + 32768, OFF_XS = OFF_KVB + 8192,
              OFF_M = SMEM_BAR + 512, OFF_WBAR = SMEM_BAR + 2048;
constexpr int B_XB = 0  , B_K = 8  , B_V = 12  , B_Q = 16, B_WO = 17, B_FULL = 18  , B_WB = 26  ,
              B_KVB = 34, B_WDOK = 35, B_INIT = 36,
              B_KFREE = 37, B_OFREE = 38, B_QFREE = 39  , B_HFREE = 41  , B_EMPTY = 45  , B_XFREE = 53, B_VFREE = 54,
              B_ORD = 55  , B_WOFREE = 59, B_RPK = 60;

constexpr int KVR_B = 11264;
constexpr int FRAG_B = 16 * 4 * STG;
constexpr int A_CNT = 0, A_EPOCH = 8192, A_KVR = A_EPOCH + 16384, A_WBAR = A_KVR + 8 * KVR_B, A_O = A_WBAR + 2048, A_H = A_O + FRAG_B,
              A_HH = A_H + FRAG_B;
constexpr int HH_B = 128 * 2 * STG;
constexpr int A_PS = A_HH + HH_B;
constexpr int WDS = 25088;
constexpr int A_WD = A_PS + 128 * 3 * TILE;

__device__ uint4 g_buf[(A_WD + 64 * WDS) / 16];
#define g_epoch ((unsigned*)buf + A_EPOCH / 4)
constexpr int C_ROW = 0, C_WD = 512, C_PS = 1024;
#define g_cnt ((unsigned*)buf + A_CNT / 4)
#define ENC_CHECK(x) (void)(x)
#define STAMP(i)
#define STAMPX(i)
#define GTIME(i)
#define STAMPP(i)
#define STAMPD(i)
#define DUMP(row)

__device__ __forceinline__ uint32_t smem_u32(const void* p) { return (uint32_t)__cvta_generic_to_shared(p); }
__device__ __forceinline__ void mbar_init(uint32_t bar, uint32_t cnt) {
  asm volatile("mbarrier.init.shared::cta.b64 [%0], %1;" ::"r"(bar), "r"(cnt) : "memory");
}
__device__ __forceinline__ void mbar_expect_tx(uint32_t bar, uint32_t bytes) {
  asm volatile("mbarrier.arrive.expect_tx.shared::cta.b64 _, [%0], %1;" ::"r"(bar), "r"(bytes) : "memory");
}
__device__ __forceinline__ void mbar_arrive(uint32_t bar) {
  asm volatile("mbarrier.arrive.shared::cta.b64 _, [%0];" ::"r"(bar) : "memory");
}
__device__ __forceinline__ void mbar_wait(uint32_t bar, uint32_t parity, int& budget) {
  asm volatile("{\n.reg .pred p;\nW:\nmbarrier.try_wait.parity.shared::cta.b64 p, [%1], %2;\n"
               "add.s32 %0, %0, -1;\nsetp.gt.and.s32 p, %0, 0, !p;\n@p bra W;\n}"
               : "+r"(budget) : "r"(bar), "r"(parity) : "memory");
}
__device__ __forceinline__ bool elect() {
  uint32_t v;
  asm volatile("{\n.reg .pred p;\nelect.sync _|p, 0xffffffff;\nselp.u32 %0, 1, 0, p;\n}" : "=r"(v));
  return v;
}
__device__ __forceinline__ void tma2d(uint32_t dst, const CUtensorMap* m, int c0, int c1, uint32_t bar) {
  asm volatile("cp.async.bulk.tensor.2d.shared::cluster.global.mbarrier::complete_tx::bytes [%0], [%1, {%3, %4}], [%2];"
               ::"r"(dst), "l"(m), "r"(bar), "r"(c0), "r"(c1) : "memory");
}
__device__ __forceinline__ void tma3d(uint32_t dst, const CUtensorMap* m, int c0, int c1, int c2, uint32_t bar) {
  asm volatile("cp.async.bulk.tensor.3d.shared::cluster.global.mbarrier::complete_tx::bytes [%0], [%1, {%3, %4, %5}], [%2];"
               ::"r"(dst), "l"(m), "r"(bar), "r"(c0), "r"(c1), "r"(c2) : "memory");
}
__device__ __forceinline__ void bulk_g2s(uint32_t dst, const void* src, uint32_t bytes, uint32_t bar) {
  asm volatile("cp.async.bulk.shared::cluster.global.mbarrier::complete_tx::bytes [%0], [%1], %2, [%3];"
               ::"r"(dst), "l"(src), "r"(bytes), "r"(bar) : "memory");
}
__device__ __forceinline__ void l2_prefetch(const void* p, uint32_t bytes) {
  asm volatile("cp.async.bulk.prefetch.L2.global [%0], %1;" ::"l"(p), "r"(bytes) : "memory");
}
__device__ __forceinline__ void prefetch_map(const CUtensorMap* m) {
  asm volatile("prefetch.tensormap [%0];" ::"l"(m) : "memory");
}
__device__ __forceinline__ void fence_async_smem() { asm volatile("fence.proxy.async.shared::cta;" ::: "memory"); }
template <int ID, int N> __device__ __forceinline__ void bar_arrive() { asm volatile("bar.arrive %0, %1;" ::"n"(ID), "n"(N) : "memory"); }
__device__ __forceinline__ void bar_sync_wg(int id) { asm volatile("bar.sync %0, 128;" ::"r"(id) : "memory"); }
template <int ID, int N> __device__ __forceinline__ void bar_sync() { asm volatile("bar.sync %0, %1;" ::"n"(ID), "n"(N) : "memory"); }
__device__ __forceinline__ void wg_fence() { asm volatile("wgmma.fence.sync.aligned;" ::: "memory"); }
__device__ __forceinline__ void wg_commit() { asm volatile("wgmma.commit_group.sync.aligned;" ::: "memory"); }
template <int N> __device__ __forceinline__ void wg_wait() { asm volatile("wgmma.wait_group.sync.aligned %0;" ::"n"(N) : "memory"); }
template <int N> __device__ __forceinline__ void acc_fence(float (&d)[N]) {
#pragma unroll
  for (int i = 0; i < N; i++) asm volatile("" : "+f"(d[i])::"memory");
}
constexpr uint64_t mn_desc(uint32_t addr) {
  return (uint64_t)((addr & 0x3FFFF) >> 4) | ((uint64_t)(TILE >> 4) << 16) | ((uint64_t)64 << 32) | ((uint64_t)1 << 62);
}
constexpr uint64_t mn_desc64(uint32_t addr) {
  return (uint64_t)((addr & 0x3FFFF) >> 4) | ((uint64_t)(TILE >> 4) << 16) | ((uint64_t)32 << 32) | ((uint64_t)2 << 62);
}
constexpr uint64_t mn_desc0(uint32_t addr) {
  return (uint64_t)((addr & 0x3FFFF) >> 4) | ((uint64_t)(1792 >> 4) << 16) | ((uint64_t)8 << 32);
}
constexpr uint64_t k_desc0(uint32_t addr) {
  return (uint64_t)((addr & 0x3FFFF) >> 4) | ((uint64_t)8 << 16) | ((uint64_t)(1792 >> 4) << 32);
}
__device__ __forceinline__ uint4 ld_rlx4(const void* p) {
  uint4 v;
  asm volatile("ld.relaxed.gpu.global.v4.u32 {%0,%1,%2,%3}, [%4];" : "=r"(v.x), "=r"(v.y), "=r"(v.z), "=r"(v.w) : "l"(p) : "memory");
  return v;
}
__device__ __forceinline__ uint2 ld_rlx2(const void* p) {
  uint2 v;
  asm volatile("ld.relaxed.gpu.global.v2.u32 {%0,%1}, [%2];" : "=r"(v.x), "=r"(v.y) : "l"(p) : "memory");
  return v;
}
__device__ __forceinline__ uint32_t ld_rlx1(const void* p) {
  uint32_t v;
  asm volatile("ld.relaxed.gpu.global.u32 %0, [%1];" : "=r"(v) : "l"(p) : "memory");
  return v;
}
__device__ __forceinline__ void st_rlx4(void* p, uint32_t a, uint32_t b, uint32_t c, uint32_t d) {
  asm volatile("st.relaxed.gpu.global.v4.u32 [%0], {%1,%2,%3,%4};" ::"l"(p), "r"(a), "r"(b), "r"(c), "r"(d) : "memory");
}
__device__ __forceinline__ void st_rlx2(void* p, uint32_t a, uint32_t b) {
  asm volatile("st.relaxed.gpu.global.v2.u32 [%0], {%1,%2};" ::"l"(p), "r"(a), "r"(b) : "memory");
}
__device__ __forceinline__ void st_rlx1(void* p, uint32_t a) {
  asm volatile("st.relaxed.gpu.global.u32 [%0], %1;" ::"l"(p), "r"(a) : "memory");
}
__device__ __forceinline__ void red_inc(unsigned* p) {
  asm volatile("red.relaxed.gpu.global.inc.u32 [%0], 0xfffffffe;" ::"l"(p) : "memory");
}
__device__ __forceinline__ void red_add4(void* p, float a, float b, float c) {
  asm volatile("red.relaxed.gpu.global.add.v4.f32 [%0], {%1,%2,%3,%4};" ::"l"(p), "f"(a), "f"(b), "f"(c), "f"(1.f) : "memory");
}
__device__ __forceinline__ void red_add2(void* p, float a) {
  asm volatile("red.relaxed.gpu.global.add.v2.f32 [%0], {%1,%2};" ::"l"(p), "f"(a), "f"(1.f) : "memory");
}
__device__ __forceinline__ void eq_wait(const void* p, uint32_t target, int& budget) {
  asm volatile("{\n.reg .pred p;\n.reg .b32 v;\nW:\nld.relaxed.gpu.global.b32 v, [%1];\nadd.s32 %0, %0, -1;\n"
               "setp.gt.s32 p, %0, 0;\nsetp.ne.and.b32 p, v, %2, p;\n@p bra W;\n}"
               : "+r"(budget) : "l"(p), "r"(target) : "memory");
}
template <bool ACQ = false>
__device__ __forceinline__ void cnt_wait(const unsigned* p, uint32_t target, int& budget) {
  if (ACQ)
    asm volatile("{\n.reg .pred p;\n.reg .s32 v;\nW:\nld.acquire.gpu.global.s32 v, [%1];\nadd.s32 %0, %0, -1;\n"
                 "setp.gt.s32 p, %0, 0;\nsub.s32 v, v, %2;\nsetp.lt.and.s32 p, v, 0, p;\n@p bra W;\n}"
                 : "+r"(budget) : "l"(p), "r"(target) : "memory");
  else
  asm volatile("{\n.reg .pred p;\n.reg .s32 v;\nW:\nld.relaxed.gpu.global.s32 v, [%1];\nadd.s32 %0, %0, -1;\n"
               "setp.gt.s32 p, %0, 0;\nsub.s32 v, v, %2;\nsetp.lt.and.s32 p, v, 0, p;\n@p bra W;\n}"
               : "+r"(budget) : "l"(p), "r"(target) : "memory");
}
__device__ __forceinline__ uint32_t or3(uint32_t a, uint32_t b, uint32_t c) {
  uint32_t r;
  asm("lop3.b32 %0, %1, %2, %3, 0xfe;" : "=r"(r) : "r"(a), "r"(b), "r"(c));
  return r;
}
__device__ __forceinline__ uint32_t xor2(uint32_t a, uint32_t b, uint32_t f) {
  uint32_t r;
  asm("lop3.b32 %0, %1, %2, %3, 0x7e;" : "=r"(r) : "r"(a), "r"(b), "r"(f));
  return r;
}
__device__ __forceinline__ bool stale(uint32_t bad, int& budget, uint32_t mask = 1) {
  uint32_t v;
  asm volatile("{\n.reg .pred p;\n.reg .b32 t;\nand.b32 t, %2, %3;\nsetp.ne.u32 p, t, 0;\nadd.s32 %1, %1, -1;\n"
               "setp.gt.and.s32 p, %1, 0, p;\nvote.sync.any.pred p, p, 0xffffffff;\nselp.u32 %0, 1, 0, p;\n}"
               : "=r"(v), "+r"(budget) : "r"(bad), "r"(mask));
  return v;
}
__device__ __forceinline__ uint32_t tag(uint32_t w, uint32_t par) {
  uint32_t r;
  asm("lop3.b32 %0, %1, %2, 1, 0xd8;" : "=r"(r) : "r"(w), "r"(par));
  return r;
}
__device__ __forceinline__ void sts1(uint32_t a, uint32_t v) { asm volatile("st.shared.u32 [%0], %1;" ::"r"(a), "r"(v) : "memory"); }
__device__ __forceinline__ void sts2(uint32_t a, uint32_t x, uint32_t y) {
  asm volatile("st.shared.v2.u32 [%0], {%1,%2};" ::"r"(a), "r"(x), "r"(y) : "memory");
}
__device__ __forceinline__ void sts4(uint32_t a, uint32_t x, uint32_t y, uint32_t z, uint32_t w) {
  asm volatile("st.shared.v4.u32 [%0], {%1,%2,%3,%4};" ::"r"(a), "r"(x), "r"(y), "r"(z), "r"(w) : "memory");
}
__device__ __forceinline__ uint32_t lds1(uint32_t a) {
  uint32_t v;
  asm volatile("ld.shared.u32 %0, [%1];" : "=r"(v) : "r"(a) : "memory");
  return v;
}
__device__ __forceinline__ uint2 lds2(uint32_t a) {
  uint2 v;
  asm volatile("ld.shared.v2.u32 {%0,%1}, [%2];" : "=r"(v.x), "=r"(v.y) : "r"(a) : "memory");
  return v;
}
__device__ __forceinline__ uint4 lds4(uint32_t a) {
  uint4 v;
  asm volatile("ld.shared.v4.u32 {%0,%1,%2,%3}, [%4];" : "=r"(v.x), "=r"(v.y), "=r"(v.z), "=r"(v.w) : "r"(a) : "memory");
  return v;
}
__device__ __forceinline__ uint4 ldsm4(uint32_t a) {
  uint4 v;
  asm volatile("ldmatrix.sync.aligned.m8n8.x4.shared.b16 {%0,%1,%2,%3}, [%4];" : "=r"(v.x), "=r"(v.y), "=r"(v.z), "=r"(v.w) : "r"(a) : "memory");
  return v;
}
__device__ __forceinline__ uint4 ldsm4t(uint32_t a) {
  uint4 v;
  asm volatile("ldmatrix.sync.aligned.m8n8.x4.trans.shared.b16 {%0,%1,%2,%3}, [%4];" : "=r"(v.x), "=r"(v.y), "=r"(v.z), "=r"(v.w) : "r"(a) : "memory");
  return v;
}
__device__ __forceinline__ uint32_t pack2(float lo, float hi) {
  uint32_t r;
  asm("cvt.rn.bf16x2.f32 %0, %1, %2;" : "=r"(r) : "f"(hi), "f"(lo));
  return r;
}
__device__ __forceinline__ float bf_lo(uint32_t w) { return __uint_as_float(w << 16); }
__device__ __forceinline__ float bf_hi(uint32_t w) { return __uint_as_float(w & 0xFFFF0000u); }
__device__ __forceinline__ uint32_t sub2(uint32_t a, uint32_t b) {
  uint32_t r;
  asm volatile("sub.rn.bf16x2 %0, %1, %2;" : "=r"(r) : "r"(a), "r"(b));
  return r;
}
__device__ __forceinline__ uint32_t add2(uint32_t a, uint32_t b) {
  uint32_t r;
  asm("add.rn.bf16x2 %0, %1, %2;" : "=r"(r) : "r"(a), "r"(b));
  return r;
}
__device__ __forceinline__ uint32_t fma2(uint32_t a, uint32_t b, uint32_t c) {
  uint32_t r;
  asm("fma.rn.bf16x2 %0, %1, %2, %3;" : "=r"(r) : "r"(a), "r"(b), "r"(c));
  return r;
}
__device__ __forceinline__ uint32_t transp(uint32_t a) {
  uint32_t r;
  asm volatile("movmatrix.sync.aligned.m8n8.trans.b16 %0, %1;" : "=r"(r) : "r"(a));
  return r;
}
__device__ __forceinline__ uint32_t sq2(uint32_t a) {
  uint32_t r;
  asm volatile("mul.rn.bf16x2 %0, %1, %1;" : "=r"(r) : "r"(a));
  return r;
}
__device__ __forceinline__ uint32_t sq2(uint32_t a, uint32_t c) {
  uint32_t r;
  asm volatile("fma.rn.bf16x2 %0, %1, %1, %2;" : "=r"(r) : "r"(a), "r"(c));
  return r;
}
__device__ __forceinline__ uint4 ldg4(const void* p) {
  uint4 v;
  asm volatile("ld.global.nc.v4.u32 {%0,%1,%2,%3}, [%4];" : "=r"(v.x), "=r"(v.y), "=r"(v.z), "=r"(v.w) : "l"(p));
  return v;
}
__device__ __forceinline__ void mma16816(float (&c)[4], uint32_t a0, uint32_t a1, uint32_t a2, uint32_t a3, uint32_t b0, uint32_t b1) {
  asm("mma.sync.aligned.m16n8k16.row.col.f32.bf16.bf16.f32 {%0,%1,%2,%3}, {%4,%5,%6,%7}, {%8,%9}, {%0,%1,%2,%3};"
      : "+f"(c[0]), "+f"(c[1]), "+f"(c[2]), "+f"(c[3]) : "r"(a0), "r"(a1), "r"(a2), "r"(a3), "r"(b0), "r"(b1));
}
__device__ __forceinline__ void mma16816z(float (&c)[4], const uint4& a, uint32_t b0, uint32_t b1) {
  asm("mma.sync.aligned.m16n8k16.row.col.f32.bf16.bf16.f32 {%0,%1,%2,%3}, {%4,%5,%6,%7}, {%8,%9}, {%10,%10,%10,%10};"
      : "=f"(c[0]), "=f"(c[1]), "=f"(c[2]), "=f"(c[3]) : "r"(a.x), "r"(a.y), "r"(a.z), "r"(a.w), "r"(b0), "r"(b1), "f"(0.f));
}
__device__ __forceinline__ float ex2f(float x) { float r; asm("ex2.approx.ftz.f32 %0, %1;" : "=f"(r) : "f"(x)); return r; }
__device__ __forceinline__ float tanhf_(float x) { float r; asm("tanh.approx.f32 %0, %1;" : "=f"(r) : "f"(x)); return r; }
__device__ __forceinline__ float rsqf(float x) { float r; asm("rsqrt.approx.ftz.f32 %0, %1;" : "=f"(r) : "f"(x)); return r; }
__device__ __forceinline__ float lg2f(float x) { float r; asm("lg2.approx.ftz.f32 %0, %1;" : "=f"(r) : "f"(x)); return r; }
__device__ __forceinline__ float rcpf(float x) { float r; asm("rcp.approx.ftz.f32 %0, %1;" : "=f"(r) : "f"(x)); return r; }
__device__ __forceinline__ float phi(float a, const float4& c) {
  return ex2f(fmaf(fminf(a, 0.f), c.x, c.y)) + fmaf(fmaxf(a, 0.f), c.z, c.w);
}
__host__ __device__ constexpr long long koff(int i, int u) { return i < 3 ? 2 * i * u : i == 3 ? 6 * u + ((6ll * u) << 32) : (2 * i - 1) * u; }
__device__ __forceinline__ float shx(float v, int m) { return __shfl_xor_sync(0xffffffffu, v, m); }
template <int V> struct IC { __host__ __device__ constexpr operator int() const { return V; } };
template <class F, int... I> __device__ __forceinline__ void sfor_impl(F&& f, std::integer_sequence<int, I...>) {
  (f(IC<I>{}), ...);
}
template <int N, class F> __device__ __forceinline__ void sfor(F&& f) { sfor_impl(f, std::make_integer_sequence<int, N>{}); }

template <long long OFF, int RO = 0, int N>
__device__ __forceinline__ void wgmma_rs_n56(float (&d)[N], const uint4& a, uint64_t base, int scale_d) {
  asm volatile("{\n.reg .pred p;\n.reg .b64 t;\nsetp.ne.b32 p, %33, 0;\nadd.s64 t, %32, %34;\n"
    "wgmma.mma_async.sync.aligned.m64n56k16.f32.bf16.bf16 {%0, %1, %2, %3, %4, %5, %6, %7, %8, %9, %10, %11, %12, %13, %14, %15, %16, %17, %18, %19, %20, %21, %22, %23, %24, %25, %26, %27}, {%28, %29, %30, %31}, t, p, 1, 1, 1;\n}\n"
    : "+f"(d[RO + 0]), "+f"(d[RO + 1]), "+f"(d[RO + 2]), "+f"(d[RO + 3]), "+f"(d[RO + 4]), "+f"(d[RO + 5]), "+f"(d[RO + 6]), "+f"(d[RO + 7]), "+f"(d[RO + 8]), "+f"(d[RO + 9]), "+f"(d[RO + 10]), "+f"(d[RO + 11]), "+f"(d[RO + 12]), "+f"(d[RO + 13]), "+f"(d[RO + 14]), "+f"(d[RO + 15]), "+f"(d[RO + 16]), "+f"(d[RO + 17]), "+f"(d[RO + 18]), "+f"(d[RO + 19]), "+f"(d[RO + 20]), "+f"(d[RO + 21]), "+f"(d[RO + 22]), "+f"(d[RO + 23]), "+f"(d[RO + 24]), "+f"(d[RO + 25]), "+f"(d[RO + 26]), "+f"(d[RO + 27])
    : "r"(a.x), "r"(a.y), "r"(a.z), "r"(a.w), "l"(base), "r"(scale_d), "n"(OFF >> 4));
}
template <long long OFF, int RO = 0, int N>
__device__ __forceinline__ void wgmma_rs_n64(float (&d)[N], const uint4& a, uint64_t base, int scale_d) {
  asm volatile("{\n.reg .pred p;\n.reg .b64 t;\nsetp.ne.b32 p, %37, 0;\nadd.s64 t, %36, %38;\n"
    "wgmma.mma_async.sync.aligned.m64n64k16.f32.bf16.bf16 {%0, %1, %2, %3, %4, %5, %6, %7, %8, %9, %10, %11, %12, %13, %14, %15, %16, %17, %18, %19, %20, %21, %22, %23, %24, %25, %26, %27, %28, %29, %30, %31}, {%32, %33, %34, %35}, t, p, 1, 1, 1;\n}\n"
    : "+f"(d[RO + 0]), "+f"(d[RO + 1]), "+f"(d[RO + 2]), "+f"(d[RO + 3]), "+f"(d[RO + 4]), "+f"(d[RO + 5]), "+f"(d[RO + 6]), "+f"(d[RO + 7]), "+f"(d[RO + 8]), "+f"(d[RO + 9]), "+f"(d[RO + 10]), "+f"(d[RO + 11]), "+f"(d[RO + 12]), "+f"(d[RO + 13]), "+f"(d[RO + 14]), "+f"(d[RO + 15]), "+f"(d[RO + 16]), "+f"(d[RO + 17]), "+f"(d[RO + 18]), "+f"(d[RO + 19]), "+f"(d[RO + 20]), "+f"(d[RO + 21]), "+f"(d[RO + 22]), "+f"(d[RO + 23]), "+f"(d[RO + 24]), "+f"(d[RO + 25]), "+f"(d[RO + 26]), "+f"(d[RO + 27]), "+f"(d[RO + 28]), "+f"(d[RO + 29]), "+f"(d[RO + 30]), "+f"(d[RO + 31])
    : "r"(a.x), "r"(a.y), "r"(a.z), "r"(a.w), "l"(base), "r"(scale_d), "n"(OFF >> 4));
}
template <long long OFF, int RO = 0, int N>
__device__ __forceinline__ void wgmma_rk_n64(float (&d)[N], const uint4& a, uint64_t base, int scale_d) {
  asm volatile("{\n.reg .pred p;\n.reg .b64 t;\nsetp.ne.b32 p, %37, 0;\nadd.s64 t, %36, %38;\n"
    "wgmma.mma_async.sync.aligned.m64n64k16.f32.bf16.bf16 {%0, %1, %2, %3, %4, %5, %6, %7, %8, %9, %10, %11, %12, %13, %14, %15, %16, %17, %18, %19, %20, %21, %22, %23, %24, %25, %26, %27, %28, %29, %30, %31}, {%32, %33, %34, %35}, t, p, 1, 1, 0;\n}\n"
    : "+f"(d[RO + 0]), "+f"(d[RO + 1]), "+f"(d[RO + 2]), "+f"(d[RO + 3]), "+f"(d[RO + 4]), "+f"(d[RO + 5]), "+f"(d[RO + 6]), "+f"(d[RO + 7]), "+f"(d[RO + 8]), "+f"(d[RO + 9]), "+f"(d[RO + 10]), "+f"(d[RO + 11]), "+f"(d[RO + 12]), "+f"(d[RO + 13]), "+f"(d[RO + 14]), "+f"(d[RO + 15]), "+f"(d[RO + 16]), "+f"(d[RO + 17]), "+f"(d[RO + 18]), "+f"(d[RO + 19]), "+f"(d[RO + 20]), "+f"(d[RO + 21]), "+f"(d[RO + 22]), "+f"(d[RO + 23]), "+f"(d[RO + 24]), "+f"(d[RO + 25]), "+f"(d[RO + 26]), "+f"(d[RO + 27]), "+f"(d[RO + 28]), "+f"(d[RO + 29]), "+f"(d[RO + 30]), "+f"(d[RO + 31])
    : "r"(a.x), "r"(a.y), "r"(a.z), "r"(a.w), "l"(base), "r"(scale_d), "n"(OFF >> 4));
}
template <long long OFF, int RO = 0, int N>
__device__ __forceinline__ void wgmma_rs_n128(float (&d)[N], const uint4& a, uint64_t base, int scale_d) {
  asm volatile("{\n.reg .pred p;\n.reg .b64 t;\nsetp.ne.b32 p, %69, 0;\nadd.s64 t, %68, %70;\n"
    "wgmma.mma_async.sync.aligned.m64n128k16.f32.bf16.bf16 {%0, %1, %2, %3, %4, %5, %6, %7, %8, %9, %10, %11, %12, %13, %14, %15, %16, %17, %18, %19, %20, %21, %22, %23, %24, %25, %26, %27, %28, %29, %30, %31, %32, %33, %34, %35, %36, %37, %38, %39, %40, %41, %42, %43, %44, %45, %46, %47, %48, %49, %50, %51, %52, %53, %54, %55, %56, %57, %58, %59, %60, %61, %62, %63}, {%64, %65, %66, %67}, t, p, 1, 1, 1;\n}\n"
    : "+f"(d[RO + 0]), "+f"(d[RO + 1]), "+f"(d[RO + 2]), "+f"(d[RO + 3]), "+f"(d[RO + 4]), "+f"(d[RO + 5]), "+f"(d[RO + 6]), "+f"(d[RO + 7]), "+f"(d[RO + 8]), "+f"(d[RO + 9]), "+f"(d[RO + 10]), "+f"(d[RO + 11]), "+f"(d[RO + 12]), "+f"(d[RO + 13]), "+f"(d[RO + 14]), "+f"(d[RO + 15]), "+f"(d[RO + 16]), "+f"(d[RO + 17]), "+f"(d[RO + 18]), "+f"(d[RO + 19]), "+f"(d[RO + 20]), "+f"(d[RO + 21]), "+f"(d[RO + 22]), "+f"(d[RO + 23]), "+f"(d[RO + 24]), "+f"(d[RO + 25]), "+f"(d[RO + 26]), "+f"(d[RO + 27]), "+f"(d[RO + 28]), "+f"(d[RO + 29]), "+f"(d[RO + 30]), "+f"(d[RO + 31]), "+f"(d[RO + 32]), "+f"(d[RO + 33]), "+f"(d[RO + 34]), "+f"(d[RO + 35]), "+f"(d[RO + 36]), "+f"(d[RO + 37]), "+f"(d[RO + 38]), "+f"(d[RO + 39]), "+f"(d[RO + 40]), "+f"(d[RO + 41]), "+f"(d[RO + 42]), "+f"(d[RO + 43]), "+f"(d[RO + 44]), "+f"(d[RO + 45]), "+f"(d[RO + 46]), "+f"(d[RO + 47]), "+f"(d[RO + 48]), "+f"(d[RO + 49]), "+f"(d[RO + 50]), "+f"(d[RO + 51]), "+f"(d[RO + 52]), "+f"(d[RO + 53]), "+f"(d[RO + 54]), "+f"(d[RO + 55]), "+f"(d[RO + 56]), "+f"(d[RO + 57]), "+f"(d[RO + 58]), "+f"(d[RO + 59]), "+f"(d[RO + 60]), "+f"(d[RO + 61]), "+f"(d[RO + 62]), "+f"(d[RO + 63])
    : "r"(a.x), "r"(a.y), "r"(a.z), "r"(a.w), "l"(base), "r"(scale_d), "n"(OFF >> 4));
}
template <int OFFA, int OFFB>
__device__ __forceinline__ void wgmma_ss_n64(float (&d)[32], uint64_t basea, uint64_t baseb, int scale_d) {
  asm volatile("{\n.reg .pred p;\n.reg .b64 t, u;\nsetp.ne.b32 p, %34, 0;\nadd.s64 t, %32, %35;\nadd.s64 u, %33, %36;\n"
    "wgmma.mma_async.sync.aligned.m64n64k16.f32.bf16.bf16 {%0, %1, %2, %3, %4, %5, %6, %7, %8, %9, %10, %11, %12, %13, %14, %15, %16, %17, %18, %19, %20, %21, %22, %23, %24, %25, %26, %27, %28, %29, %30, %31}, t, u, p, 1, 1, 1, 1;\n}\n"
    : "+f"(d[0]), "+f"(d[1]), "+f"(d[2]), "+f"(d[3]), "+f"(d[4]), "+f"(d[5]), "+f"(d[6]), "+f"(d[7]), "+f"(d[8]), "+f"(d[9]), "+f"(d[10]), "+f"(d[11]), "+f"(d[12]), "+f"(d[13]), "+f"(d[14]), "+f"(d[15]), "+f"(d[16]), "+f"(d[17]), "+f"(d[18]), "+f"(d[19]), "+f"(d[20]), "+f"(d[21]), "+f"(d[22]), "+f"(d[23]), "+f"(d[24]), "+f"(d[25]), "+f"(d[26]), "+f"(d[27]), "+f"(d[28]), "+f"(d[29]), "+f"(d[30]), "+f"(d[31])
    : "l"(basea), "l"(baseb), "r"(scale_d), "n"(OFFA >> 4), "n"(OFFB >> 4));
}

__device__ __forceinline__ void publish7(char* b16, char* b8, const uint32_t (&P)[14], uint32_t par) {
  st_rlx4(b16, tag(P[0], par), P[1], P[2], P[3]);
  st_rlx4(b16 + 512, tag(P[4], par), P[5], P[6], P[7]);
  st_rlx4(b16 + 1024, tag(P[8], par), P[9], P[10], P[11]);
  st_rlx2(b8, tag(P[12], par), P[13]);
}
template <int GOFF>
__device__ __forceinline__ void fix7(uint4* v, const char* g, uint32_t par, int& budget) {
  asm volatile("{\n.reg .pred p;\n.reg .b32 t, w<4>;\nsetp.eq.s32 p, %28, 0;\nC:\n@!p bra.uni L;\nadd.s32 %28, %28, -1;\n"
               "ld.relaxed.gpu.global.v4.u32 {%0,%1,%2,%3}, [%29+%31+0];\n"
               "ld.relaxed.gpu.global.v4.u32 {%4,%5,%6,%7}, [%29+%31+512];\n"
               "ld.relaxed.gpu.global.v4.u32 {%8,%9,%10,%11}, [%29+%31+1024];\n"
               "ld.relaxed.gpu.global.v4.u32 {%12,%13,%14,%15}, [%29+%31+1536];\n"
               "ld.relaxed.gpu.global.v4.u32 {%16,%17,%18,%19}, [%29+%31+2048];\n"
               "ld.relaxed.gpu.global.v4.u32 {%20,%21,%22,%23}, [%29+%31+2560];\n"
               "ld.relaxed.gpu.global.v4.u32 {%24,%25,%26,%27}, [%29+%31+3072];\n"
               "L:\nlop3.b32 w0, %0, %4, %30, 0x7e;\nlop3.b32 w1, %8, %12, %30, 0x7e;\nlop3.b32 w2, %16, %20, %30, 0x7e;\nxor.b32 w3, %24, %30;\n"
               "lop3.b32 t, w0, w1, w2, 0xfe;\nlop3.b32 t, t, w3, 1, 0xa8;\n"
               "setp.ne.u32 p, t, 0;\nsetp.gt.and.s32 p, %28, 0, p;\nvote.sync.any.pred p, p, 0xffffffff;\n@p bra.uni C;\n}"
               : "+r"(v[0].x), "+r"(v[0].y), "+r"(v[0].z), "+r"(v[0].w), "+r"(v[1].x), "+r"(v[1].y), "+r"(v[1].z), "+r"(v[1].w), "+r"(v[2].x), "+r"(v[2].y), "+r"(v[2].z), "+r"(v[2].w), "+r"(v[3].x), "+r"(v[3].y), "+r"(v[3].z), "+r"(v[3].w), "+r"(v[4].x), "+r"(v[4].y), "+r"(v[4].z), "+r"(v[4].w), "+r"(v[5].x), "+r"(v[5].y), "+r"(v[5].z), "+r"(v[5].w), "+r"(v[6].x), "+r"(v[6].y), "+r"(v[6].z), "+r"(v[6].w), "+r"(budget)
               : "l"(g), "r"(par), "n"(GOFF) : "memory");
}
template <int SOFF>
__device__ __forceinline__ void load7s(uint4* v, uint32_t s, uint32_t s8) {
  asm volatile("ld.shared.v4.u32 {%0,%1,%2,%3}, [%28+%30+0];\n"
               "ld.shared.v4.u32 {%4,%5,%6,%7}, [%28+%30+512];\n"
               "ld.shared.v4.u32 {%8,%9,%10,%11}, [%28+%30+1024];\n"
               "ld.shared.v2.u32 {%12,%13}, [%29+%30+1536];\nld.shared.v2.u32 {%14,%15}, [%29+%30+1792];\n"
               "ld.shared.v4.u32 {%16,%17,%18,%19}, [%28+%30+2048];\n"
               "ld.shared.v4.u32 {%20,%21,%22,%23}, [%28+%30+2560];\n"
               "ld.shared.v4.u32 {%24,%25,%26,%27}, [%28+%30+3072];\n"
               : "=r"(v[0].x), "=r"(v[0].y), "=r"(v[0].z), "=r"(v[0].w), "=r"(v[1].x), "=r"(v[1].y), "=r"(v[1].z), "=r"(v[1].w), "=r"(v[2].x), "=r"(v[2].y), "=r"(v[2].z), "=r"(v[2].w), "=r"(v[3].x), "=r"(v[3].y), "=r"(v[3].z), "=r"(v[3].w), "=r"(v[4].x), "=r"(v[4].y), "=r"(v[4].z), "=r"(v[4].w), "=r"(v[5].x), "=r"(v[5].y), "=r"(v[5].z), "=r"(v[5].w), "=r"(v[6].x), "=r"(v[6].y), "=r"(v[6].z), "=r"(v[6].w)
               : "r"(s), "r"(s8), "n"(SOFF) : "memory");
}
template <int GOFF>
__device__ __forceinline__ void fix7s(uint4* v, const char* g, uint32_t par, int& budget) {
  asm volatile("{\n.reg .pred p;\n.reg .b32 t, w<4>;\n.reg .b64 h;\nsetp.eq.s32 p, %28, 0;\nC:\n@!p bra.uni L;\n"
               "add.s32 %28, %28, -1;\nmov.u32 t, %%laneid;\nmad.wide.s32 h, t, -8, %29;\n"
               "ld.relaxed.gpu.global.v4.u32 {%0,%1,%2,%3}, [%29+%31+0];\n"
               "ld.relaxed.gpu.global.v4.u32 {%4,%5,%6,%7}, [%29+%31+512];\n"
               "ld.relaxed.gpu.global.v4.u32 {%8,%9,%10,%11}, [%29+%31+1024];\n"
               "ld.relaxed.gpu.global.v2.u32 {%12,%13}, [h+%31+1536];\nld.relaxed.gpu.global.v2.u32 {%14,%15}, [h+%31+1792];\n"
               "ld.relaxed.gpu.global.v4.u32 {%16,%17,%18,%19}, [%29+%31+2048];\n"
               "ld.relaxed.gpu.global.v4.u32 {%20,%21,%22,%23}, [%29+%31+2560];\n"
               "ld.relaxed.gpu.global.v4.u32 {%24,%25,%26,%27}, [%29+%31+3072];\nL:\n"
               "lop3.b32 w0, %0, %4, %30, 0x7e;\nlop3.b32 w1, %8, %12, %30, 0x7e;\nlop3.b32 w2, %14, %16, %30, 0x7e;\nlop3.b32 w3, %20, %24, %30, 0x7e;\n"
               "lop3.b32 t, w0, w1, w2, 0xfe;\nlop3.b32 t, t, w3, 1, 0xa8;\n"
               "setp.ne.u32 p, t, 0;\nsetp.gt.and.s32 p, %28, 0, p;\nvote.sync.any.pred p, p, 0xffffffff;\n@p bra.uni C;\n}"
               : "+r"(v[0].x), "+r"(v[0].y), "+r"(v[0].z), "+r"(v[0].w), "+r"(v[1].x), "+r"(v[1].y), "+r"(v[1].z), "+r"(v[1].w), "+r"(v[2].x), "+r"(v[2].y), "+r"(v[2].z), "+r"(v[2].w), "+r"(v[3].x), "+r"(v[3].y), "+r"(v[3].z), "+r"(v[3].w), "+r"(v[4].x), "+r"(v[4].y), "+r"(v[4].z), "+r"(v[4].w), "+r"(v[5].x), "+r"(v[5].y), "+r"(v[5].z), "+r"(v[5].w), "+r"(v[6].x), "+r"(v[6].y), "+r"(v[6].z), "+r"(v[6].w), "+r"(budget)
               : "l"(g), "r"(par), "n"(GOFF) : "memory");
}
template <int GOFF>
__device__ __forceinline__ void fix7t(uint4* v, const char* base, uint32_t off, uint32_t s, uint32_t s8, uint32_t par, int& budget) {
  asm volatile("{\n.reg .pred p;\n.reg .b32 t, w<4>;\n.reg .b64 g, h;\nC:\n"
               "lop3.b32 w0, %0, %4, %30, 0x7e;\nlop3.b32 w1, %8, %12, %30, 0x7e;\nlop3.b32 w2, %14, %16, %30, 0x7e;\nlop3.b32 w3, %20, %24, %30, 0x7e;\n"
               "lop3.b32 t, w0, w1, w2, 0xfe;\nlop3.b32 t, t, w3, 1, 0xa8;\n"
               "setp.ne.u32 p, t, 0;\nvote.sync.any.pred p, p, 0xffffffff;\n@!p bra.uni L;\n"
               "add.s32 %28, %28, -1;\nsetp.le.s32 p, %28, 0;\n@p bra.uni L;\n"
               "add.u32 t, %32, %33;\nmad.wide.u32 g, t, 1, %29;\nadd.u32 t, %32, %34;\nmad.wide.u32 h, t, 1, %29;\n"
               "ld.relaxed.gpu.global.v4.u32 {%0,%1,%2,%3}, [g+%31+0];\n"
               "ld.relaxed.gpu.global.v4.u32 {%4,%5,%6,%7}, [g+%31+512];\n"
               "ld.relaxed.gpu.global.v4.u32 {%8,%9,%10,%11}, [g+%31+1024];\n"
               "ld.relaxed.gpu.global.v2.u32 {%12,%13}, [h+%31+1536];\nld.relaxed.gpu.global.v2.u32 {%14,%15}, [h+%31+1792];\n"
               "ld.relaxed.gpu.global.v4.u32 {%16,%17,%18,%19}, [g+%31+2048];\n"
               "ld.relaxed.gpu.global.v4.u32 {%20,%21,%22,%23}, [g+%31+2560];\n"
               "ld.relaxed.gpu.global.v4.u32 {%24,%25,%26,%27}, [g+%31+3072];\nbra.uni C;\nL:\n}"
               : "+r"(v[0].x), "+r"(v[0].y), "+r"(v[0].z), "+r"(v[0].w), "+r"(v[1].x), "+r"(v[1].y), "+r"(v[1].z), "+r"(v[1].w), "+r"(v[2].x), "+r"(v[2].y), "+r"(v[2].z), "+r"(v[2].w), "+r"(v[3].x), "+r"(v[3].y), "+r"(v[3].z), "+r"(v[3].w), "+r"(v[4].x), "+r"(v[4].y), "+r"(v[4].z), "+r"(v[4].w), "+r"(v[5].x), "+r"(v[5].y), "+r"(v[5].z), "+r"(v[5].w), "+r"(v[6].x), "+r"(v[6].y), "+r"(v[6].z), "+r"(v[6].w), "+r"(budget)
               : "l"(base), "r"(par), "n"(GOFF - (int)sb - OFF_G), "r"(off), "r"(s), "r"(s8) : "memory");
}
template <int OFF>
__device__ __forceinline__ void fixq(uint4& v, uint32_t a, uint32_t s, const char* g, uint32_t par, int& budget) {
  asm volatile("{\n.reg .pred p;\n.reg .b32 t, u, i, w<4>;\n.reg .b64 h;\nsetp.eq.s32 p, %4, 0;\nC:\n@!p bra.uni L;\n"
               "add.s32 %4, %4, -1;\nmov.u32 i, 0;\nR:\nmad.wide.u32 h, i, 1, %7;\n"
               "ld.relaxed.gpu.global.v4.u32 {w0,w1,w2,w3}, [h+%9];\nadd.u32 t, i, %6;\nst.shared.v4.u32 [t+%9], {w0,w1,w2,w3};\n"
               "add.u32 i, i, 512;\nsetp.lt.u32 p, i, 3584;\n@p bra.uni R;\n"
               "fence.proxy.async.shared::cta;\nbar.warp.sync 0xffffffff;\n"
               "ld.shared.u32 %0, [%5+%9];\nld.shared.u32 %1, [%5+%9+896];\nld.shared.u32 %2, [%5+%9+1792];\nld.shared.u32 %3, [%5+%9+2688];\n"
               "L:\nlop3.b32 t, %0, %1, %8, 0x7e;\nlop3.b32 u, %2, %3, %8, 0x7e;\nlop3.b32 t, t, u, 1, 0xa8;\n"
               "setp.ne.u32 p, t, 0;\nsetp.gt.and.s32 p, %4, 0, p;\nvote.sync.any.pred p, p, 0xffffffff;\n@p bra.uni C;\n}"
               : "+r"(v.x), "+r"(v.y), "+r"(v.z), "+r"(v.w), "+r"(budget)
               : "r"(a), "r"(s), "l"(g), "r"(par), "n"(OFF) : "memory");
}
#define SPINS(i)
#define RETRY(i, ...) __VA_ARGS__
#define BAR(i) (sb + SMEM_BAR + 8 * (i))
#define WAIT(b, ph) mbar_wait(b, ph, budget)

template <bool SWAP>
__global__ void __launch_bounds__(384, 1)
fused_block_kernel(char* const buf, const char* __restrict__ wo, const uint64_t d128, const uint64_t d64, const uint64_t d0,
                   const uint64_t dq, const uint64_t d1, const uint64_t dko,
                   const char* __restrict__ wg, const char* __restrict__ wu, const char* __restrict__ wd, const char* __restrict__ wq, char* __restrict__ out,
                   const __grid_constant__ CUtensorMap map_x, const __grid_constant__ CUtensorMap map_qkv,
                   const __grid_constant__ CUtensorMap map_wo, const __grid_constant__ CUtensorMap map_gu,
                   const __grid_constant__ CUtensorMap map_gu32) {
  extern __shared__ __align__(1024) uint8_t smem[];
  const int tid = threadIdx.x, lane = tid & 31;
  const int warp = __shfl_sync(0xffffffffu, tid >> 5, 0);
#define LPOS 1
#define LREL 1
#define WPOS 1
#define SQB 1
#define EREL 0
#define GGATE 2
#define SQV 3
#define RPK 15
#define OPUB 14
#define WOPOS 0
#define HRED 4
#define HRED1 4
#define ORED 2
#define MPF 0
  const int cta = (blockIdx.x & 56) * 2 + (blockIdx.x & 1) * 8 + (blockIdx.x & 6) + (blockIdx.x >> 6), r = cta >> 3, p = cta & 7;
  const int kh = p & 1;
  const int wcol = 56 * p - 8 * kh;
  int budget = SPIN_LIMIT;
  STAMP(0);
  if (warp < 8) {
    STAMP(60);
    const uint32_t par = ~ld_rlx1(&g_epoch[cta * 32]) & 1;
    bar_sync<0, 384>();
    STAMP(63);
    asm volatile("setmaxnreg.inc.sync.aligned.u32 224;");
    STAMP(61);
    const int g = warp >> 2, gq = lane >> 2, tq = lane & 3;
    const uint64_t dk = d128 + kh;
    uint4 A[28];
    float rs0, rs1, m0, m1;
    float acc0[28], acc1[28];
    uint32_t mb0, mb1;
    {
      uint32_t la[4];
#pragma unroll
      for (int i = 0; i < 4; i++) {
        la[i] = sb + OFF_X + warp * TILE + (lane & 15) * 128 + (((2 * i + (lane >> 4)) ^ (lane & 7)) << 4);
        asm volatile("" : "+r"(la[i]));
      }
      STAMP(62);
      WAIT(BAR(B_XB + warp), 0);
      STAMP(1);
#pragma unroll
      for (int ks = 0; ks < 28; ks++) A[ks] = ldsm4(la[ks & 3] + (ks >> 2) * 2048);
      float cs[4][4] = {};
#pragma unroll
      for (int ks = 0; ks < 28; ks++) mma16816(cs[ks & 3], A[ks].x, A[ks].y, A[ks].z, A[ks].w, 0x3F803F80u, 0x3F803F80u);
      m0 = ((cs[0][0] + cs[1][0]) + (cs[2][0] + cs[3][0])) * (1.f / DM);
      m1 = ((cs[0][2] + cs[1][2]) + (cs[2][2] + cs[3][2])) * (1.f / DM);
      mb0 = pack2(m0, m0); mb1 = pack2(m1, m1);
      asm volatile("" ::"r"(mb0) : "memory");
      __syncwarp();
      if (lane == 0) mbar_arrive(BAR(B_XFREE));
      if (tq < 2) sts1(sb + OFF_M + warp * 64 + gq * 4 + tq * 32, __float_as_uint(tq ? m1 : m0));
    }
    STAMP(2);
    uint32_t pa[7];
    {
      const uint32_t prow = sb + OFF_PK + warp * 4096 + gq * 128 + (gq << 4), t = tq >> 1;
      const uint32_t b2 = (prow + ((4 * tq + 8) & 15)) ^ (t << 4);
      pa[0] = prow + 4 * tq; pa[1] = pa[0] ^ 16; pa[2] = pa[0] ^ 32;
      pa[3] = (prow + 4 * (tq & 1)) ^ (48 + 16 * t);
      pa[4] = b2 ^ 64; pa[5] = b2 ^ 80 ^ (t << 5); pa[6] = b2 ^ 96;
#pragma unroll
      for (int j = 0; j < 7; j++) asm volatile("" : "+r"(pa[j]));
    }
    auto sqs = [&](int q) {
      uint4 s;
#pragma unroll
      for (int ks = 7 * q; ks < 7 * q + 7; ks++) {
        if (ks % 7 == 0) s = make_uint4(sq2(A[ks].x), sq2(A[ks].y), sq2(A[ks].z), sq2(A[ks].w));
        else s = make_uint4(sq2(A[ks].x, s.x), sq2(A[ks].y, s.y), sq2(A[ks].z, s.z), sq2(A[ks].w, s.w));
      }
      s.x = add2(s.x, s.z);
      s.y = add2(s.y, s.w);
      rs0 = (q ? rs0 : 0.f) + (bf_lo(s.x) + bf_hi(s.x));
      rs1 = (q ? rs1 : 0.f) + (bf_lo(s.y) + bf_hi(s.y));
      if (q == 3) {
        rs0 += shx(rs0, 1); rs1 += shx(rs1, 1);
        rs0 += shx(rs0, 2); rs1 += shx(rs1, 2);
      }
      asm volatile("" : "+f"(rs0), "+f"(rs1));
    };
    auto sub = [&](int q) {
#pragma unroll
      for (int ks = 7 * q; ks < 7 * q + 7; ks++)
        A[ks] = make_uint4(sub2(A[ks].x, mb0), sub2(A[ks].y, mb1), sub2(A[ks].z, mb0), sub2(A[ks].w, mb1));
    };
    uint32_t sdw;
    float4 c0, c1;
    auto stats = [&] {
      const float d0 = m0 - bf_lo(mb0), d1 = m1 - bf_lo(mb1);
      const float q0 = fmaxf(rs0 * (1.f / DM) - d0 * d0, 0.f) + 1e-5f;
      const float q1 = fmaxf(rs1 * (1.f / DM) - d1 * d1, 0.f) + 1e-5f;
      rs0 = rsqf(q0);
      rs1 = rsqf(q1);
      const float sd = (tq & 2 ? q1 * rs1 : q0 * rs0);
      sdw = pack2(sd, sd - bf_lo(pack2(sd, 0.f)));
      c0 = make_float4(rs0 * 1.4426950408889634f, lg2f(rs0), rs0 * rs0, 1e-6f * rs0);
      c1 = make_float4(rs1 * 1.4426950408889634f, lg2f(rs1), rs1 * rs1, 1e-6f * rs1);
      asm volatile("" : "+r"(sdw), "+f"(c0.x), "+f"(c0.y), "+f"(c0.z), "+f"(c0.w), "+f"(c1.x), "+f"(c1.y), "+f"(c1.z), "+f"(c1.w));
    };
    sub(0);
    sub(1);
    sqs(0);
    sfor<4>([&](auto J) {
      constexpr int j = J;
      WAIT(BAR(B_K + j), 0);
      STAMP(26 + j);
      if (j == 0 && g) bar_sync<7, 256>();
      wg_fence();
      sfor<7>([&](auto I) { wgmma_rs_n56<2 * STG + (7 * j + I) * 2048>(acc0, A[7 * j + I], dk, j + I != 0); });
      if (j == 0 && !g) bar_arrive<7, 256>();
      if (j < 2) sub(j + 2);
      if (j < 3) sqs(j + 1);
      if (j == 2) stats();
    });
    wg_commit();
    STAMP(3);
    WAIT(BAR(B_V), 0);
    STAMP(10);
    wg_fence();
    sfor<7>([&](auto I) { wgmma_rs_n56<I * 2048>(acc1, A[I], dk, I != 0); });
    wg_commit();
    WAIT(BAR(B_XFREE), 0);
    wg_wait<1>();
    acc_fence(acc0);
    STAMP(4);
    if (lane == 0) mbar_arrive(BAR(B_KFREE));
    sfor<7>([&](auto J) {
      constexpr int j = J;
      sfor<3>([&](auto I) {
        constexpr int ks = 7 + 3 * j + I;
        if (ks % 7 == 0) { WAIT(BAR(B_V + ks / 7), 0); STAMP(49 + ks / 7); wg_fence(); }
        wgmma_rs_n56<ks * 2048>(acc1, A[ks], dk, 1);
      });
      sts1(pa[j], pack2(phi(acc0[4 * j], c0), phi(acc0[4 * j + 1], c0)));
      sts1(pa[j] + 1024, pack2(phi(acc0[4 * j + 2], c1), phi(acc0[4 * j + 3], c1)));
    });
    wg_commit();
    if (g == 1) bar_arrive<3, 256>();
    sts1(((pa[0] & ~15u) ^ (48 + 64 * (tq & 1))) + 2048 + 8 + ((tq >> 1) << 10), sdw);
    wg_wait<0>();
    acc_fence(acc1);
    STAMP(5);
#pragma unroll
    for (int j = 0; j < 7; j++) {
      sts1(pa[j] + 2048, pack2(acc1[4 * j], acc1[4 * j + 1]));
      sts1(pa[j] + 3072, pack2(acc1[4 * j + 2], acc1[4 * j + 3]));
    }
    fence_async_smem();
    if (lane == 0) mbar_arrive(BAR(B_VFREE));
    if (g == 0) {
      bar_arrive<1, 256>();
      bar_sync<3, 256>();
    } else {
      bar_sync<1, 256>();
      float kv[32];
      wg_fence();
      sfor<8>([&](auto I) {
        constexpr int o = OFF_PK + I * 4096;
        wgmma_ss_n64<o, o + 2048>(kv, d128, d128, I != 0);
      });
      wg_commit();
      WAIT(BAR(B_INIT), 0);
      char* dst = buf + (A_KVR + p * KVR_B) + (uint32_t)((tid - 128) * 16);
      wg_wait<0>();
      acc_fence(kv);
#define S(i) (warp & 2 ? kv[16 + i] : kv[i])
      red_add4(dst, S(0), S(1), S(4));
      red_add4(dst + 2048, S(5), S(8), S(9));
      red_add4(dst + 4096, S(2), S(3), S(6));
      red_add4(dst + 6144, S(7), S(10), S(11));
      red_add4(dst + 8192, S(12), S(13), S(14));
      red_add2(dst + 10240 - (tid - 128) * 8, S(15));
    }
    STAMP(6);
    WAIT(BAR(B_Q), 0);
    wg_fence();
    sfor<28>([&](auto I) { wgmma_rs_n56<I * 2048>(acc0, A[I], dq + kh, I != 0); });
    wg_commit();
    const uint32_t wb = BAR(B_WB) + 32 * g;
    const int wq4 = warp & 3;
    char* const oblk = buf + (A_O + (r * 2 + g) * 2 * STG);
    const uint32_t gsub = sb + OFF_G + wq4 * 3584 + lane * 16, gsub8 = gsub - lane * 8;
    const char* const olane = oblk + (uint32_t)(wq4 * 3584 + lane * 16);
    char* const ob = oblk + (uint32_t)((p >> 1) * TILE + wq4 * 3584 + kh * 896 + gq * 16);
    char *ob16 = ob + tq * 128, *ob8 = ob + 512 + (tq >> 1) * 128 + (tq & 1) * 8, *ob4 = ob + 768 + tq * 4;
    unsigned* cnt = &g_cnt[C_ROW + r * 32];
    asm volatile("" : "+l"(ob16), "+l"(ob8), "+l"(ob4), "+l"(cnt));
    wg_wait<0>();
    acc_fence(acc0);
    STAMP(7);
    if (lane < 2) mbar_arrive(BAR(B_QFREE + lane));
    uint32_t R[14];
    {
      uint4 Q[4];
#pragma unroll
      for (int j = 0; j < 7; j++) {
        const uint32_t lo = pack2(phi(acc0[4 * j], c0), phi(acc0[4 * j + 1], c0));
        const uint32_t hi = pack2(phi(acc0[4 * j + 2], c1), phi(acc0[4 * j + 3], c1));
        if (j & 1) { Q[j >> 1].z = lo; Q[j >> 1].w = hi; } else { Q[j >> 1].x = lo; Q[j >> 1].y = hi; }
      }
      Q[3].z = 0; Q[3].w = 0;
      STAMP(8);
      WAIT(BAR(B_KVB), 0);
      STAMP(9);
      float o[32];
      wg_fence();
      sfor<4>([&](auto I) { wgmma_rs_n64<OFF_KVB + I * 2048>(o, Q[I], d128, I != 0); });
      wg_commit();
      if (ORED == 1 && lane == 0) red_inc(cnt);
      wg_wait<0>();
      if (ORED == 2 && lane == 0) red_inc(cnt);
      acc_fence(o);
      if (ORED == 3 && lane == 0) red_inc(cnt);
      const float da0 = rcpf(o[28] + c0.w), db0 = rcpf(o[29] + c0.w), da1 = rcpf(o[30] + c1.w), db1 = rcpf(o[31] + c1.w);
      uint32_t P[14];
#pragma unroll
      for (int j = 0; j < 7; j++) {
        const bool first = j < 2 || (j < 4 && tq < 3);
        const float s0 = first ? da0 : db0, s1 = first ? da1 : db1;
        P[2 * j] = pack2(o[4 * j] * s0, o[4 * j + 1] * s0);
        P[2 * j + 1] = pack2(o[4 * j + 2] * s1, o[4 * j + 3] * s1);
        if (0x53 >> j & 1) { P[2 * j] = tag(P[2 * j], par); P[2 * j + 1] = tag(P[2 * j + 1], par); }
      }
      auto publish = [&] {
#pragma unroll
        for (int h = 0; h < 2; h++) {
          st_rlx4(ob16 + 1792 * h, P[h], P[2 + h], P[4 + h], P[6 + h]);
          st_rlx2(ob8 + 1792 * h, P[8 + h], P[10 + h]);
          st_rlx1(ob4 + 1792 * h, P[12 + h]);
        }
      };
      if (!g) {
        publish();
        STAMP(11);
        if (lane == 0) mbar_arrive(BAR(B_OFREE));
        const int sec = min(lane, 27);
        uint32_t ta = sb + OFF_G + wq4 * 3584 + sec * 32 + (0x3625410 >> (sec & 28) & 7) * 4;
        const char* ol = olane;
        asm volatile("" : "+r"(ta), "+l"(ol));
#pragma unroll 1
        for (int h = 0; h < 2; h++) {
          sfor<4>([&](auto Q) {
            constexpr int so = Q * TILE;
            WAIT(BAR(B_WB + Q) + 32 * h, 0);
            STAMPD(1 + 4 * h + Q);
            uint4 tg = make_uint4(lds1(ta + so), lds1(ta + so + 896), lds1(ta + so + 1792), lds1(ta + so + 2688));
            RETRY(4 * h + Q, fixq<so>(tg, ta, gsub, ol, par, budget));
            bar_arrive<8 + Q, 256>();
          });
          ol += 2 * STG;
        }
        bar_sync<12, 256>();
      } else {
        const uint32_t wa = sb + (lane >> 4) * 1024 + (lane & 7) * 128 + ((((2 * wq4 + (lane >> 3 & 1) + kh) ^ lane) & 7) << 4);
        uint4 X[8];
#pragma unroll
        for (int i = 0; i < 8; i++) X[i] = ldsm4t(wa + OFF_XS + i * 2048);
        if (lane == 0) mbar_arrive(BAR(B_OFREE));
        WAIT(BAR(B_WO), 0);
        const uint32_t keep = wq4 < 3 ? 0x3F803F80u : 0;
#pragma unroll
        for (int ks = 0; ks < 28; ks++) {
          if (ks == OPUB) {
            WAIT(BAR(B_WO), 0);
            publish();
            STAMP(11);
            WAIT(BAR(B_WO), 0);
          }
          A[ks] = ldsm4t(wa + OFF_WO + ks * 2048);
        }
#pragma unroll
        for (int i = 0; i < 14; i++) {
          const uint4 w = lds4(sb + OFF_WBAR + i * 64 + tq * 16);
          A[2 * i] = make_uint4(add2(A[2 * i].x, w.x), fma2(A[2 * i].y, keep, w.x), add2(A[2 * i].z, w.y), fma2(A[2 * i].w, keep, w.y));
          A[2 * i + 1] = make_uint4(add2(A[2 * i + 1].x, w.z), fma2(A[2 * i + 1].y, keep, w.z), add2(A[2 * i + 1].z, w.w), fma2(A[2 * i + 1].w, keep, w.w));
          asm volatile("" : "+r"(A[2 * i].x), "+r"(A[2 * i].y), "+r"(A[2 * i].z), "+r"(A[2 * i].w),
                            "+r"(A[2 * i + 1].x), "+r"(A[2 * i + 1].y), "+r"(A[2 * i + 1].z), "+r"(A[2 * i + 1].w)::"memory");
        }
        __syncwarp();
        if (lane < 2) mbar_arrive(BAR(B_WOFREE));
        STAMP(10);
        float hacc[2][32];
        uint32_t ma = sb + OFF_M + tq * 8;
        asm volatile("" : "+r"(ma));
#pragma unroll
        for (int j = 0; j < 16; j++) {
          const uint2 m = lds2(ma + 32 * j);
          const uint32_t lo = j & 1 ? X[j / 2].z : X[j / 2].x, hi = keep ? (j & 1 ? X[j / 2].w : X[j / 2].y) : 0;
          float* a = &hacc[j / 8][4 * (j & 7)];
          a[0] = bf_lo(lo) - __uint_as_float(m.x);
          a[1] = bf_hi(lo) - __uint_as_float(m.y);
          a[2] = bf_lo(hi) - __uint_as_float(m.x);
          a[3] = bf_hi(hi) - __uint_as_float(m.y);
        }
        acc_fence(hacc[0]);
        acc_fence(hacc[1]);
        char* hb = oblk + (uint32_t)(FRAG_B - 2 * STG + (p >> 1) * TILE + (wq4 < 3 ? kh * 2048 + wq4 * 512 + lane * 16 : 1536 + kh * 256 + lane * 8));
        asm volatile("" : "+l"(hb));
        STAMP(16);
        sfor<2>([&](auto H) {
          constexpr int h = H;
          sfor<4>([&](auto Q) {
            constexpr int q = Q;
            bar_sync<8 + q, 256>();
            STAMP(1 + 4 * h + q);
            wg_fence();
            sfor<7>([&](auto I) { wgmma_rk_n64<OFF_G + q * TILE + I * 256>(hacc[h], A[7 * q + I], dko, 1); });
            wg_commit();
            if (q == (h ? HRED1 : HRED)) {
              if (h) bar_sync<6, 160>();
              if (lane == 0) red_inc(cnt + 2 + h);
            }
            if (q) {
              wg_wait<1>();
              if (lane < 2) mbar_arrive(BAR(B_ORD + q - 1));
            }
          });
          if ((h ? HRED1 : HRED) == 4) {
            if (h) bar_sync<6, 160>();
            if (lane == 0) red_inc(cnt + 2 + h);
          }
          wg_wait<0>();
          acc_fence(hacc[h]);
          STAMP(12 + 2 * h);
          if (lane < 2) mbar_arrive(BAR(B_ORD + 3));
          if (wq4 < 3) {
#pragma unroll
            for (int i = 0; i < 4; i++) {
              const float* a = hacc[h] + 8 * i;
              st_rlx4(hb + h * 2 * STG + 3584 * i, tag(transp(pack2(a[0], a[1])), par), transp(pack2(a[4], a[5])), transp(pack2(a[2], a[3])), transp(pack2(a[6], a[7])));
            }
          } else {
#pragma unroll
            for (int i = 0; i < 4; i++) {
              const float* a = hacc[h] + 8 * i;
              st_rlx2(hb + h * 2 * STG + 3584 * i, tag(transp(pack2(a[0], a[1])), par), transp(pack2(a[4], a[5])));
            }
            if (gq == 0) {
#pragma unroll
              for (int j = 0; j < 8; j++) sts2(ma + 256 * h + 32 * j, __float_as_uint(hacc[h][4 * j + 2]), __float_as_uint(hacc[h][4 * j + 3]));
            }
          }
          STAMP(13 + 2 * h);
          if (h) bar_sync<5, 128>(); else bar_arrive<12, 256>();
        });
      }
      const char* const rb = olane + (FRAG_B + (p >> 1) * TILE);
#pragma unroll
      for (int i = 0; i < 3; i++) {
        const uint4 v = ld_rlx4(rb + kh * 2048 + 512 * i);
        R[4 * i] = v.x; R[4 * i + 1] = v.y; R[4 * i + 2] = v.z; R[4 * i + 3] = v.w;
      }
      const uint2 v = ld_rlx2(rb + 1536 + kh * 256 - lane * 8);
      R[12] = v.x; R[13] = v.y;
    }
    char* hdst = buf + (A_HH + cta * 2 * STG + warp * 3584) + (uint32_t)(lane * 16);
    {
#define GLU(gt, up, e) fmaf((up) * (e), tanhf_((gt) * (e)), (up) * (e))
      float acc[64];
      uint4 own[5];
#pragma unroll
      for (int i = 0; i < 5; i++) asm volatile("" : "=r"(own[i].x), "=r"(own[i].y), "=r"(own[i].z), "=r"(own[i].w));
      sfor<4>([&](auto I) { WAIT(BAR(B_FULL + I), 0); });
      uint32_t relb = g ? BAR(B_HFREE + 2) : BAR(B_ORD);
      const bool rels = lane < 2 - g;
      WAIT(wb, 1);
      STAMP(58);
      load7s<0>(A, gsub, gsub8);
      if (!LREL && rels) mbar_arrive(relb);
#pragma unroll 1
      for (int c = 0; c < 3; c++) {
        const uint32_t half = (c & 1) * 4;
        if (c == 0) {
          sfor<4>([&](auto KQ) {
            constexpr int kq = KQ;
            if ((LPOS == 0 || WPOS) && kq < 3) WAIT(wb + 8 * kq + 8, 1);
            if (WPOS && kq == 3) WAIT(wb, 1);
            RETRY(8 + kq + 4 * g, fix7t<A_H + kq * TILE>(&A[7 * kq], buf, (r * 2 + g) * 2 * STG, gsub, gsub8, par, budget));
            if (LREL && rels) mbar_arrive(relb);
            STAMPD(30 + kq);
            if (LPOS == 1 && !WPOS && kq < 3) WAIT(wb + 8 * kq + 8, 1);
            auto rel = [&] {
              relb += kq == 1 ? 8 : 8 - 8 * g;
              if (!LREL && rels) mbar_arrive(relb);
            };
            if (LPOS == 1 && kq < 3) { load7s<(kq + 1) * TILE>(&A[(7 * kq + 7) % 28], gsub, gsub8); rel(); }
            wg_fence();
            sfor<7>([&](auto I) {
              wgmma_rs_n128<kq * STG + koff(I, 1024)>(acc, A[7 * kq + I], d128, kq + I != 0);
              if (LPOS == 0 && kq < 3) {
                constexpr int o = (kq + 1) * TILE + I * 512;
                if (I == 3) {
                  const uint2 u = lds2(gsub8 + o), v = lds2(gsub8 + o + 256);
                  A[(7 * kq + 10) % 28] = make_uint4(u.x, u.y, v.x, v.y);
                } else A[(7 * kq + 7 + I) % 28] = lds4(gsub + o);
              }
            });
            wg_commit();
            if (LPOS == 2 && kq < 3) { WAIT(wb + 8 * kq + 8, 1); load7s<(kq + 1) * TILE>(&A[(7 * kq + 7) % 28], gsub, gsub8); }
            if (LPOS != 1 && kq < 3) rel();
            if (SQV == 1) sqs(kq);
            else if (SQV == 3) { if (kq == 3) { if (SQB) WAIT(wb, 1); sqs(0); sqs(1); sqs(2); sqs(3); } }
            else if (kq > 1) {
              sqs(2 * kq - 4);
              sqs(2 * kq - 3);
            }
            if (kq == 3) {
              rs0 = 0.5f * rsqf(rs0 * (1.f / DM) + 1e-5f);
              rs1 = 0.5f * rsqf(rs1 * (1.f / DM) + 1e-5f);
            }
            if (EREL ? kq > 0 : kq == 3) {
              wg_wait<1>();
              if (EREL) { if (lane == 0) mbar_arrive(BAR(B_EMPTY + kq - 1)); }
              else if (lane < 3) mbar_arrive(BAR(B_EMPTY + lane));
            }
          });
        } else {
          const uint64_t dc = d128 + half * (STG >> 4);
          if (GGATE && c == 1) WAIT(BAR(B_HFREE + 1 + GGATE), 0);
          sfor<4>([&](auto KQ) {
            constexpr int kq = KQ;
            WAIT(BAR(B_FULL + kq) + 8 * half, c >> 1);
            STAMPD(30 + 4 * c + kq);
            wg_fence();
            sfor<7>([&](auto I) { wgmma_rs_n128<kq * STG + koff(I, 1024)>(acc, A[7 * kq + I], dc, kq + I != 0); });
            wg_commit();
            if (kq > 0) {
              wg_wait<1>();
              if (lane == 0) mbar_arrive(BAR(B_EMPTY + kq - 1) + 8 * half);
            }
          });
        }
        wg_wait<0>();
        acc_fence(acc);
        if (lane == 0) mbar_arrive(BAR(B_EMPTY + 3) + 8 * half);
        STAMPD(17 + c);
        constexpr int GO = SWAP ? 32 : 0, UO = SWAP ? 0 : 32;
        own[0] = own[4];
#pragma unroll
        for (int i = 0; i < 4; i++) {
          uint32_t w[4];
#pragma unroll
          for (int t = 0; t < 2; t++) {
            const int b = 8 * i + 4 * t;
            w[2 * t] = pack2(GLU(acc[GO + b], acc[UO + b], rs0), GLU(acc[GO + b + 1], acc[UO + b + 1], rs0));
            w[2 * t + 1] = pack2(GLU(acc[GO + b + 2], acc[UO + b + 2], rs1), GLU(acc[GO + b + 3], acc[UO + b + 3], rs1));
          }
          if (i == 3 && c == 1) hdst += STG - 3584;
          own[i + 1] = make_uint4(tag(w[0], par), w[1], w[2], w[3]);
          st_rlx4(hdst + i * 512, own[i + 1].x, w[1], w[2], w[3]);
        }
        hdst += 2048;
        if (c == 1 && lane == 0) red_inc(&g_cnt[C_ROW + r * 32 + 4 + 2 * (p & 6) + g]);
      }
      float acct[32];
      sfor<2>([&](auto H) {
        constexpr int h = H;
        WAIT(BAR(B_FULL + 4 + h), 1);
        wg_fence();
        sfor<14>([&](auto I) { wgmma_rs_n64<(4 + h) * STG + I / 7 * (TILE / 2) + koff(I % 7, 512)>(acct, A[14 * h + I], d64, h + I != 0); });
        wg_commit();
      });
      wg_wait<1>();
      if (lane == 0) mbar_arrive(BAR(B_EMPTY + 4));
      wg_wait<0>();
      acc_fence(acct);
      if (lane == 0) mbar_arrive(BAR(B_EMPTY + 5));
      STAMP(20);
      constexpr int GO = SWAP ? 16 : 0, UO = SWAP ? 0 : 16;
#pragma unroll
      for (int i = 0; i < 2; i++) {
        uint32_t w[4];
#pragma unroll
        for (int t = 0; t < 2; t++) {
          const int b = 8 * i + 4 * t;
          w[2 * t] = pack2(GLU(acct[GO + b], acct[UO + b], rs0), GLU(acct[GO + b + 1], acct[UO + b + 1], rs0));
          w[2 * t + 1] = pack2(GLU(acct[GO + b + 2], acct[UO + b + 2], rs1), GLU(acct[GO + b + 3], acct[UO + b + 3], rs1));
        }
        st_rlx4(hdst + i * 512, tag(w[0], par), w[1], w[2], w[3]);
        A[5 + i] = make_uint4(w[0], w[1], w[2], w[3]);
      }
#pragma unroll
      for (int i = 0; i < 5; i++) A[i] = own[i];
    }
    STAMP(21);
    {
      const char* const hnb = hdst + (1 - 2 * kh) * 2 * STG;
      auto send = [&](float (&acc)[28], int x) {
        acc_fence(acc);
        char* const pd = buf + (A_PS + ((cta ^ 2 * x) * 6 + 3 * g + x - 1) * 7168 + (warp & 3) * 1792);
        uint32_t P[14];
#pragma unroll
        for (int j = 0; j < 14; j++) P[j] = pack2(acc[2 * j], acc[2 * j + 1]);
        publish7(pd + (uint32_t)(lane * 16), pd + 1536 + (uint32_t)(lane * 8), P, par);
        if (x < 3 && lane == 0) red_inc(&g_cnt[C_PS + (cta ^ 2 * x) * 8 + g]);
      };
      sfor<4>([&](auto K) {
        constexpr int k = K;
        if (k > 1) {
          wg_wait<1>();
          if (lane == 0) mbar_arrive(BAR(B_EMPTY + k - 2));
        }
        if (k) RETRY(16 + k + 4 * g, fix7<-2560 - (k < 3) * STG>(&A[7 * k], k > 1 ? hnb : hdst, par, budget));
        if (k == 2 && lane < 2) mbar_arrive(BAR(B_HFREE + 1) + 16 * g);
        if (k < 2) {
          WAIT(wb + 8 * k, 0);
#pragma unroll
          for (int i = 0; i < 7; i++) A[7 * k + 7 + i] = lds4(gsub + g * STG + k * TILE + i * 512);
        }
        if (k == 2) {
#pragma unroll
          for (int i = 0; i < 7; i++) A[21 + i] = ld_rlx4(hnb - 2560 + 512 * i);
        }
        WAIT(BAR(B_FULL + k), 0);
        STAMP(42 + k);
        wg_fence();
        sfor<7>([&](auto I) { wgmma_rs_n56<k * STG + I * 3584>(acc0, A[7 * k + I], d0, k + I != 0); });
        if (k == 3) wg_commit();
        sfor<7>([&](auto I) { wgmma_rs_n56<k * STG + I * 3584 + 896>(acc1, A[7 * k + I], d0, k + I != 0); });
        wg_commit();
      });
      wg_wait<1>();
      send(acc0, 1);
      sfor<4>([&](auto K) {
        constexpr int k = K, s = (k + 4) % 6;
        WAIT(BAR(B_FULL + s), k >= 2);
        STAMP(46 + k);
        wg_fence();
        sfor<7>([&](auto I) { wgmma_rs_n56<s * STG + I * 3584>(acc0, A[7 * k + I], d1, k + I != 0); });
        wg_commit();
        if (k == 0) {
          wg_wait<1>();
          send(acc1, 2);
          const float m0 = __uint_as_float(lds1(sb + OFF_M + warp * 64 + gq * 4)), m1 = __uint_as_float(lds1(sb + OFF_M + warp * 64 + gq * 4 + 32));
#pragma unroll
          for (int i = 0; i < 28; i++) acc1[i] = i & 2 ? -m1 : -m0;
          acc_fence(acc1);
        }
      });
      if (g) bar_arrive<7, 256>();
      wg_wait<0>();
      STAMP(22);
      send(acc0, 3);
      if (!g) bar_sync<7, 256>();
      uint32_t P[3][14];
      const char* const ps = buf + (A_PS + (cta * 6 + 3 * g) * 7168 + (warp & 3) * 1792) + (uint32_t)(lane * 16);
      auto fetch = [&](int x) {
#pragma unroll
        for (int i = 0; i < 3; i++) {
          const uint4 v = ld_rlx4(ps + 7168 * x + 512 * i);
          P[x][4 * i] = v.x; P[x][4 * i + 1] = v.y; P[x][4 * i + 2] = v.z; P[x][4 * i + 3] = v.w;
        }
        const uint2 v = ld_rlx2(ps + 7168 * x + 1536 - lane * 8);
        P[x][12] = v.x; P[x][13] = v.y;
      };
      const uint32_t pss = sb + (6 + g) * STG + (warp & 3) * 1792;
      auto fetchs = [&] {
        WAIT(wb + 24, 0);
#pragma unroll
        for (int x = 0; x < 2; x++) {
          const uint32_t a = pss + TILE + 7168 * x;
#pragma unroll
          for (int i = 0; i < 3; i++) {
            const uint4 v = lds4(a + 512 * i + lane * 16);
            P[x][4 * i] = v.x; P[x][4 * i + 1] = v.y; P[x][4 * i + 2] = v.z; P[x][4 * i + 3] = v.w;
          }
          const uint2 v = lds2(a + 1536 + lane * 8);
          P[x][12] = v.x; P[x][13] = v.y;
        }
      };
      WAIT(BAR(B_FULL + 5), 0);
      wg_fence();
      sfor<28>([&](auto I) {
        if (I == 21) {
          fetchs();
          fetch(2);
          wg_fence();
        }
        wgmma_rs_n56<(I / 7 + 4) % 6 * STG + I % 7 * 3584 + 896>(acc1, A[I], d1, 1);
      });
      wg_commit();
      STAMP(23);
      WAIT(BAR(B_FULL + 5), 0);
      auto check = [&](int x) {
#pragma unroll 1
        while (stale(xor2(P[x][0], P[x][4], par) | xor2(P[x][8], P[x][12], par), budget)) fetch(x);
      };
      uint32_t ob = pss + 7168 + (lane & 15) * 112 + (lane & 16);
      uint32_t eye = tq == gq >> 1 ? 0x3F80u << (16 * (gq & 1)) : 0;
      char* op = out + (uint32_t)((128 * r + (tid >> 5) * 16 + (lane >> 3)) * 896 + 112 * p + (lane & 7) * 16);
      uint32_t ia = pss + 7168 + (lane >> 3) * 112 + (lane & 7) * 16;
      asm volatile("" : "+r"(ob), "+r"(eye), "+l"(op), "+r"(ia));
      auto add = [&](const uint32_t (&v)[14]) {
#pragma unroll
        for (int j = 0; j < 7; j++)
          asm("mma.sync.aligned.m16n8k8.row.col.f32.bf16.bf16.f32 {%0,%1,%2,%3}, {%4,%5}, {%6}, {%0,%1,%2,%3};"
              : "+f"(acc1[4 * j]), "+f"(acc1[4 * j + 1]), "+f"(acc1[4 * j + 2]), "+f"(acc1[4 * j + 3]) : "r"(v[2 * j]), "r"(v[2 * j + 1]), "r"(eye));
      };
      check(0);
      check(1);
      wg_wait<0>();
      acc_fence(acc1);
      STAMP(24);
      add(R);
      add(P[0]);
      add(P[1]);
      acc_fence(acc1);
      WAIT(BAR(B_FULL + 5), 0);
      check(2);
      STAMP(57);
      add(P[2]);
      uint32_t o[14];
#pragma unroll
      for (int j = 0; j < 14; j++) o[j] = pack2(acc1[2 * j], acc1[2 * j + 1]);
#pragma unroll
      for (int i = 0; i < 3; i++)
        asm volatile("stmatrix.sync.aligned.m8n8.x4.shared.b16 [%0], {%1,%2,%3,%4};" ::"r"(ob + 32 * i), "r"(o[4 * i]), "r"(o[4 * i + 1]), "r"(o[4 * i + 2]), "r"(o[4 * i + 3]) : "memory");
      asm volatile("stmatrix.sync.aligned.m8n8.x2.shared.b16 [%0], {%1,%2};" ::"r"(ob + 96), "r"(o[12]), "r"(o[13]) : "memory");
      __syncwarp();
      {
        uint4 v[4];
#pragma unroll
        for (int i = 0; i < 4; i++) v[i] = lds4(ia + 448 * i);
        if ((lane & 7) < 7) {
#pragma unroll
          for (int i = 0; i < 4; i++) *(uint4*)(op + 3584 * i) = v[i];
        }
      }
      STAMP(25);
      SPINS(24 + g);
      GTIME(1);
    }
  } else {
    {
      const uint32_t c = 0x100000 - (tid < 256 + B_KVB ? 1 : tid < 256 + B_KFREE ? 4 : tid == 256 + B_XFREE ? 12 : 8);
      if (tid < 320) sts2(BAR(tid - 256), c << 1, c << 11);
      fence_async_smem();
      bar_arrive<0, 384>();
      bar_sync<2, 128>();
#pragma unroll
      for (int i = warp - 8; i < warp; i += 4) {
        if (elect()) {
          mbar_expect_tx(BAR(B_XB + i), TILE);
          tma3d(sb + OFF_X + i * TILE, &map_x, 0, 128 * r + 16 * i, 0, BAR(B_XB + i));
        }
      }
      prefetch_map(&map_qkv);
    }
    STAMPP(60);
    asm volatile("setmaxnreg.dec.sync.aligned.u32 56;");
    STAMPP(63);
    if (warp == 11) {
#pragma unroll 1
      for (int j = 0; j < 8; j++) {
        if (elect()) {
          mbar_expect_tx(BAR(B_K + j), TILE);
          tma2d(sb + (j ^ 4) * TILE, &map_qkv, wcol + DM + DM * (j >> 2), 112 * (j & 3), BAR(B_K + j));
        }
      }
    }
    STAMPP(59);
    const int w = warp - 8, t = tid - 256;
    STAMPP(61);
    char* const kvr = buf + (A_KVR + p * KVR_B);
    if (t < 44) st_rlx4(kvr + (uint32_t)((r * 44 + t) * 16), 0, r * 44 + t < 640 ? 0u : 0xC1800000u, 0, 0xC1800000u);
    const uint32_t e1 = ld_rlx1(&g_epoch[cta * 32]) + 1;
    const char* wrow = wo + (min(cta, 111) * 4 + w) * (DM * 2) + lane * 16;
    const uint4 u0 = ldg4(wrow);
    uint4 u1 = make_uint4(0, 0, 0, 0);
    if (lane < 24) u1 = ldg4(wrow + 512);
    if (lane < 7) asm volatile("prefetch.global.L2 [%0];" ::"l"(wq + (min(cta, 111) * 4 + w) * (DM * 6) + lane * 128));
    GTIME(0);
    const uint32_t par = e1 & 1;
    STAMPP(62);
    {
      float c[4];
      mma16816z(c, u0, 0x3F803F80u, 0x3F803F80u);
      mma16816(c, u1.x, u1.y, u1.z, u1.w, 0x3F803F80u, 0x3F803F80u);
      float s = c[0] + c[2];
      s += shx(s, 4); s += shx(s, 8); s += shx(s, 16);
      if (lane == 0) st_rlx1(buf + (A_WBAR + cta * 16 + w * 4), pack2(0.f, s * (-1.f / DM)) | par);
    }
    if (smem_u32(smem) != sb) __trap();
    if (MPF && w == 2) { prefetch_map(&map_wo); }
    STAMPP(19);
    uint4 xs[8];
#pragma unroll
    for (int i = 0; i < 8; i++) {
      const int G = 7 * p - kh + (lane & 7), row = (lane >> 3) + 4 * (i & 3);
      if (i % 4 == 0) WAIT(BAR(B_XB + w + i), 0);
      xs[i] = lds4(sb + OFF_X + (w + (i & 4)) * TILE + (G >> 3) * 2048 + row * 128 + (((G ^ row) & 7) << 4));
    }
    __syncwarp();
    if (lane == 0) mbar_arrive(BAR(B_XFREE));
    WAIT(BAR(B_XFREE), 0);
    auto load_wo = [&] {
      mbar_expect_tx(BAR(B_WO), 2 * STG);
      tma2d(sb + OFF_WO, &map_wo, wcol, 0, BAR(B_WO));
      tma2d(sb + OFF_WO + STG, &map_wo, wcol, 224, BAR(B_WO));
    };
    if (WOPOS == 0 && w == 0 && elect()) load_wo();
#pragma unroll
    for (int i = 0; i < 4; i++) sts4(sb + OFF_KVB + 2048 * i + t * 16, 0, 0, 0, 0);
#pragma unroll
    for (int i = 0; i < 8; i++) {
      const int row = (lane >> 3) + 4 * (i & 3);
      sts4(sb + OFF_XS + (w + (i & 4)) * 2048 + row * 128 + (((lane ^ row) & 7) << 4), xs[i].x, xs[i].y, xs[i].z, xs[i].w);
    }
    const char* const kvt = kvr + (uint32_t)(t * 16);
    const char* const kvt8 = kvr + 10240 + (uint32_t)(t * 8);
    {
      uint32_t c[6];
      auto counts = [&] {
#pragma unroll
        for (int i = 0; i < 5; i++) c[i] = ld_rlx1(kvt + 2048 * i + 12);
        c[5] = ld_rlx1(kvt8 + 4);
      };
      counts();
      if (w == 0) {
        WAIT(BAR(B_KFREE), 0);
        if (elect()) {
          mbar_expect_tx(BAR(B_Q), 2 * STG);
#pragma unroll 1
          for (int j = 0; j < 4; j++) tma2d(sb + OFF_Q + j * TILE, &map_qkv, wcol, 112 * j, BAR(B_Q));
          if (WOPOS == 2) load_wo();
        }
      }
#pragma unroll 1
      while (stale(~(c[0] & c[1] & c[2] & c[3] & c[4] & c[5]), budget, 0x80000000u)) counts();
    }
    if (lane == 0) mbar_arrive(BAR(B_INIT));
    STAMPP(1);
    if (w == 1 && elect()) {
      prefetch_map(&map_gu);
      l2_prefetch(wg + cta * 12544, 12544);
      l2_prefetch(wu + cta * 12544, 12544);
      l2_prefetch(wd + cta * 12544, 12544);
      prefetch_map(&map_gu32);
    }
    uint4 m = ld_rlx4(buf + A_WBAR + (uint32_t)(t * 16));
    WAIT(BAR(B_VFREE), 0);
    auto load_w = [&](int u0) {
#pragma unroll 1
      for (int u = u0; u < u0 + 2; u++) {
        if (elect()) {
          mbar_expect_tx(BAR(B_FULL + u), STG);
          tma3d(sb + u * STG, &map_gu, 224 * p + 32 * kh, 112 * u, 0, BAR(B_FULL + u));
        }
      }
    };
    if (WOPOS == 1 && w == 0 && elect()) load_wo();
    if (w == 0) load_w(0);
    {
#pragma unroll 1
      while (stale(xor2(m.x, m.y, par) | xor2(m.z, m.w, par), budget)) m = ld_rlx4(buf + A_WBAR + (uint32_t)(t * 16));
      const uint32_t wa = sb + OFF_WBAR + (t >> 3) * 64 + (t & 1) * 32 + (t & 6) * 2;
      if (t < 112) {
        sts1(wa, __byte_perm(m.x, m.y, 0x7632));
        sts1(wa + 16, __byte_perm(m.z, m.w, 0x7632));
      }
      STAMPP(6);
    }
    bar_sync<2, 128>();
    const int gq = lane >> 2, tq = lane & 3, k = 28 * (w >> 1) + 16 * (w & 1) + gq;
    const uint32_t row = sb + OFF_KVB + k * 128, sw = (k & 7) << 4;
    uint32_t ad[4];
#pragma unroll
    for (int q = 0; q < 4; q++) {
      const int c = 28 * (w >> 1) + 2 * tq + 8 * q;
      ad[q] = row + (2 * (c < 32 ? (c & 6) * 4 + (c >> 3) * 2 : c < 48 ? 32 + (c & 2) * 4 + (c >> 1 & 6) : c) ^ sw);
      asm volatile("" : "+r"(ad[q]));
    }
    eq_wait(kvr + 2 * 2048 + w * 512 + 12, 0, budget);
    STAMPX(2);
    {
      uint4 v[5];
      uint2 v5;
#pragma unroll 1
      do {
#pragma unroll
        for (int i = 0; i < 5; i++) v[i] = ld_rlx4(kvt + 2048 * i);
        v5 = ld_rlx2(kvt8);
      } while (stale(or3(v[0].w, v[1].w, v[2].w) | or3(v[3].w, v[4].w, v5.y), budget, ~0u));
      STAMPX(3);
      const bool lo = !(w & 1) || gq < 4;
#define F(x) __uint_as_float(x)
      const uint32_t a[4] = {pack2(F(v[0].x), F(v[0].y)), pack2(F(v[0].z), F(v[1].x)), pack2(F(v[1].y), F(v[1].z)), pack2(F(v[4].x), F(v[4].y))};
      const uint32_t b[4] = {pack2(F(v[2].x), F(v[2].y)), pack2(F(v[2].z), F(v[3].x)), pack2(F(v[3].y), F(v[3].z)), pack2(F(v[4].z), F(v5.x))};
#pragma unroll
      for (int q = 0; q < 4; q++) {
        if (q < 3 || tq < 2) {
          sts1(ad[q], a[q]);
          if (lo) sts1(ad[q] + 1024, b[q]);
        }
      }
      if (tq == 2) {
        const uint32_t z = pack2(F(v[4].x) + F(v[4].y), F(v[4].z) + F(v5.x));
        const uint32_t za = __byte_perm(z, 0, w & 2 ? 0x1044 : 0x4410), zb = __byte_perm(z, 0, w & 2 ? 0x3244 : 0x4432);
        sts4(row + (112 ^ sw), za, za, za, za);
        if (lo) sts4(row + 1024 + (112 ^ sw), zb, zb, zb, zb);
      }
      fence_async_smem();
      __syncwarp();
      if (lane == 0) mbar_arrive(BAR(B_KVB));
      STAMPP(4);
      if (w == 0) { WAIT(BAR(B_QFREE), 0); load_w(2); }
    }
    if (w == 0) {
#pragma unroll 1
      for (int u = 4; u < 22; u++) {
        const int s = u < 14 ? u & 7 : u < 20 ? u - 14 : u - 20;
        if (u == 14) WAIT(BAR(B_WDOK), 0);
        WAIT(BAR(B_KFREE + s) + (u >= 8 ? 64 : 0), u >= 14 && u < 20);
        STAMPP(20 + u);
        if (elect()) {
          mbar_expect_tx(BAR(B_FULL + s), u < 14 ? STG : WDS);
          if (u < 12) tma3d(sb + s * STG, &map_gu, 224 * p + 32 * kh + 64 * (u >> 2), 112 * (u & 3), 0, BAR(B_FULL + s));
          else if (u < 14) tma3d(sb + s * STG, &map_gu32, 224 * p + 192 - 192 * kh, 224 * (u - 12), 0, BAR(B_FULL + s));
          else bulk_g2s(sb + s * STG, buf + (A_WD + (p * 8 + u - 14) * WDS), WDS, BAR(B_FULL + s));
        }
      }
      SPINS(26);
    } else {
#pragma unroll 1
      for (int j = 0; j < (w == 1 ? 4 : 0); j++) {
        const char* src = buf + (A_O + (j >> 1) * FRAG_B + (r * 2 + (j & 1)) * 2 * STG);
        const uint32_t full = BAR(B_WB + 4 * (j & 1));
        if (j != 1) cnt_wait(&g_cnt[C_ROW + r * 32 + j], e1 * (j ? 32 : 64), budget);
        if (j == 0) WAIT(BAR(B_OFREE), 0);
        if (j == 2) bar_arrive<6, 160>();
        STAMPX(50 + 2 * j);
#pragma unroll
        for (int q = 0; q < 4; q++) {
          if (j) WAIT(BAR(B_ORD + q), ~j & 1);
          if (elect()) {
            mbar_expect_tx(full + 8 * q, TILE);
            bulk_g2s(sb + OFF_G + q * TILE, src + q * TILE, TILE, full + 8 * q);
          }
          if (RPK >= 4 && q == RPK % 4 && j == RPK / 4 && lane < 8) mbar_arrive(BAR(B_RPK));
        }
        if (j == 0) {
          WAIT(BAR(B_WOFREE), 0);
          if (lane < 16) mbar_arrive(BAR(B_HFREE + (lane >> 3)));
        }
        STAMPP(51 + 2 * j);
      }
      if (w == 1) { SPINS(27); return; }
      const int g = w - 2;
      WAIT(BAR(RPK < 4 ? B_HFREE + RPK : B_RPK), 0);
      if (t < 120) {
        const int src = p ^ (r >> 2 & 1), part = (r & 1) + (~(r ^ r >> 1) & 2);
        char* zp = buf + (uint32_t)(A_WD + (p * 16 + r) * (WDS / 2) + t * 16 - 1024);
#pragma unroll 1
        for (int x = 1 + (r >> 2 & 2);; x++, zp += 896) {
          const char* wp = wd + (uint32_t)((224 * src + 32 * (src & 1) + 56 * part + (t & 7)) * 896 + (p ^ 2 * x & 7) * 112 + (t & 56) * 2);
          uint4 z[7];
#pragma unroll
          for (int i = 0; i < 7; i++) {
            if (i == 3 && part + (src & 1) == 4) wp -= 224 * 896;
            z[i] = ldg4(wp + i * 8 * 896);
          }
#pragma unroll
          for (int i = 0; i < 7; i++) st_rlx4(zp + i * 1792, z[i].x, z[i].y, z[i].z, z[i].w);
          if (!(x & 1)) break;
        }
      }
      STAMPP(5);
      asm volatile("fence.proxy.async.global;" ::: "memory");
      __syncwarp();
      if (lane == 0) asm volatile("red.release.gpu.global.add.u32 [%0], 1;" ::"l"(&g_cnt[C_WD + p * 32]) : "memory");
      STAMPP(7);
      cnt_wait<true>(&g_cnt[C_WD + p * 32], e1 * 32, budget);
      STAMPP(18);
      asm volatile("fence.proxy.async.global;" ::: "memory");
      if (lane < 2) mbar_arrive(BAR(B_WDOK));
#pragma unroll 1
      for (int j = 0; j < 4; j += j + 1) {
        const uint32_t bar = BAR(B_WB + 4 * g + j);
        const char* src = buf + (j < 3 ? A_HH + (cta ^ j) * 2 * STG + g * TILE : A_PS + (cta * 6 + 3 * g) * 7168);
        if (j != 1) cnt_wait(&g_cnt[(j < 3 ? C_ROW + r * 32 + 4 + 2 * (p & 6) : C_PS + cta * 8) + g], e1 * 8, budget);
        WAIT(j >= 2 ? BAR(B_HFREE + 2 * g + 1) : BAR(B_EMPTY + 6 + g), j >> 1);
        if (elect()) {
          mbar_expect_tx(bar, TILE);
          bulk_g2s(sb + (6 + g) * STG + (j & 1) * TILE, src, TILE, bar);
        }
      }
      SPINS(28 + g);
      if (g) st_rlx1(&g_epoch[cta * 32], e1);
      if (g && lane == 0) DUMP(2);
    }
  }
}

typedef CUresult (*EncodeFn)(CUtensorMap*, CUtensorMapDataType, cuuint32_t, void*, const cuuint64_t*, const cuuint64_t*,
                             const cuuint32_t*, const cuuint32_t*, CUtensorMapInterleave, CUtensorMapSwizzle,
                             CUtensorMapL2promotion, CUtensorMapFloatOOBfill);

void make_map(EncodeFn enc, CUtensorMap* m, const void* p, int rank, const cuuint64_t* gd, const cuuint64_t* gs,
              const cuuint32_t* bd, CUtensorMapSwizzle sw) {
  const cuuint32_t es[5] = {1, 1, 1, 1, 1};
  ENC_CHECK(enc(m, CU_TENSOR_MAP_DATA_TYPE_BFLOAT16, rank, (void*)p, gd, gs, bd, es, CU_TENSOR_MAP_INTERLEAVE_NONE, sw,
                CU_TENSOR_MAP_L2_PROMOTION_NONE, CU_TENSOR_MAP_FLOAT_OOB_FILL_NONE));
}

}

extern "C" void kernel_launch(void* const* d_in, const int* in_sizes, int n_in, void* d_out, int out_size) {
  (void)in_sizes; (void)n_in; (void)out_size;
  static EncodeFn enc = nullptr;
  static char* buf = nullptr;
  if (!enc) {
    void* fn = nullptr;
    cudaDriverEntryPointQueryResult qr;
    cudaGetDriverEntryPoint("cuTensorMapEncodeTiled", &fn, cudaEnableDefault, &qr);
    enc = (EncodeFn)fn;
    cudaGetSymbolAddress((void**)&buf, g_buf);
    cudaFuncSetAttribute(fused_block_kernel<false>, cudaFuncAttributeMaxDynamicSharedMemorySize, SMEM_TOTAL);
    cudaFuncSetAttribute(fused_block_kernel<true>, cudaFuncAttributeMaxDynamicSharedMemorySize, SMEM_TOTAL);
  }
  const CUtensorMapSwizzle S128 = CU_TENSOR_MAP_SWIZZLE_128B;
  CUtensorMap mx, mqkv, mwor, mgu, mgu32;
  {
    cuuint64_t gd[3] = {64, SEQ, 7}, gs[2] = {DM * 2, 128};
    cuuint32_t bd[3] = {64, 16, 7};
    make_map(enc, &mx, d_in[0], 3, gd, gs, bd, S128);
  }
  {
    cuuint64_t gd[2] = {3 * DM, DM}, gs[1] = {3 * DM * 2};
    cuuint32_t bd[2] = {64, 112};
    make_map(enc, &mqkv, d_in[1], 2, gd, gs, bd, S128);
  }
  {
    cuuint64_t gd[2] = {DM, DM}, gs[1] = {DM * 2};
    cuuint32_t bd[2] = {64, 224};
    make_map(enc, &mwor, d_in[2], 2, gd, gs, bd, S128);
  }
  const char *wg = (const char*)d_in[4], *wu = (const char*)d_in[5];
  const bool swap = wu < wg;
  const char* gub = swap ? wu : wg;
  const cuuint64_t gud = swap ? (cuuint64_t)(wg - wu) : (cuuint64_t)(wu - wg);
  {
    cuuint64_t gd[3] = {FF, DM, 2}, gs[2] = {FF * 2, gud};
    cuuint32_t bd[3] = {64, 112, 2};
    make_map(enc, &mgu, gub, 3, gd, gs, bd, S128);
  }
  {
    cuuint64_t gd[3] = {FF, DM, 2}, gs[2] = {FF * 2, gud};
    cuuint32_t bd[3] = {32, 224, 2};
    make_map(enc, &mgu32, gub, 3, gd, gs, bd, CU_TENSOR_MAP_SWIZZLE_64B);
  }
  (swap ? fused_block_kernel<true> : fused_block_kernel<false>)<<<128, 384, SMEM_TOTAL>>>(
      buf, (const char*)d_in[2], mn_desc(sb), mn_desc64(sb), mn_desc0(sb), mn_desc(sb + OFF_Q), mn_desc0(sb), k_desc0(sb), wg, wu, (const char*)d_in[6], (const char*)d_in[1], (char*)d_out, mx, mqkv, mwor, mgu, mgu32);
}
```

```cpp
#include <cuda_runtime.h>
#include <cuda_bf16.h>
#include <cuda.h>
#include <stdint.h>
#include <stdio.h>
#include <utility>

#define SPIN_LIMIT (1 << 18)

namespace {

constexpr uint32_t sb = 1024;
constexpr int SEQ = 2048, DM = 448, FF = 1792;
constexpr int TILE = 14336;
constexpr int STG = 2 * TILE;
constexpr int SMEM_BAR = 8 * STG;
constexpr int SMEM_TOTAL = SMEM_BAR + 3072;
constexpr int OFF_X = 4 * STG, OFF_Q = 4 * STG, OFF_WO = 2 * STG, OFF_G = 4 * STG, OFF_PK = 6 * STG, OFF_KVB = OFF_PK + 32768, OFF_XS = OFF_KVB + 8192,
              OFF_M = SMEM_BAR + 512, OFF_WBAR = SMEM_BAR + 2048, OFF_POLL = SMEM_BAR + 2944;
constexpr int B_XB = 0  , B_K = 8  , B_V = 12  , B_Q = 16, B_WO = 17, B_FULL = 18  , B_WB = 26  ,
              B_KVB = 34, B_WDOK = 35, B_INIT = 36,
              B_KFREE = 37, B_OFREE = 38, B_QFREE = 39  , B_HFREE = 41  , B_EMPTY = 45  , B_XFREE = 53, B_VFREE = 54,
              B_ORD = 55  , B_WOFREE = 59, B_RPK = 60;

constexpr int KVR_B = 8704;
constexpr int FRAG_B = 16 * 4 * STG;
constexpr int A_CNT = 0, A_EPOCH = 8192, A_KVR = A_EPOCH + 16384, A_WBAR = A_KVR + 8 * KVR_B, A_O = A_WBAR + 2048, A_H = A_O + FRAG_B,
              A_HH = A_H + FRAG_B;
constexpr int HH_B = 128 * 2 * STG;
constexpr int A_PS = A_HH + HH_B;
constexpr int WDS = 25088;
constexpr int A_WD = A_PS + 128 * 3 * TILE;

__device__ uint4 g_buf[(A_WD + 64 * WDS) / 16];
#define g_epoch ((unsigned*)buf + A_EPOCH / 4)
constexpr int C_ROW = 0, C_WD = 512, C_PS = 1024;
#define g_cnt ((unsigned*)buf + A_CNT / 4)
#define ENC_CHECK(x) (void)(x)
#define STAMP(i)
#define STAMPX(i)
#define GTIME(i)
#define STAMPP(i)
#define STAMPD(i)
#define DUMP(row)

__device__ __forceinline__ uint32_t smem_u32(const void* p) { return (uint32_t)__cvta_generic_to_shared(p); }
__device__ __forceinline__ void mbar_init(uint32_t bar, uint32_t cnt) {
  asm volatile("mbarrier.init.shared::cta.b64 [%0], %1;" ::"r"(bar), "r"(cnt) : "memory");
}
__device__ __forceinline__ void mbar_expect_tx(uint32_t bar, uint32_t bytes) {
  asm volatile("mbarrier.arrive.expect_tx.shared::cta.b64 _, [%0], %1;" ::"r"(bar), "r"(bytes) : "memory");
}
__device__ __forceinline__ void mbar_arrive(uint32_t bar) {
  asm volatile("mbarrier.arrive.shared::cta.b64 _, [%0];" ::"r"(bar) : "memory");
}
__device__ __forceinline__ void mbar_wait(uint32_t bar, uint32_t parity, int& budget) {
  asm volatile("{\n.reg .pred p;\nW:\nmbarrier.try_wait.parity.shared::cta.b64 p, [%1], %2;\n"
               "add.s32 %0, %0, -1;\nsetp.gt.and.s32 p, %0, 0, !p;\n@p bra W;\n}"
               : "+r"(budget) : "r"(bar), "r"(parity) : "memory");
}
__device__ __forceinline__ bool elect() {
  uint32_t v;
  asm volatile("{\n.reg .pred p;\nelect.sync _|p, 0xffffffff;\nselp.u32 %0, 1, 0, p;\n}" : "=r"(v));
  return v;
}
__device__ __forceinline__ void tma2d(uint32_t dst, const CUtensorMap* m, int c0, int c1, uint32_t bar) {
  asm volatile("cp.async.bulk.tensor.2d.shared::cluster.global.mbarrier::complete_tx::bytes [%0], [%1, {%3, %4}], [%2];"
               ::"r"(dst), "l"(m), "r"(bar), "r"(c0), "r"(c1) : "memory");
}
__device__ __forceinline__ void tma3d(uint32_t dst, const CUtensorMap* m, int c0, int c1, int c2, uint32_t bar) {
  asm volatile("cp.async.bulk.tensor.3d.shared::cluster.global.mbarrier::complete_tx::bytes [%0], [%1, {%3, %4, %5}], [%2];"
               ::"r"(dst), "l"(m), "r"(bar), "r"(c0), "r"(c1), "r"(c2) : "memory");
}
__device__ __forceinline__ void bulk_g2s(uint32_t dst, const void* src, uint32_t bytes, uint32_t bar) {
  asm volatile("cp.async.bulk.shared::cluster.global.mbarrier::complete_tx::bytes [%0], [%1], %2, [%3];"
               ::"r"(dst), "l"(src), "r"(bytes), "r"(bar) : "memory");
}
__device__ __forceinline__ void l2_prefetch(const void* p, uint32_t bytes) {
  asm volatile("cp.async.bulk.prefetch.L2.global [%0], %1;" ::"l"(p), "r"(bytes) : "memory");
}
__device__ __forceinline__ void prefetch_map(const CUtensorMap* m) {
  asm volatile("prefetch.tensormap [%0];" ::"l"(m) : "memory");
}
__device__ __forceinline__ void fence_async_smem() { asm volatile("fence.proxy.async.shared::cta;" ::: "memory"); }
template <int ID, int N> __device__ __forceinline__ void bar_arrive() { asm volatile("bar.arrive %0, %1;" ::"n"(ID), "n"(N) : "memory"); }
__device__ __forceinline__ void bar_arrive_id(int id) { asm volatile("bar.arrive %0, 256;" ::"r"(id) : "memory"); }
__device__ __forceinline__ void bar_sync_wg(int id) { asm volatile("bar.sync %0, 128;" ::"r"(id) : "memory"); }
template <int ID, int N> __device__ __forceinline__ void bar_sync() { asm volatile("bar.sync %0, %1;" ::"n"(ID), "n"(N) : "memory"); }
__device__ __forceinline__ void wg_fence() { asm volatile("wgmma.fence.sync.aligned;" ::: "memory"); }
__device__ __forceinline__ void wg_commit() { asm volatile("wgmma.commit_group.sync.aligned;" ::: "memory"); }
template <int N> __device__ __forceinline__ void wg_wait() { asm volatile("wgmma.wait_group.sync.aligned %0;" ::"n"(N) : "memory"); }
template <int N> __device__ __forceinline__ void acc_fence(float (&d)[N]) {
#pragma unroll
  for (int i = 0; i < N; i++) asm volatile("" : "+f"(d[i])::"memory");
}
constexpr uint64_t mn_desc(uint32_t addr) {
  return (uint64_t)((addr & 0x3FFFF) >> 4) | ((uint64_t)(TILE >> 4) << 16) | ((uint64_t)64 << 32) | ((uint64_t)1 << 62);
}
constexpr uint64_t mn_desc64(uint32_t addr) {
  return (uint64_t)((addr & 0x3FFFF) >> 4) | ((uint64_t)(TILE >> 4) << 16) | ((uint64_t)32 << 32) | ((uint64_t)2 << 62);
}
constexpr uint64_t mn_desc0(uint32_t addr) {
  return (uint64_t)((addr & 0x3FFFF) >> 4) | ((uint64_t)(1792 >> 4) << 16) | ((uint64_t)8 << 32);
}
constexpr uint64_t k_desc0(uint32_t addr) {
  return (uint64_t)((addr & 0x3FFFF) >> 4) | ((uint64_t)8 << 16) | ((uint64_t)(1792 >> 4) << 32);
}
__device__ __forceinline__ uint4 ld_rlx4(const void* p) {
  uint4 v;
  asm volatile("ld.relaxed.gpu.global.v4.u32 {%0,%1,%2,%3}, [%4];" : "=r"(v.x), "=r"(v.y), "=r"(v.z), "=r"(v.w) : "l"(p) : "memory");
  return v;
}
__device__ __forceinline__ uint2 ld_rlx2(const void* p) {
  uint2 v;
  asm volatile("ld.relaxed.gpu.global.v2.u32 {%0,%1}, [%2];" : "=r"(v.x), "=r"(v.y) : "l"(p) : "memory");
  return v;
}
__device__ __forceinline__ uint32_t ld_rlx1(const void* p) {
  uint32_t v;
  asm volatile("ld.relaxed.gpu.global.u32 %0, [%1];" : "=r"(v) : "l"(p) : "memory");
  return v;
}
__device__ __forceinline__ void st_rlx4(void* p, uint32_t a, uint32_t b, uint32_t c, uint32_t d) {
  asm volatile("st.relaxed.gpu.global.v4.u32 [%0], {%1,%2,%3,%4};" ::"l"(p), "r"(a), "r"(b), "r"(c), "r"(d) : "memory");
}
__device__ __forceinline__ void st_rlx2(void* p, uint32_t a, uint32_t b) {
  asm volatile("st.relaxed.gpu.global.v2.u32 [%0], {%1,%2};" ::"l"(p), "r"(a), "r"(b) : "memory");
}
__device__ __forceinline__ void st_rlx1(void* p, uint32_t a) {
  asm volatile("st.relaxed.gpu.global.u32 [%0], %1;" ::"l"(p), "r"(a) : "memory");
}
__device__ __forceinline__ void red_inc(unsigned* p) {
  asm volatile("red.relaxed.gpu.global.inc.u32 [%0], 0xfffffffe;" ::"l"(p) : "memory");
}
__device__ __forceinline__ void red_add4(void* p, float a, float b, float c, float d) {
  asm volatile("red.relaxed.gpu.global.add.v4.f32 [%0], {%1,%2,%3,%4};" ::"l"(p), "f"(a), "f"(b), "f"(c), "f"(d) : "memory");
}
__device__ __forceinline__ void eq_wait(const void* p, uint32_t target, int& budget) {
  asm volatile("{\n.reg .pred p;\n.reg .b32 v;\nW:\nld.relaxed.gpu.global.b32 v, [%1];\nadd.s32 %0, %0, -1;\n"
               "setp.gt.s32 p, %0, 0;\nsetp.gt.and.u32 p, v, %2, p;\n@p bra W;\n}"
               : "+r"(budget) : "l"(p), "r"(target) : "memory");
}
template <bool ACQ = false>
__device__ __forceinline__ void cnt_wait(const unsigned* p, uint32_t target, int& budget) {
  if (ACQ)
    asm volatile("{\n.reg .pred p;\n.reg .s32 v;\nW:\nld.acquire.gpu.global.s32 v, [%1];\nadd.s32 %0, %0, -1;\n"
                 "setp.gt.s32 p, %0, 0;\nsub.s32 v, v, %2;\nsetp.lt.and.s32 p, v, 0, p;\n@p bra W;\n}"
                 : "+r"(budget) : "l"(p), "r"(target) : "memory");
  else
  asm volatile("{\n.reg .pred p;\n.reg .s32 v;\nW:\nld.relaxed.gpu.global.s32 v, [%1];\nadd.s32 %0, %0, -1;\n"
               "setp.gt.s32 p, %0, 0;\nsub.s32 v, v, %2;\nsetp.lt.and.s32 p, v, 0, p;\n@p bra W;\n}"
               : "+r"(budget) : "l"(p), "r"(target) : "memory");
}
#define PGAP 1
template <bool EQ = false>
__device__ __forceinline__ void cnt_poll(const void* p, uint32_t s, uint32_t a, uint32_t target, int& budget) {
  asm volatile("{\n.reg .pred p, e;\n.reg .s32 v;\nelect.sync _|e, 0xffffffff;\nW:\n@e cp.async.cg.shared.global [%2], [%1], 16;\n"
               "add.s32 %0, %0, -1;\nsetp.gt.s32 p, %0, 0;\n"
               "ld.volatile.shared.s32 v, [%3];\nsub.s32 v, v, %4;\nsetp.lt.and.s32 p, v, 0, p;\n"
               "@p bra W;\nE:\n}"
               : "+r"(budget) : "l"(p), "r"(s), "r"(a), "r"(target) : "memory");
}
__device__ __forceinline__ uint32_t or3(uint32_t a, uint32_t b, uint32_t c) {
  uint32_t r;
  asm("lop3.b32 %0, %1, %2, %3, 0xfe;" : "=r"(r) : "r"(a), "r"(b), "r"(c));
  return r;
}
__device__ __forceinline__ uint32_t xor2(uint32_t a, uint32_t b, uint32_t f) {
  uint32_t r;
  asm("lop3.b32 %0, %1, %2, %3, 0x7e;" : "=r"(r) : "r"(a), "r"(b), "r"(f));
  return r;
}
__device__ __forceinline__ bool stale(uint32_t bad, int& budget, uint32_t mask = 1) {
  uint32_t v;
  asm volatile("{\n.reg .pred p;\n.reg .b32 t;\nand.b32 t, %2, %3;\nsetp.ne.u32 p, t, 0;\nadd.s32 %1, %1, -1;\n"
               "setp.gt.and.s32 p, %1, 0, p;\nvote.sync.any.pred p, p, 0xffffffff;\nselp.u32 %0, 1, 0, p;\n}"
               : "=r"(v), "+r"(budget) : "r"(bad), "r"(mask));
  return v;
}
__device__ __forceinline__ uint32_t tag(uint32_t w, uint32_t par) {
  uint32_t r;
  asm("lop3.b32 %0, %1, %2, 1, 0xd8;" : "=r"(r) : "r"(w), "r"(par));
  return r;
}
__device__ __forceinline__ void sts1(uint32_t a, uint32_t v) { asm volatile("st.shared.u32 [%0], %1;" ::"r"(a), "r"(v) : "memory"); }
__device__ __forceinline__ void sts2(uint32_t a, uint32_t x, uint32_t y) {
  asm volatile("st.shared.v2.u32 [%0], {%1,%2};" ::"r"(a), "r"(x), "r"(y) : "memory");
}
__device__ __forceinline__ void sts4(uint32_t a, uint32_t x, uint32_t y, uint32_t z, uint32_t w) {
  asm volatile("st.shared.v4.u32 [%0], {%1,%2,%3,%4};" ::"r"(a), "r"(x), "r"(y), "r"(z), "r"(w) : "memory");
}
__device__ __forceinline__ uint32_t lds1(uint32_t a) {
  uint32_t v;
  asm volatile("ld.shared.u32 %0, [%1];" : "=r"(v) : "r"(a) : "memory");
  return v;
}
__device__ __forceinline__ uint2 lds2(uint32_t a) {
  uint2 v;
  asm volatile("ld.shared.v2.u32 {%0,%1}, [%2];" : "=r"(v.x), "=r"(v.y) : "r"(a) : "memory");
  return v;
}
__device__ __forceinline__ uint4 lds4(uint32_t a) {
  uint4 v;
  asm volatile("ld.shared.v4.u32 {%0,%1,%2,%3}, [%4];" : "=r"(v.x), "=r"(v.y), "=r"(v.z), "=r"(v.w) : "r"(a) : "memory");
  return v;
}
__device__ __forceinline__ uint4 ldsm4(uint32_t a) {
  uint4 v;
  asm volatile("ldmatrix.sync.aligned.m8n8.x4.shared.b16 {%0,%1,%2,%3}, [%4];" : "=r"(v.x), "=r"(v.y), "=r"(v.z), "=r"(v.w) : "r"(a) : "memory");
  return v;
}
__device__ __forceinline__ uint4 ldsm4t(uint32_t a) {
  uint4 v;
  asm volatile("ldmatrix.sync.aligned.m8n8.x4.trans.shared.b16 {%0,%1,%2,%3}, [%4];" : "=r"(v.x), "=r"(v.y), "=r"(v.z), "=r"(v.w) : "r"(a) : "memory");
  return v;
}
__device__ __forceinline__ uint32_t pack2(float lo, float hi) {
  uint32_t r;
  asm("cvt.rn.bf16x2.f32 %0, %1, %2;" : "=r"(r) : "f"(hi), "f"(lo));
  return r;
}
__device__ __forceinline__ float bf_lo(uint32_t w) { return __uint_as_float(w << 16); }
__device__ __forceinline__ float bf_hi(uint32_t w) { return __uint_as_float(w & 0xFFFF0000u); }
__device__ __forceinline__ uint32_t sub2(uint32_t a, uint32_t b) {
  uint32_t r;
  asm volatile("sub.rn.bf16x2 %0, %1, %2;" : "=r"(r) : "r"(a), "r"(b));
  return r;
}
__device__ __forceinline__ uint32_t add2(uint32_t a, uint32_t b) {
  uint32_t r;
  asm("add.rn.bf16x2 %0, %1, %2;" : "=r"(r) : "r"(a), "r"(b));
  return r;
}
__device__ __forceinline__ uint32_t fma2(uint32_t a, uint32_t b, uint32_t c) {
  uint32_t r;
  asm("fma.rn.bf16x2 %0, %1, %2, %3;" : "=r"(r) : "r"(a), "r"(b), "r"(c));
  return r;
}
__device__ __forceinline__ uint32_t transp(uint32_t a) {
  uint32_t r;
  asm volatile("movmatrix.sync.aligned.m8n8.trans.b16 %0, %1;" : "=r"(r) : "r"(a));
  return r;
}
__device__ __forceinline__ uint32_t sq2(uint32_t a) {
  uint32_t r;
  asm volatile("mul.rn.bf16x2 %0, %1, %1;" : "=r"(r) : "r"(a));
  return r;
}
__device__ __forceinline__ uint32_t sq2(uint32_t a, uint32_t c) {
  uint32_t r;
  asm volatile("fma.rn.bf16x2 %0, %1, %1, %2;" : "=r"(r) : "r"(a), "r"(c));
  return r;
}
__device__ __forceinline__ uint4 ldg4(const void* p) {
  uint4 v;
  asm volatile("ld.global.nc.v4.u32 {%0,%1,%2,%3}, [%4];" : "=r"(v.x), "=r"(v.y), "=r"(v.z), "=r"(v.w) : "l"(p));
  return v;
}
__device__ __forceinline__ void mma16816(float (&c)[4], uint32_t a0, uint32_t a1, uint32_t a2, uint32_t a3, uint32_t b0, uint32_t b1) {
  asm("mma.sync.aligned.m16n8k16.row.col.f32.bf16.bf16.f32 {%0,%1,%2,%3}, {%4,%5,%6,%7}, {%8,%9}, {%0,%1,%2,%3};"
      : "+f"(c[0]), "+f"(c[1]), "+f"(c[2]), "+f"(c[3]) : "r"(a0), "r"(a1), "r"(a2), "r"(a3), "r"(b0), "r"(b1));
}
__device__ __forceinline__ void mma16816z(float (&c)[4], const uint4& a, uint32_t b0, uint32_t b1) {
  asm("mma.sync.aligned.m16n8k16.row.col.f32.bf16.bf16.f32 {%0,%1,%2,%3}, {%4,%5,%6,%7}, {%8,%9}, {%10,%10,%10,%10};"
      : "=f"(c[0]), "=f"(c[1]), "=f"(c[2]), "=f"(c[3]) : "r"(a.x), "r"(a.y), "r"(a.z), "r"(a.w), "r"(b0), "r"(b1), "f"(0.f));
}
__device__ __forceinline__ float ex2f(float x) { float r; asm("ex2.approx.ftz.f32 %0, %1;" : "=f"(r) : "f"(x)); return r; }
__device__ __forceinline__ float tanhf_(float x) { float r; asm("tanh.approx.f32 %0, %1;" : "=f"(r) : "f"(x)); return r; }
__device__ __forceinline__ float rsqf(float x) { float r; asm("rsqrt.approx.ftz.f32 %0, %1;" : "=f"(r) : "f"(x)); return r; }
__device__ __forceinline__ float lg2f(float x) { float r; asm("lg2.approx.ftz.f32 %0, %1;" : "=f"(r) : "f"(x)); return r; }
__device__ __forceinline__ float rcpf(float x) { float r; asm("rcp.approx.ftz.f32 %0, %1;" : "=f"(r) : "f"(x)); return r; }
__device__ __forceinline__ float phi(float a, const float4& c) {
  return ex2f(fmaf(fminf(a, 0.f), c.x, c.y)) + fmaf(fmaxf(a, 0.f), c.z, c.w);
}
__host__ __device__ constexpr long long koff(int i, int u) { return i < 3 ? 2 * i * u : i == 3 ? 6 * u + ((6ll * u) << 32) : (2 * i - 1) * u; }
__device__ __forceinline__ float shx(float v, int m) { return __shfl_xor_sync(0xffffffffu, v, m); }
template <int V> struct IC { __host__ __device__ constexpr operator int() const { return V; } };
template <class F, int... I> __device__ __forceinline__ void sfor_impl(F&& f, std::integer_sequence<int, I...>) {
  (f(IC<I>{}), ...);
}
template <int N, class F> __device__ __forceinline__ void sfor(F&& f) { sfor_impl(f, std::make_integer_sequence<int, N>{}); }

template <long long OFF, int RO = 0, int N>
__device__ __forceinline__ void wgmma_rs_n56(float (&d)[N], const uint4& a, uint64_t base, int scale_d) {
  asm volatile("{\n.reg .pred p;\n.reg .b64 t;\nsetp.ne.b32 p, %33, 0;\nadd.s64 t, %32, %34;\n"
    "wgmma.mma_async.sync.aligned.m64n56k16.f32.bf16.bf16 {%0, %1, %2, %3, %4, %5, %6, %7, %8, %9, %10, %11, %12, %13, %14, %15, %16, %17, %18, %19, %20, %21, %22, %23, %24, %25, %26, %27}, {%28, %29, %30, %31}, t, p, 1, 1, 1;\n}\n"
    : "+f"(d[RO + 0]), "+f"(d[RO + 1]), "+f"(d[RO + 2]), "+f"(d[RO + 3]), "+f"(d[RO + 4]), "+f"(d[RO + 5]), "+f"(d[RO + 6]), "+f"(d[RO + 7]), "+f"(d[RO + 8]), "+f"(d[RO + 9]), "+f"(d[RO + 10]), "+f"(d[RO + 11]), "+f"(d[RO + 12]), "+f"(d[RO + 13]), "+f"(d[RO + 14]), "+f"(d[RO + 15]), "+f"(d[RO + 16]), "+f"(d[RO + 17]), "+f"(d[RO + 18]), "+f"(d[RO + 19]), "+f"(d[RO + 20]), "+f"(d[RO + 21]), "+f"(d[RO + 22]), "+f"(d[RO + 23]), "+f"(d[RO + 24]), "+f"(d[RO + 25]), "+f"(d[RO + 26]), "+f"(d[RO + 27])
    : "r"(a.x), "r"(a.y), "r"(a.z), "r"(a.w), "l"(base), "r"(scale_d), "n"(OFF >> 4));
}
template <long long OFF, int RO = 0, int N>
__device__ __forceinline__ void wgmma_rs_n64(float (&d)[N], const uint4& a, uint64_t base, int scale_d) {
  asm volatile("{\n.reg .pred p;\n.reg .b64 t;\nsetp.ne.b32 p, %37, 0;\nadd.s64 t, %36, %38;\n"
    "wgmma.mma_async.sync.aligned.m64n64k16.f32.bf16.bf16 {%0, %1, %2, %3, %4, %5, %6, %7, %8, %9, %10, %11, %12, %13, %14, %15, %16, %17, %18, %19, %20, %21, %22, %23, %24, %25, %26, %27, %28, %29, %30, %31}, {%32, %33, %34, %35}, t, p, 1, 1, 1;\n}\n"
    : "+f"(d[RO + 0]), "+f"(d[RO + 1]), "+f"(d[RO + 2]), "+f"(d[RO + 3]), "+f"(d[RO + 4]), "+f"(d[RO + 5]), "+f"(d[RO + 6]), "+f"(d[RO + 7]), "+f"(d[RO + 8]), "+f"(d[RO + 9]), "+f"(d[RO + 10]), "+f"(d[RO + 11]), "+f"(d[RO + 12]), "+f"(d[RO + 13]), "+f"(d[RO + 14]), "+f"(d[RO + 15]), "+f"(d[RO + 16]), "+f"(d[RO + 17]), "+f"(d[RO + 18]), "+f"(d[RO + 19]), "+f"(d[RO + 20]), "+f"(d[RO + 21]), "+f"(d[RO + 22]), "+f"(d[RO + 23]), "+f"(d[RO + 24]), "+f"(d[RO + 25]), "+f"(d[RO + 26]), "+f"(d[RO + 27]), "+f"(d[RO + 28]), "+f"(d[RO + 29]), "+f"(d[RO + 30]), "+f"(d[RO + 31])
    : "r"(a.x), "r"(a.y), "r"(a.z), "r"(a.w), "l"(base), "r"(scale_d), "n"(OFF >> 4));
}
template <long long OFF, int RO = 0, int N>
__device__ __forceinline__ void wgmma_rk_n64(float (&d)[N], const uint4& a, uint64_t base, int scale_d) {
  asm volatile("{\n.reg .pred p;\n.reg .b64 t;\nsetp.ne.b32 p, %37, 0;\nadd.s64 t, %36, %38;\n"
    "wgmma.mma_async.sync.aligned.m64n64k16.f32.bf16.bf16 {%0, %1, %2, %3, %4, %5, %6, %7, %8, %9, %10, %11, %12, %13, %14, %15, %16, %17, %18, %19, %20, %21, %22, %23, %24, %25, %26, %27, %28, %29, %30, %31}, {%32, %33, %34, %35}, t, p, 1, 1, 0;\n}\n"
    : "+f"(d[RO + 0]), "+f"(d[RO + 1]), "+f"(d[RO + 2]), "+f"(d[RO + 3]), "+f"(d[RO + 4]), "+f"(d[RO + 5]), "+f"(d[RO + 6]), "+f"(d[RO + 7]), "+f"(d[RO + 8]), "+f"(d[RO + 9]), "+f"(d[RO + 10]), "+f"(d[RO + 11]), "+f"(d[RO + 12]), "+f"(d[RO + 13]), "+f"(d[RO + 14]), "+f"(d[RO + 15]), "+f"(d[RO + 16]), "+f"(d[RO + 17]), "+f"(d[RO + 18]), "+f"(d[RO + 19]), "+f"(d[RO + 20]), "+f"(d[RO + 21]), "+f"(d[RO + 22]), "+f"(d[RO + 23]), "+f"(d[RO + 24]), "+f"(d[RO + 25]), "+f"(d[RO + 26]), "+f"(d[RO + 27]), "+f"(d[RO + 28]), "+f"(d[RO + 29]), "+f"(d[RO + 30]), "+f"(d[RO + 31])
    : "r"(a.x), "r"(a.y), "r"(a.z), "r"(a.w), "l"(base), "r"(scale_d), "n"(OFF >> 4));
}
template <long long OFF, int RO = 0, int N>
__device__ __forceinline__ void wgmma_rs_n128(float (&d)[N], const uint4& a, uint64_t base, int scale_d) {
  asm volatile("{\n.reg .pred p;\n.reg .b64 t;\nsetp.ne.b32 p, %69, 0;\nadd.s64 t, %68, %70;\n"
    "wgmma.mma_async.sync.aligned.m64n128k16.f32.bf16.bf16 {%0, %1, %2, %3, %4, %5, %6, %7, %8, %9, %10, %11, %12, %13, %14, %15, %16, %17, %18, %19, %20, %21, %22, %23, %24, %25, %26, %27, %28, %29, %30, %31, %32, %33, %34, %35, %36, %37, %38, %39, %40, %41, %42, %43, %44, %45, %46, %47, %48, %49, %50, %51, %52, %53, %54, %55, %56, %57, %58, %59, %60, %61, %62, %63}, {%64, %65, %66, %67}, t, p, 1, 1, 1;\n}\n"
    : "+f"(d[RO + 0]), "+f"(d[RO + 1]), "+f"(d[RO + 2]), "+f"(d[RO + 3]), "+f"(d[RO + 4]), "+f"(d[RO + 5]), "+f"(d[RO + 6]), "+f"(d[RO + 7]), "+f"(d[RO + 8]), "+f"(d[RO + 9]), "+f"(d[RO + 10]), "+f"(d[RO + 11]), "+f"(d[RO + 12]), "+f"(d[RO + 13]), "+f"(d[RO + 14]), "+f"(d[RO + 15]), "+f"(d[RO + 16]), "+f"(d[RO + 17]), "+f"(d[RO + 18]), "+f"(d[RO + 19]), "+f"(d[RO + 20]), "+f"(d[RO + 21]), "+f"(d[RO + 22]), "+f"(d[RO + 23]), "+f"(d[RO + 24]), "+f"(d[RO + 25]), "+f"(d[RO + 26]), "+f"(d[RO + 27]), "+f"(d[RO + 28]), "+f"(d[RO + 29]), "+f"(d[RO + 30]), "+f"(d[RO + 31]), "+f"(d[RO + 32]), "+f"(d[RO + 33]), "+f"(d[RO + 34]), "+f"(d[RO + 35]), "+f"(d[RO + 36]), "+f"(d[RO + 37]), "+f"(d[RO + 38]), "+f"(d[RO + 39]), "+f"(d[RO + 40]), "+f"(d[RO + 41]), "+f"(d[RO + 42]), "+f"(d[RO + 43]), "+f"(d[RO + 44]), "+f"(d[RO + 45]), "+f"(d[RO + 46]), "+f"(d[RO + 47]), "+f"(d[RO + 48]), "+f"(d[RO + 49]), "+f"(d[RO + 50]), "+f"(d[RO + 51]), "+f"(d[RO + 52]), "+f"(d[RO + 53]), "+f"(d[RO + 54]), "+f"(d[RO + 55]), "+f"(d[RO + 56]), "+f"(d[RO + 57]), "+f"(d[RO + 58]), "+f"(d[RO + 59]), "+f"(d[RO + 60]), "+f"(d[RO + 61]), "+f"(d[RO + 62]), "+f"(d[RO + 63])
    : "r"(a.x), "r"(a.y), "r"(a.z), "r"(a.w), "l"(base), "r"(scale_d), "n"(OFF >> 4));
}
template <int OFFA, int OFFB>
__device__ __forceinline__ void wgmma_ss_n64(float (&d)[32], uint64_t basea, uint64_t baseb, int scale_d) {
  asm volatile("{\n.reg .pred p;\n.reg .b64 t, u;\nsetp.ne.b32 p, %34, 0;\nadd.s64 t, %32, %35;\nadd.s64 u, %33, %36;\n"
    "wgmma.mma_async.sync.aligned.m64n64k16.f32.bf16.bf16 {%0, %1, %2, %3, %4, %5, %6, %7, %8, %9, %10, %11, %12, %13, %14, %15, %16, %17, %18, %19, %20, %21, %22, %23, %24, %25, %26, %27, %28, %29, %30, %31}, t, u, p, 1, 1, 1, 1;\n}\n"
    : "+f"(d[0]), "+f"(d[1]), "+f"(d[2]), "+f"(d[3]), "+f"(d[4]), "+f"(d[5]), "+f"(d[6]), "+f"(d[7]), "+f"(d[8]), "+f"(d[9]), "+f"(d[10]), "+f"(d[11]), "+f"(d[12]), "+f"(d[13]), "+f"(d[14]), "+f"(d[15]), "+f"(d[16]), "+f"(d[17]), "+f"(d[18]), "+f"(d[19]), "+f"(d[20]), "+f"(d[21]), "+f"(d[22]), "+f"(d[23]), "+f"(d[24]), "+f"(d[25]), "+f"(d[26]), "+f"(d[27]), "+f"(d[28]), "+f"(d[29]), "+f"(d[30]), "+f"(d[31])
    : "l"(basea), "l"(baseb), "r"(scale_d), "n"(OFFA >> 4), "n"(OFFB >> 4));
}

__device__ __forceinline__ void publish7(char* b16, char* b8, const uint32_t (&P)[14], uint32_t par) {
  st_rlx4(b16, tag(P[0], par), P[1], P[2], P[3]);
  st_rlx4(b16 + 512, tag(P[4], par), P[5], P[6], P[7]);
  st_rlx4(b16 + 1024, tag(P[8], par), P[9], P[10], P[11]);
  st_rlx2(b8, tag(P[12], par), P[13]);
}
template <int GOFF>
__device__ __forceinline__ void fix7(uint4* v, const char* g, uint32_t par, int& budget) {
  asm volatile("{\n.reg .pred p;\n.reg .b32 t, w<4>;\nsetp.eq.s32 p, %28, 0;\nC:\n@!p bra.uni L;\nadd.s32 %28, %28, -1;\n"
               "ld.relaxed.gpu.global.v4.u32 {%0,%1,%2,%3}, [%29+%31+0];\n"
               "ld.relaxed.gpu.global.v4.u32 {%4,%5,%6,%7}, [%29+%31+512];\n"
               "ld.relaxed.gpu.global.v4.u32 {%8,%9,%10,%11}, [%29+%31+1024];\n"
               "ld.relaxed.gpu.global.v4.u32 {%12,%13,%14,%15}, [%29+%31+1536];\n"
               "ld.relaxed.gpu.global.v4.u32 {%16,%17,%18,%19}, [%29+%31+2048];\n"
               "ld.relaxed.gpu.global.v4.u32 {%20,%21,%22,%23}, [%29+%31+2560];\n"
               "ld.relaxed.gpu.global.v4.u32 {%24,%25,%26,%27}, [%29+%31+3072];\n"
               "L:\nlop3.b32 w0, %0, %4, %30, 0x7e;\nlop3.b32 w1, %8, %12, %30, 0x7e;\nlop3.b32 w2, %16, %20, %30, 0x7e;\nxor.b32 w3, %24, %30;\n"
               "lop3.b32 t, w0, w1, w2, 0xfe;\nlop3.b32 t, t, w3, 1, 0xa8;\n"
               "setp.ne.u32 p, t, 0;\nsetp.gt.and.s32 p, %28, 0, p;\nvote.sync.any.pred p, p, 0xffffffff;\n@p bra.uni C;\n}"
               : "+r"(v[0].x), "+r"(v[0].y), "+r"(v[0].z), "+r"(v[0].w), "+r"(v[1].x), "+r"(v[1].y), "+r"(v[1].z), "+r"(v[1].w), "+r"(v[2].x), "+r"(v[2].y), "+r"(v[2].z), "+r"(v[2].w), "+r"(v[3].x), "+r"(v[3].y), "+r"(v[3].z), "+r"(v[3].w), "+r"(v[4].x), "+r"(v[4].y), "+r"(v[4].z), "+r"(v[4].w), "+r"(v[5].x), "+r"(v[5].y), "+r"(v[5].z), "+r"(v[5].w), "+r"(v[6].x), "+r"(v[6].y), "+r"(v[6].z), "+r"(v[6].w), "+r"(budget)
               : "l"(g), "r"(par), "n"(GOFF) : "memory");
}
template <int SOFF>
__device__ __forceinline__ void load7s(uint4* v, uint32_t s, uint32_t s8) {
  asm volatile("ld.shared.v4.u32 {%0,%1,%2,%3}, [%28+%30+0];\n"
               "ld.shared.v4.u32 {%4,%5,%6,%7}, [%28+%30+512];\n"
               "ld.shared.v4.u32 {%8,%9,%10,%11}, [%28+%30+1024];\n"
               "ld.shared.v2.u32 {%12,%13}, [%29+%30+1536];\nld.shared.v2.u32 {%14,%15}, [%29+%30+1792];\n"
               "ld.shared.v4.u32 {%16,%17,%18,%19}, [%28+%30+2048];\n"
               "ld.shared.v4.u32 {%20,%21,%22,%23}, [%28+%30+2560];\n"
               "ld.shared.v4.u32 {%24,%25,%26,%27}, [%28+%30+3072];\n"
               : "=r"(v[0].x), "=r"(v[0].y), "=r"(v[0].z), "=r"(v[0].w), "=r"(v[1].x), "=r"(v[1].y), "=r"(v[1].z), "=r"(v[1].w), "=r"(v[2].x), "=r"(v[2].y), "=r"(v[2].z), "=r"(v[2].w), "=r"(v[3].x), "=r"(v[3].y), "=r"(v[3].z), "=r"(v[3].w), "=r"(v[4].x), "=r"(v[4].y), "=r"(v[4].z), "=r"(v[4].w), "=r"(v[5].x), "=r"(v[5].y), "=r"(v[5].z), "=r"(v[5].w), "=r"(v[6].x), "=r"(v[6].y), "=r"(v[6].z), "=r"(v[6].w)
               : "r"(s), "r"(s8), "n"(SOFF) : "memory");
}
template <int GOFF>
__device__ __forceinline__ void fix7s(uint4* v, const char* g, uint32_t par, int& budget) {
  asm volatile("{\n.reg .pred p;\n.reg .b32 t, w<4>;\n.reg .b64 h;\nsetp.eq.s32 p, %28, 0;\nC:\n@!p bra.uni L;\n"
               "add.s32 %28, %28, -1;\nmov.u32 t, %%laneid;\nmad.wide.s32 h, t, -8, %29;\n"
               "ld.relaxed.gpu.global.v4.u32 {%0,%1,%2,%3}, [%29+%31+0];\n"
               "ld.relaxed.gpu.global.v4.u32 {%4,%5,%6,%7}, [%29+%31+512];\n"
               "ld.relaxed.gpu.global.v4.u32 {%8,%9,%10,%11}, [%29+%31+1024];\n"
               "ld.relaxed.gpu.global.v2.u32 {%12,%13}, [h+%31+1536];\nld.relaxed.gpu.global.v2.u32 {%14,%15}, [h+%31+1792];\n"
               "ld.relaxed.gpu.global.v4.u32 {%16,%17,%18,%19}, [%29+%31+2048];\n"
               "ld.relaxed.gpu.global.v4.u32 {%20,%21,%22,%23}, [%29+%31+2560];\n"
               "ld.relaxed.gpu.global.v4.u32 {%24,%25,%26,%27}, [%29+%31+3072];\nL:\n"
               "lop3.b32 w0, %0, %4, %30, 0x7e;\nlop3.b32 w1, %8, %12, %30, 0x7e;\nlop3.b32 w2, %14, %16, %30, 0x7e;\nlop3.b32 w3, %20, %24, %30, 0x7e;\n"
               "lop3.b32 t, w0, w1, w2, 0xfe;\nlop3.b32 t, t, w3, 1, 0xa8;\n"
               "setp.ne.u32 p, t, 0;\nsetp.gt.and.s32 p, %28, 0, p;\nvote.sync.any.pred p, p, 0xffffffff;\n@p bra.uni C;\n}"
               : "+r"(v[0].x), "+r"(v[0].y), "+r"(v[0].z), "+r"(v[0].w), "+r"(v[1].x), "+r"(v[1].y), "+r"(v[1].z), "+r"(v[1].w), "+r"(v[2].x), "+r"(v[2].y), "+r"(v[2].z), "+r"(v[2].w), "+r"(v[3].x), "+r"(v[3].y), "+r"(v[3].z), "+r"(v[3].w), "+r"(v[4].x), "+r"(v[4].y), "+r"(v[4].z), "+r"(v[4].w), "+r"(v[5].x), "+r"(v[5].y), "+r"(v[5].z), "+r"(v[5].w), "+r"(v[6].x), "+r"(v[6].y), "+r"(v[6].z), "+r"(v[6].w), "+r"(budget)
               : "l"(g), "r"(par), "n"(GOFF) : "memory");
}
template <int GOFF>
__device__ __forceinline__ void fix7t(uint4* v, const char* base, uint32_t off, uint32_t s, uint32_t s8, uint32_t par, int& budget) {
  asm volatile("{\n.reg .pred p;\n.reg .b32 t, w<4>;\n.reg .b64 g, h;\nC:\n"
               "lop3.b32 w0, %0, %4, %30, 0x7e;\nlop3.b32 w1, %8, %12, %30, 0x7e;\nlop3.b32 w2, %14, %16, %30, 0x7e;\nlop3.b32 w3, %20, %24, %30, 0x7e;\n"
               "lop3.b32 t, w0, w1, w2, 0xfe;\nlop3.b32 t, t, w3, 1, 0xa8;\n"
               "setp.ne.u32 p, t, 0;\nvote.sync.any.pred p, p, 0xffffffff;\n@!p bra.uni L;\n"
               "add.s32 %28, %28, -1;\nsetp.le.s32 p, %28, 0;\n@p bra.uni L;\n"
               "add.u32 t, %32, %33;\nmad.wide.u32 g, t, 1, %29;\nadd.u32 t, %32, %34;\nmad.wide.u32 h, t, 1, %29;\n"
               "ld.relaxed.gpu.global.v4.u32 {%0,%1,%2,%3}, [g+%31+0];\n"
               "ld.relaxed.gpu.global.v4.u32 {%4,%5,%6,%7}, [g+%31+512];\n"
               "ld.relaxed.gpu.global.v4.u32 {%8,%9,%10,%11}, [g+%31+1024];\n"
               "ld.relaxed.gpu.global.v2.u32 {%12,%13}, [h+%31+1536];\nld.relaxed.gpu.global.v2.u32 {%14,%15}, [h+%31+1792];\n"
               "ld.relaxed.gpu.global.v4.u32 {%16,%17,%18,%19}, [g+%31+2048];\n"
               "ld.relaxed.gpu.global.v4.u32 {%20,%21,%22,%23}, [g+%31+2560];\n"
               "ld.relaxed.gpu.global.v4.u32 {%24,%25,%26,%27}, [g+%31+3072];\nbra.uni C;\nL:\n}"
               : "+r"(v[0].x), "+r"(v[0].y), "+r"(v[0].z), "+r"(v[0].w), "+r"(v[1].x), "+r"(v[1].y), "+r"(v[1].z), "+r"(v[1].w), "+r"(v[2].x), "+r"(v[2].y), "+r"(v[2].z), "+r"(v[2].w), "+r"(v[3].x), "+r"(v[3].y), "+r"(v[3].z), "+r"(v[3].w), "+r"(v[4].x), "+r"(v[4].y), "+r"(v[4].z), "+r"(v[4].w), "+r"(v[5].x), "+r"(v[5].y), "+r"(v[5].z), "+r"(v[5].w), "+r"(v[6].x), "+r"(v[6].y), "+r"(v[6].z), "+r"(v[6].w), "+r"(budget)
               : "l"(base), "r"(par), "n"(GOFF - (int)sb - OFF_G), "r"(off), "r"(s), "r"(s8) : "memory");
}
template <int OFF>
__device__ __forceinline__ void fixq(uint4& v, uint32_t a, uint32_t s, const char* g, uint32_t par, int& budget) {
  asm volatile("{\n.reg .pred p;\n.reg .b32 t, u, w<28>;\nsetp.eq.s32 p, %4, 0;\nC:\n@!p bra.uni L;\nadd.s32 %4, %4, -1;\n"
               "ld.relaxed.gpu.global.v4.u32 {w0,w1,w2,w3}, [%7+%9+0];\n"
               "ld.relaxed.gpu.global.v4.u32 {w4,w5,w6,w7}, [%7+%9+512];\n"
               "ld.relaxed.gpu.global.v4.u32 {w8,w9,w10,w11}, [%7+%9+1024];\n"
               "ld.relaxed.gpu.global.v4.u32 {w12,w13,w14,w15}, [%7+%9+1536];\n"
               "ld.relaxed.gpu.global.v4.u32 {w16,w17,w18,w19}, [%7+%9+2048];\n"
               "ld.relaxed.gpu.global.v4.u32 {w20,w21,w22,w23}, [%7+%9+2560];\n"
               "ld.relaxed.gpu.global.v4.u32 {w24,w25,w26,w27}, [%7+%9+3072];\n"
               "st.shared.v4.u32 [%6+%9+0], {w0,w1,w2,w3};\n"
               "st.shared.v4.u32 [%6+%9+512], {w4,w5,w6,w7};\n"
               "st.shared.v4.u32 [%6+%9+1024], {w8,w9,w10,w11};\n"
               "st.shared.v4.u32 [%6+%9+1536], {w12,w13,w14,w15};\n"
               "st.shared.v4.u32 [%6+%9+2048], {w16,w17,w18,w19};\n"
               "st.shared.v4.u32 [%6+%9+2560], {w20,w21,w22,w23};\n"
               "st.shared.v4.u32 [%6+%9+3072], {w24,w25,w26,w27};\n"
               "fence.proxy.async.shared::cta;\nbar.warp.sync 0xffffffff;\n"
               "ld.shared.u32 %0, [%5+%9];\nld.shared.u32 %1, [%5+%9+896];\nld.shared.u32 %2, [%5+%9+1792];\nld.shared.u32 %3, [%5+%9+2688];\n"
               "L:\nlop3.b32 t, %0, %1, %8, 0x7e;\nlop3.b32 u, %2, %3, %8, 0x7e;\nlop3.b32 t, t, u, 1, 0xa8;\n"
               "setp.ne.u32 p, t, 0;\nsetp.gt.and.s32 p, %4, 0, p;\nvote.sync.any.pred p, p, 0xffffffff;\n@p bra.uni C;\n}"
               : "+r"(v.x), "+r"(v.y), "+r"(v.z), "+r"(v.w), "+r"(budget)
               : "r"(a), "r"(s), "l"(g), "r"(par), "n"(OFF) : "memory");
}
#define SPINS(i)
#define RETRY(i, ...) __VA_ARGS__
#define BAR(i) (sb + SMEM_BAR + 8 * (i))
#define WAIT(b, ph) mbar_wait(b, ph, budget)

template <bool SWAP>
__global__ void __launch_bounds__(384, 1)
fused_block_kernel(char* const buf, const char* __restrict__ wo, const uint64_t d128, const uint64_t d64, const uint64_t d0,
                   const uint64_t dq, const uint64_t d1, const uint64_t dko,
                   const char* __restrict__ wg, const char* __restrict__ wu, const char* __restrict__ wd, const char* __restrict__ wq, char* __restrict__ out,
                   const __grid_constant__ CUtensorMap map_x, const __grid_constant__ CUtensorMap map_qkv,
                   const __grid_constant__ CUtensorMap map_wo, const __grid_constant__ CUtensorMap map_gu,
                   const __grid_constant__ CUtensorMap map_gu32) {
  extern __shared__ __align__(1024) uint8_t smem[];
  const int tid = threadIdx.x, lane = tid & 31;
  const int warp = __shfl_sync(0xffffffffu, tid >> 5, 0);
#define KVTHR 0xC0800000
#define KVP 1152
#define OFP 1
#define PP 0
#define WT 0xff4422
#define HORD 0
#define ORED1 8
#define B6 1
#define LA0 1
#define LA1 2
#define W4G 4
#define PFT 0x222
#define PFW 2
#define PFV 3
#define EPC 1
#define QG 1
#define GGATE 2
#define RPK 1
#define OPUB 14
#define HRED 5
#define HRED1 5
#define ORED 2
  const int cta = (blockIdx.x & 56) * 2 + (blockIdx.x & 1) * 8 + (blockIdx.x & 6) + (blockIdx.x >> 6), r = cta >> 3, p = cta & 7;
  const int kh = p & 1;
  const int wcol = 56 * p - 8 * kh;
  int budget = SPIN_LIMIT;
  const uint32_t zero = d0 >> 48;
  STAMP(0);
  if (warp < 8) {
    STAMP(60);
    bar_sync<0, 384>();
    STAMP(63);
    asm volatile("setmaxnreg.inc.sync.aligned.u32 224;");
    STAMP(61);
    const int g = warp >> 2, gq = lane >> 2, tq = lane & 3;
    const uint64_t dk = d128 + kh;
    uint4 A[28];
    float rs0, rs1, m0, m1;
    float acc0[28], acc1[28];
    uint32_t mb0, mb1;
    {
      uint32_t la[4];
#pragma unroll
      for (int i = 0; i < 4; i++) {
        la[i] = sb + OFF_X + warp * TILE + (lane & 15) * 128 + (((2 * i + (lane >> 4)) ^ (lane & 7)) << 4);
        asm volatile("" : "+r"(la[i]));
      }
      STAMP(62);
      WAIT(BAR(B_XB + warp), 0);
      STAMP(1);
#pragma unroll
      for (int ks = 0; ks < 28; ks++) A[ks] = ldsm4(la[ks & 3] + (ks >> 2) * 2048);
      float cs[4][4] = {};
#pragma unroll
      for (int ks = 0; ks < 28; ks++) mma16816(cs[ks & 3], A[ks].x, A[ks].y, A[ks].z, A[ks].w, 0x3F803F80u, 0x3F803F80u);
      m0 = ((cs[0][0] + cs[1][0]) + (cs[2][0] + cs[3][0])) * (1.f / DM);
      m1 = ((cs[0][2] + cs[1][2]) + (cs[2][2] + cs[3][2])) * (1.f / DM);
      mb0 = pack2(m0, m0); mb1 = pack2(m1, m1);
      if (lane == 0) mbar_arrive(BAR(B_XFREE) + (mb0 & zero));
      if (tq < 2) sts1(sb + OFF_M + warp * 64 + gq * 4 + tq * 32, __float_as_uint(tq ? m1 : m0));
    }
    STAMP(2);
    uint32_t pa[7];
    {
      const uint32_t prow = sb + OFF_PK + warp * 4096 + gq * 128 + (gq << 4), t = tq >> 1;
      const uint32_t b2 = (prow + ((4 * tq + 8) & 15)) ^ (t << 4);
      pa[0] = prow + 4 * tq; pa[1] = pa[0] ^ 16; pa[2] = pa[0] ^ 32;
      pa[3] = (prow + 4 * (tq & 1)) ^ (48 + 16 * t);
      pa[4] = b2 ^ 64; pa[5] = b2 ^ 80 ^ (t << 5); pa[6] = b2 ^ 96;
#pragma unroll
      for (int j = 0; j < 7; j++) asm volatile("" : "+r"(pa[j]));
    }
    auto sqs = [&](int q) {
      uint4 s;
#pragma unroll
      for (int ks = 7 * q; ks < 7 * q + 7; ks++) {
        if (ks % 7 == 0) s = make_uint4(sq2(A[ks].x), sq2(A[ks].y), sq2(A[ks].z), sq2(A[ks].w));
        else s = make_uint4(sq2(A[ks].x, s.x), sq2(A[ks].y, s.y), sq2(A[ks].z, s.z), sq2(A[ks].w, s.w));
      }
      s.x = add2(s.x, s.z);
      s.y = add2(s.y, s.w);
      rs0 = (q ? rs0 : 0.f) + (bf_lo(s.x) + bf_hi(s.x));
      rs1 = (q ? rs1 : 0.f) + (bf_lo(s.y) + bf_hi(s.y));
      if (q == 3) {
        rs0 += shx(rs0, 1); rs1 += shx(rs1, 1);
        rs0 += shx(rs0, 2); rs1 += shx(rs1, 2);
      }
      asm volatile("" : "+f"(rs0), "+f"(rs1));
    };
    auto sub = [&](int q) {
#pragma unroll
      for (int ks = 7 * q; ks < 7 * q + 7; ks++)
        A[ks] = make_uint4(sub2(A[ks].x, mb0), sub2(A[ks].y, mb1), sub2(A[ks].z, mb0), sub2(A[ks].w, mb1));
    };
    uint32_t sdw;
    float4 c0, c1;
    auto stats = [&] {
      const float d0 = m0 - bf_lo(mb0), d1 = m1 - bf_lo(mb1);
      const float q0 = fmaxf(rs0 * (1.f / DM) - d0 * d0, 0.f) + 1e-5f;
      const float q1 = fmaxf(rs1 * (1.f / DM) - d1 * d1, 0.f) + 1e-5f;
      rs0 = rsqf(q0);
      rs1 = rsqf(q1);
      const float sd = (tq & 2 ? q1 * rs1 : q0 * rs0);
      sdw = pack2(sd, sd - bf_lo(pack2(sd, 0.f)));
      c0 = make_float4(rs0 * 1.4426950408889634f, lg2f(rs0), rs0 * rs0, 1e-6f * rs0);
      c1 = make_float4(rs1 * 1.4426950408889634f, lg2f(rs1), rs1 * rs1, 1e-6f * rs1);
      asm volatile("" : "+r"(sdw), "+f"(c0.x), "+f"(c0.y), "+f"(c0.z), "+f"(c0.w), "+f"(c1.x), "+f"(c1.y), "+f"(c1.z), "+f"(c1.w));
    };
    sub(0);
    sub(1);
    sqs(0);
    sfor<4>([&](auto J) {
      constexpr int j = J;
      WAIT(BAR(B_K + j), 0);
      STAMP(26 + j);
      if (j == 0 && g) bar_sync<7, 256>();
      wg_fence();
      sfor<7>([&](auto I) { wgmma_rs_n56<2 * STG + (7 * j + I) * 2048>(acc0, A[7 * j + I], dk, j + I != 0); });
      if (j == 0 && !g) bar_arrive<7, 256>();
      if (j < 2) sub(j + 2);
      if (j < 3) sqs(j + 1);
      if (j == 2) stats();
    });
    wg_commit();
    STAMP(3);
    WAIT(BAR(B_V), 0);
    STAMP(10);
    wg_fence();
    sfor<7>([&](auto I) { wgmma_rs_n56<I * 2048>(acc1, A[I], dk, I != 0); });
    wg_commit();
    WAIT(BAR(B_XFREE), 0);
    wg_wait<1>();
    acc_fence(acc0);
    STAMP(4);
    if (lane == 0) mbar_arrive(BAR(B_KFREE));
    sfor<7>([&](auto J) {
      constexpr int j = J;
      sfor<3>([&](auto I) {
        constexpr int ks = 7 + 3 * j + I;
        if (ks % 7 == 0) { WAIT(BAR(B_V + ks / 7), 0); STAMP(49 + ks / 7); wg_fence(); }
        wgmma_rs_n56<ks * 2048>(acc1, A[ks], dk, 1);
      });
      sts1(pa[j], pack2(phi(acc0[4 * j], c0), phi(acc0[4 * j + 1], c0)));
      sts1(pa[j] + 1024, pack2(phi(acc0[4 * j + 2], c1), phi(acc0[4 * j + 3], c1)));
    });
    wg_commit();
    if (QG == 0 && g == 1) bar_arrive<3, 256>();
    sts1(((pa[0] & ~15u) ^ (48 + 64 * (tq & 1))) + 2048 + 8 + ((tq >> 1) << 10), sdw);
    wg_wait<0>();
    acc_fence(acc1);
    STAMP(5);
    STAMP(54);
#pragma unroll
    for (int j = 0; j < 7; j++) {
      sts1(pa[j] + 2048, pack2(acc1[4 * j], acc1[4 * j + 1]));
      sts1(pa[j] + 3072, pack2(acc1[4 * j + 2], acc1[4 * j + 3]));
    }
    fence_async_smem();
    if (lane == 0) mbar_arrive(BAR(B_VFREE));
    if (g == 0) {
      bar_arrive<1, 256>();
      bar_sync<3, 256>();
    } else {
      bar_sync<1, 256>();
      STAMP(55);
      float kv[32];
      wg_fence();
      sfor<8>([&](auto I) {
        constexpr int o = OFF_PK + I * 4096;
        wgmma_ss_n64<o, o + 2048>(kv, d128, d128, I != 0);
      });
      wg_commit();
      if (QG == 1) bar_arrive<3, 256>();
      WAIT(BAR(B_INIT), 0);
      char* da = buf + (A_KVR + p * KVR_B + (warp & 3) * 2176) + (uint32_t)(gq * 64 + (tq & 1) * 32 + (tq & 2) * 8);
      char *db = da + (uint32_t)(1152 + gq * 64), *dz = da + (uint32_t)(1008 - gq * 48);
      asm volatile("" : "+l"(da), "+l"(db), "+l"(dz));
      wg_wait<0>();
      acc_fence(kv);
      if (QG == 2) bar_arrive<3, 256>();
      STAMP(56);
      auto put = [&](const float* v, int n) {
        const int b = n & 2;
        if (!b || (tid & 48) != 48) {
          if (n & 1) red_add4(b ? db + 64 : da + 512, v[b + 8], v[b + 9], tq & 2 ? v[b + 5] : v[b + 12], tq & 2 ? 1.f : v[b + 13]);
          else red_add4(b ? db : da, v[b], v[b + 1], v[b + 4], tq & 2 ? 1.f : v[b + 5]);
        }
      };
#pragma unroll
      for (int i = 0; i < 16; i++) kv[i] = warp & 2 ? kv[16 + i] : kv[i];
#pragma unroll
      for (int n = 0; n < 4; n++) put(kv, n);
      if (tq == 2) red_add4(dz, kv[12] + kv[13], kv[14] + kv[15], 0.f, 1.f);
      STAMP(53);
      if (QG == 3) bar_arrive<3, 256>();
    }
    STAMP(6);
    const uint32_t par = EPC ? ~ld_rlx1(&g_cnt[C_ROW + r * 32 + g]) >> 5 & 1 : ~ld_rlx1(&g_epoch[cta * 32]) & 1;
    WAIT(BAR(B_Q), 0);
    wg_fence();
    sfor<28>([&](auto I) { wgmma_rs_n56<I * 2048>(acc0, A[I], dq + kh, I != 0); });
    wg_commit();
    const uint32_t wb = BAR(B_WB) + 32 * g;
    const int wq4 = warp & 3;
    char* const oblk = buf + (A_O + (r * 2 + g) * 2 * STG);
    const uint32_t gsub = sb + OFF_G + g * 2 * STG + wq4 * 3584 + lane * 16, gsub8 = gsub - lane * 8;
    const char* const olane = oblk + (uint32_t)(wq4 * 3584 + lane * 16);
    char* const ob = oblk + (uint32_t)((p >> 1) * TILE + wq4 * 3584 + kh * 896 + gq * 16);
    char *ob16 = ob + tq * 128, *ob8 = ob + 512 + (tq >> 1) * 128 + (tq & 1) * 8, *ob4 = ob + 768 + tq * 4;
    unsigned* cnt = &g_cnt[C_ROW + r * 32];
    asm volatile("" : "+l"(ob16), "+l"(ob8), "+l"(ob4), "+l"(cnt));
    wg_wait<0>();
    acc_fence(acc0);
    STAMP(7);
    if (lane < 2) mbar_arrive(BAR(B_QFREE + lane));
    uint32_t R[14];
    {
      uint4 Q[4];
#pragma unroll
      for (int j = 0; j < 7; j++) {
        const uint32_t lo = pack2(phi(acc0[4 * j], c0), phi(acc0[4 * j + 1], c0));
        const uint32_t hi = pack2(phi(acc0[4 * j + 2], c1), phi(acc0[4 * j + 3], c1));
        if (j & 1) { Q[j >> 1].z = lo; Q[j >> 1].w = hi; } else { Q[j >> 1].x = lo; Q[j >> 1].y = hi; }
      }
      Q[3].z = 0; Q[3].w = 0;
      STAMP(8);
      WAIT(BAR(B_KVB), 0);
      STAMP(9);
      float o[32];
      wg_fence();
      sfor<4>([&](auto I) { wgmma_rs_n64<OFF_KVB + I * 2048>(o, Q[I], d128, I != 0); });
      wg_commit();
      if (ORED == 1 && !g && lane == 0) red_inc(cnt);
      wg_wait<0>();
      if (ORED == 2 && !g && lane == 0) red_inc(cnt);
      acc_fence(o);
      if (ORED == 3 && !g && lane == 0) red_inc(cnt);
      const float da0 = rcpf(o[28] + c0.w), db0 = rcpf(o[29] + c0.w), da1 = rcpf(o[30] + c1.w), db1 = rcpf(o[31] + c1.w);
      uint32_t P[14];
#pragma unroll
      for (int j = 0; j < 7; j++) {
        const bool first = j < 2 || (j < 4 && tq < 3);
        const float s0 = first ? da0 : db0, s1 = first ? da1 : db1;
        P[2 * j] = pack2(o[4 * j] * s0, o[4 * j + 1] * s0);
        P[2 * j + 1] = pack2(o[4 * j + 2] * s1, o[4 * j + 3] * s1);
        if (0x53 >> j & 1) { P[2 * j] = tag(P[2 * j], par); P[2 * j + 1] = tag(P[2 * j + 1], par); }
      }
      auto publish = [&] {
#pragma unroll
        for (int h = 0; h < 2; h++) {
          if (ORED == 4 + h && !g && lane == 0) red_inc(cnt);
          st_rlx4(ob16 + 1792 * h, P[h], P[2 + h], P[4 + h], P[6 + h]);
          st_rlx2(ob8 + 1792 * h, P[8 + h], P[10 + h]);
          st_rlx1(ob4 + 1792 * h, P[12 + h]);
        }
      };
      if (!g) {
        publish();
        if (ORED == 6 && lane == 0) red_inc(cnt);
        STAMP(11);
        if (lane == 0) mbar_arrive(BAR(B_OFREE));
        const int sec = min(lane, 27);
        uint32_t ta = sb + OFF_G + wq4 * 3584 + sec * 32 + (0x3625410 >> (sec & 28) & 7) * 4;
        uint32_t gs = gsub;
        const char* ol = olane;
        asm volatile("" : "+r"(ta), "+l"(ol));
#pragma unroll 1
        for (int h = 0; h < 2; h++) {
          sfor<4>([&](auto Q) {
            constexpr int so = Q * TILE;
            WAIT(BAR(B_WB + Q) + 32 * h, 0);
            STAMPD(1 + 4 * h + Q);
            uint4 tg = make_uint4(lds1(ta + so), lds1(ta + so + 896), lds1(ta + so + 1792), lds1(ta + so + 2688));
            RETRY(4 * h + Q, fixq<so>(tg, ta, gs, ol, par, budget));
            bar_arrive_id(8 + Q + 4 * h);
          });
          ol += 2 * STG;
          ta += 2 * STG;
          gs += 2 * STG;
        }
        bar_sync<3, 256>();
      } else {
        const uint32_t wa = sb + (lane >> 4) * 1024 + (lane & 7) * 128 + ((((2 * wq4 + (lane >> 3 & 1) + kh) ^ lane) & 7) << 4);
        uint4 X[8];
#pragma unroll
        for (int i = 0; i < 8; i++) X[i] = ldsm4t(wa + OFF_XS + i * 2048);
        if (OFP == 0 && lane == 0) mbar_arrive(BAR(B_OFREE));
        WAIT(BAR(B_WO), 0);
        const uint32_t keep = wq4 < 3 ? 0x3F803F80u : 0;
#pragma unroll
        for (int ks = 0; ks < 28; ks++) {
          if (ks == ORED1 && lane == 0) red_inc(cnt + 1);
          if (ks == OPUB) {
            WAIT(BAR(B_WO), 0);
            publish();
            STAMP(11);
            WAIT(BAR(B_WO), 0);
          }
          A[ks] = ldsm4t(wa + OFF_WO + ks * 2048);
        }
#pragma unroll
        for (int i = 0; i < 14; i++) {
          const uint4 w = lds4(sb + OFF_WBAR + i * 64 + tq * 16);
          A[2 * i] = make_uint4(add2(A[2 * i].x, w.x), fma2(A[2 * i].y, keep, w.x), add2(A[2 * i].z, w.y), fma2(A[2 * i].w, keep, w.y));
          A[2 * i + 1] = make_uint4(add2(A[2 * i + 1].x, w.z), fma2(A[2 * i + 1].y, keep, w.z), add2(A[2 * i + 1].z, w.w), fma2(A[2 * i + 1].w, keep, w.w));
          asm volatile("" : "+r"(A[2 * i].x), "+r"(A[2 * i].y), "+r"(A[2 * i].z), "+r"(A[2 * i].w),
                            "+r"(A[2 * i + 1].x), "+r"(A[2 * i + 1].y), "+r"(A[2 * i + 1].z), "+r"(A[2 * i + 1].w)::"memory");
          if (OFP == i + 1 && lane == 0) mbar_arrive(BAR(B_OFREE));
        }
        __syncwarp();
        if (lane < 2) mbar_arrive(BAR(B_WOFREE));
        STAMP(10);
        float hacc[2][32];
        uint32_t ma = sb + OFF_M + tq * 8;
        asm volatile("" : "+r"(ma));
#pragma unroll
        for (int j = 0; j < 16; j++) {
          const uint2 m = lds2(ma + 32 * j);
          const uint32_t lo = j & 1 ? X[j / 2].z : X[j / 2].x, hi = keep ? (j & 1 ? X[j / 2].w : X[j / 2].y) : 0;
          float* a = &hacc[j / 8][4 * (j & 7)];
          a[0] = bf_lo(lo) - __uint_as_float(m.x);
          a[1] = bf_hi(lo) - __uint_as_float(m.y);
          a[2] = bf_lo(hi) - __uint_as_float(m.x);
          a[3] = bf_hi(hi) - __uint_as_float(m.y);
        }
        acc_fence(hacc[0]);
        acc_fence(hacc[1]);
        char* hb = oblk + (uint32_t)(FRAG_B - 2 * STG + (p >> 1) * TILE + (wq4 < 3 ? kh * 2048 + wq4 * 512 + lane * 16 : 1536 + kh * 256 + lane * 8));
        asm volatile("" : "+l"(hb));
        STAMP(16);
        auto hmma = [&](auto N) {
          constexpr int h = N / 4, q = N % 4;
          bar_sync<8 + N, 256>();
          STAMP(1 + N);
          wg_fence();
          sfor<7>([&](auto I) { wgmma_rk_n64<OFF_G + N * TILE + I * 256>(hacc[h], A[7 * q + I], dko, 1); });
        };
        sfor<2>([&](auto H) {
          constexpr int h = H;
          sfor<4>([&](auto Q) { if (!h || Q >= HORD) hmma(IC<4 * h + Q>{}); });
          wg_commit();
          if (!h && HORD) {
            sfor<HORD>([&](auto Q) { hmma(IC<4 + Q>{}); });
            wg_commit();
          }
          if (B6 && h) bar_sync<6, 160>();
          if ((h ? HRED1 : HRED) == 4 && lane == 0) red_inc(cnt + 2 + h);
          wg_wait<!h && HORD>();
          if ((h ? HRED1 : HRED) == 5 && lane == 0) red_inc(cnt + 2 + h);
          acc_fence(hacc[h]);
          STAMP(12 + 2 * h);
          if (lane < 2) mbar_arrive(BAR(B_ORD + h));
          if (wq4 < 3) {
#pragma unroll
            for (int i = 0; i < 4; i++) {
              const float* a = hacc[h] + 8 * i;
              st_rlx4(hb + h * 2 * STG + 3584 * i, tag(transp(pack2(a[0], a[1])), par), transp(pack2(a[4], a[5])), transp(pack2(a[2], a[3])), transp(pack2(a[6], a[7])));
            }
          } else {
#pragma unroll
            for (int i = 0; i < 4; i++) {
              const float* a = hacc[h] + 8 * i;
              st_rlx2(hb + h * 2 * STG + 3584 * i, tag(transp(pack2(a[0], a[1])), par), transp(pack2(a[4], a[5])));
            }
            if (gq == 0) {
#pragma unroll
              for (int j = 0; j < 8; j++) sts2(ma + 256 * h + 32 * j, __float_as_uint(hacc[h][4 * j + 2]), __float_as_uint(hacc[h][4 * j + 3]));
            }
          }
          if ((h ? HRED1 : HRED) == 6 && lane == 0) red_inc(cnt + 2 + h);
          STAMP(13 + 2 * h);
          if (h) bar_sync<5, 128>(); else bar_arrive<3, 256>();
        });
      }
      const char* const rb = olane + (FRAG_B + (p >> 1) * TILE);
#pragma unroll
      for (int i = 0; i < 3; i++) {
        const uint4 v = ld_rlx4(rb + kh * 2048 + 512 * i);
        R[4 * i] = v.x; R[4 * i + 1] = v.y; R[4 * i + 2] = v.z; R[4 * i + 3] = v.w;
      }
      const uint2 v = ld_rlx2(rb + 1536 + kh * 256 - lane * 8);
      R[12] = v.x; R[13] = v.y;
    }
    char* hdst = buf + (A_HH + cta * 2 * STG + warp * 3584) + (uint32_t)(lane * 16);
    {
#define GLU(gt, up, e) fmaf((up) * (e), tanhf_((gt) * (e)), (up) * (e))
      float acc[64];
      uint4 own[5];
#pragma unroll
      for (int i = 0; i < 5; i++) asm volatile("" : "=r"(own[i].x), "=r"(own[i].y), "=r"(own[i].z), "=r"(own[i].w));
      sfor<4>([&](auto I) { WAIT(BAR(B_FULL + I), 0); });
      auto ld = [&](auto Q, bool wait) {
        constexpr int q = Q;
        if (q < 4) {
          if (wait) WAIT(wb + 8 * q, 1);
          load7s<q % 4 * TILE>(&A[7 * (q % 4)], gsub, gsub8);
        }
      };
      WAIT(wb, 1);
      STAMP(58);
      ld(IC<0>{}, false);
      sfor<LA0 - 1>([&](auto Q) { ld(IC<Q + 1>{}, true); });
      if (g) sfor<LA1 - LA0>([&](auto Q) { ld(IC<Q + LA0>{}, true); });
#pragma unroll 1
      for (int c = 0; c < 3; c++) {
        const uint32_t half = (c & 1) * 4;
        if (c == 0) {
          sfor<4>([&](auto KQ) {
            constexpr int kq = KQ;
            WAIT(wb + 8 * ((kq + LA0) % 4), 1);
            RETRY(8 + kq + 4 * g, fix7t<A_H + kq * TILE>(&A[7 * kq], buf, r * 4 * STG, gsub, gsub8, par, budget));
            if (lane == 0) mbar_arrive(BAR(B_HFREE + kq / 2) + 16 * g);
            STAMPD(30 + kq);
            if (LA0 == LA1 || !g) ld(IC<kq + LA0>{}, false);
            else ld(IC<kq + LA1>{}, true);
            wg_fence();
            sfor<7>([&](auto I) { wgmma_rs_n128<kq * STG + koff(I, 1024)>(acc, A[7 * kq + I], d128, kq + I != 0); });
            wg_commit();
          });
          WAIT(wb, 1);
          sfor<4>([&](auto Q) { sqs(Q); });
          rs0 = 0.5f * rsqf(rs0 * (1.f / DM) + 1e-5f);
          rs1 = 0.5f * rsqf(rs1 * (1.f / DM) + 1e-5f);
          wg_wait<1>();
          if (lane < 3) mbar_arrive(BAR(B_EMPTY + lane));
        } else {
          const uint64_t dc = d128 + half * (STG >> 4);
          if (GGATE && c == 1) WAIT(BAR(B_HFREE + 1 + GGATE), 0);
          sfor<4>([&](auto KQ) {
            constexpr int kq = KQ;
            WAIT(BAR(B_FULL + kq) + 8 * half, c >> 1);
            STAMPD(30 + 4 * c + kq);
            wg_fence();
            sfor<7>([&](auto I) { wgmma_rs_n128<kq * STG + koff(I, 1024)>(acc, A[7 * kq + I], dc, kq + I != 0); });
            wg_commit();
            if (kq > 0) {
              wg_wait<1>();
              if (lane == 0) mbar_arrive(BAR(B_EMPTY + kq - 1) + 8 * half);
            }
          });
        }
        wg_wait<0>();
        acc_fence(acc);
        if (lane == 0) mbar_arrive(BAR(B_EMPTY + 3) + 8 * half);
        STAMPD(17 + c);
        constexpr int GO = SWAP ? 32 : 0, UO = SWAP ? 0 : 32;
        own[0] = own[4];
#pragma unroll
        for (int i = 0; i < 4; i++) {
          uint32_t w[4];
#pragma unroll
          for (int t = 0; t < 2; t++) {
            const int b = 8 * i + 4 * t;
            w[2 * t] = pack2(GLU(acc[GO + b], acc[UO + b], rs0), GLU(acc[GO + b + 1], acc[UO + b + 1], rs0));
            w[2 * t + 1] = pack2(GLU(acc[GO + b + 2], acc[UO + b + 2], rs1), GLU(acc[GO + b + 3], acc[UO + b + 3], rs1));
          }
          if (i == 3 && c == 1) hdst += STG - 3584;
          own[i + 1] = make_uint4(tag(w[0], par), w[1], w[2], w[3]);
          st_rlx4(hdst + i * 512, own[i + 1].x, w[1], w[2], w[3]);
        }
        hdst += 2048;
        if (c == 1 && lane == 0) red_inc(&g_cnt[C_ROW + r * 32 + 4 + 2 * (p & 6) + g]);
      }
      float acct[32];
      sfor<2>([&](auto H) {
        constexpr int h = H;
        WAIT(BAR(B_FULL + 4 + h), 1);
        wg_fence();
        sfor<14>([&](auto I) { wgmma_rs_n64<(4 + h) * STG + I / 7 * (TILE / 2) + koff(I % 7, 512)>(acct, A[14 * h + I], d64, h + I != 0); });
        wg_commit();
      });
      wg_wait<1>();
      if (lane == 0) mbar_arrive(BAR(B_EMPTY + 4));
      wg_wait<0>();
      acc_fence(acct);
      if (lane == 0) mbar_arrive(BAR(B_EMPTY + 5));
      STAMP(20);
      constexpr int GO = SWAP ? 16 : 0, UO = SWAP ? 0 : 16;
#pragma unroll
      for (int i = 0; i < 2; i++) {
        uint32_t w[4];
#pragma unroll
        for (int t = 0; t < 2; t++) {
          const int b = 8 * i + 4 * t;
          w[2 * t] = pack2(GLU(acct[GO + b], acct[UO + b], rs0), GLU(acct[GO + b + 1], acct[UO + b + 1], rs0));
          w[2 * t + 1] = pack2(GLU(acct[GO + b + 2], acct[UO + b + 2], rs1), GLU(acct[GO + b + 3], acct[UO + b + 3], rs1));
        }
        st_rlx4(hdst + i * 512, tag(w[0], par), w[1], w[2], w[3]);
        A[5 + i] = make_uint4(w[0], w[1], w[2], w[3]);
      }
#pragma unroll
      for (int i = 0; i < 5; i++) A[i] = own[i];
    }
    STAMP(21);
    {
      const char* const hnb = hdst + (1 - 2 * kh) * 2 * STG;
      auto send = [&](float (&acc)[28], int x) {
        acc_fence(acc);
        char* const pd = buf + (A_PS + ((cta ^ 2 * x) * 6 + 3 * g + x - 1) * 7168 + (warp & 3) * 1792);
        uint32_t P[14];
#pragma unroll
        for (int j = 0; j < 14; j++) P[j] = pack2(acc[2 * j], acc[2 * j + 1]);
        publish7(pd + (uint32_t)(lane * 16), pd + 1536 + (uint32_t)(lane * 8), P, par);
        if (x < 3 && lane == 0) red_inc(&g_cnt[C_PS + (cta ^ 2 * x) * 8 + g]);
      };
      sfor<4>([&](auto K) {
        constexpr int k = K;
        if (k > 1) {
          wg_wait<1>();
          if (lane == 0) mbar_arrive(BAR(B_EMPTY + k - 2));
        }
        if (k) RETRY(16 + k + 4 * g, fix7<-2560 - (k < 3) * STG>(&A[7 * k], k > 1 ? hnb : hdst, par, budget));
        if (k == 2 && lane < 2) mbar_arrive(BAR(B_HFREE + 1) + 16 * g);
        if (k < 2) {
          WAIT(wb + 8 * k, 0);
#pragma unroll
          for (int i = 0; i < 7; i++) A[7 * k + 7 + i] = lds4(gsub - g * STG + 2 * STG + k * TILE + i * 512);
        }
        if (k == 2) {
#pragma unroll
          for (int i = 0; i < 7; i++) A[21 + i] = ld_rlx4(hnb - 2560 + 512 * i);
        }
        WAIT(BAR(B_FULL + k), 0);
        STAMP(42 + k);
        wg_fence();
        sfor<7>([&](auto I) { wgmma_rs_n56<k * STG + I * 3584>(acc0, A[7 * k + I], d0, k + I != 0); });
        if (k == 3) wg_commit();
        sfor<7>([&](auto I) { wgmma_rs_n56<k * STG + I * 3584 + 896>(acc1, A[7 * k + I], d0, k + I != 0); });
        wg_commit();
      });
      wg_wait<1>();
      send(acc0, 1);
      sfor<4>([&](auto K) {
        constexpr int k = K, s = (k + 4) % 6;
        WAIT(BAR(B_FULL + s), k >= 2);
        STAMP(46 + k);
        wg_fence();
        sfor<7>([&](auto I) { wgmma_rs_n56<s * STG + I * 3584>(acc0, A[7 * k + I], d1, k + I != 0); });
        wg_commit();
        if (k == 0) {
          wg_wait<1>();
          send(acc1, 2);
          const float m0 = __uint_as_float(lds1(sb + OFF_M + warp * 64 + gq * 4)), m1 = __uint_as_float(lds1(sb + OFF_M + warp * 64 + gq * 4 + 32));
#pragma unroll
          for (int i = 0; i < 28; i++) acc1[i] = i & 2 ? -m1 : -m0;
          acc_fence(acc1);
        }
      });
      if (g) bar_arrive<7, 256>();
      wg_wait<0>();
      STAMP(22);
      send(acc0, 3);
      if (!g) bar_sync<7, 256>();
      uint32_t P[3][14];
      const char* const ps = buf + (A_PS + (cta * 6 + 3 * g) * 7168 + (warp & 3) * 1792) + (uint32_t)(lane * 16);
      auto fetch = [&](int x) {
#pragma unroll
        for (int i = 0; i < 3; i++) {
          const uint4 v = ld_rlx4(ps + 7168 * x + 512 * i);
          P[x][4 * i] = v.x; P[x][4 * i + 1] = v.y; P[x][4 * i + 2] = v.z; P[x][4 * i + 3] = v.w;
        }
        const uint2 v = ld_rlx2(ps + 7168 * x + 1536 - lane * 8);
        P[x][12] = v.x; P[x][13] = v.y;
      };
      const uint32_t pss = sb + (6 + g) * STG + (warp & 3) * 1792;
      auto fetchs = [&] {
        WAIT(wb + 24, 0);
#pragma unroll
        for (int x = 0; x < 2; x++) {
          const uint32_t a = pss + TILE + 7168 * x;
#pragma unroll
          for (int i = 0; i < 3; i++) {
            const uint4 v = lds4(a + 512 * i + lane * 16);
            P[x][4 * i] = v.x; P[x][4 * i + 1] = v.y; P[x][4 * i + 2] = v.z; P[x][4 * i + 3] = v.w;
          }
          const uint2 v = lds2(a + 1536 + lane * 8);
          P[x][12] = v.x; P[x][13] = v.y;
        }
      };
      WAIT(BAR(B_FULL + 5), 0);
      wg_fence();
      sfor<28>([&](auto I) {
        if (I == 21) {
          fetchs();
          fetch(2);
          wg_fence();
        }
        wgmma_rs_n56<(I / 7 + 4) % 6 * STG + I % 7 * 3584 + 896>(acc1, A[I], d1, 1);
      });
      wg_commit();
      STAMP(23);
      WAIT(BAR(B_FULL + 5), 0);
      auto check = [&](int x) {
#pragma unroll 1
        while (stale(xor2(P[x][0], P[x][4], par) | xor2(P[x][8], P[x][12], par), budget)) fetch(x);
      };
      uint32_t ob = pss + 7168 + (lane & 15) * 112 + (lane & 16);
      uint32_t eye = tq == gq >> 1 ? 0x3F80u << (16 * (gq & 1)) : 0;
      char* op = out + (uint32_t)((128 * r + (tid >> 5) * 16 + (lane >> 3)) * 896 + 112 * p + (lane & 7) * 16);
      uint32_t ia = pss + 7168 + (lane >> 3) * 112 + (lane & 7) * 16;
      asm volatile("" : "+r"(ob), "+r"(eye), "+l"(op), "+r"(ia));
      auto add = [&](const uint32_t (&v)[14]) {
#pragma unroll
        for (int j = 0; j < 7; j++)
          asm("mma.sync.aligned.m16n8k8.row.col.f32.bf16.bf16.f32 {%0,%1,%2,%3}, {%4,%5}, {%6}, {%0,%1,%2,%3};"
              : "+f"(acc1[4 * j]), "+f"(acc1[4 * j + 1]), "+f"(acc1[4 * j + 2]), "+f"(acc1[4 * j + 3]) : "r"(v[2 * j]), "r"(v[2 * j + 1]), "r"(eye));
      };
      check(0);
      check(1);
      wg_wait<0>();
      acc_fence(acc1);
      STAMP(24);
      add(R);
      add(P[0]);
      add(P[1]);
      acc_fence(acc1);
      WAIT(BAR(B_FULL + 5), 0);
      check(2);
      STAMP(57);
      add(P[2]);
      uint32_t o[14];
#pragma unroll
      for (int j = 0; j < 14; j++) o[j] = pack2(acc1[2 * j], acc1[2 * j + 1]);
#pragma unroll
      for (int i = 0; i < 3; i++)
        asm volatile("stmatrix.sync.aligned.m8n8.x4.shared.b16 [%0], {%1,%2,%3,%4};" ::"r"(ob + 32 * i), "r"(o[4 * i]), "r"(o[4 * i + 1]), "r"(o[4 * i + 2]), "r"(o[4 * i + 3]) : "memory");
      asm volatile("stmatrix.sync.aligned.m8n8.x2.shared.b16 [%0], {%1,%2};" ::"r"(ob + 96), "r"(o[12]), "r"(o[13]) : "memory");
      __syncwarp();
      {
        uint4 v[4];
#pragma unroll
        for (int i = 0; i < 4; i++) v[i] = lds4(ia + 448 * i);
        if ((lane & 7) < 7) {
#pragma unroll
          for (int i = 0; i < 4; i++) *(uint4*)(op + 3584 * i) = v[i];
        }
      }
      STAMP(25);
      SPINS(24 + g);
      GTIME(1);
    }
  } else {
    {
      const uint32_t c = 0x100000 - (tid < 256 + B_KVB ? 1 : tid < 256 + B_KFREE ? 4 : tid == 256 + B_XFREE ? 12 : 8);
      if (tid < 320) sts2(BAR(tid - 256), c << 1, c << 11);
      fence_async_smem();
      bar_arrive<0, 384>();
      bar_sync<2, 128>();
#pragma unroll
      for (int i = warp - 8; i < warp; i += 4) {
        if (elect()) {
          mbar_expect_tx(BAR(B_XB + i), TILE);
          tma3d(sb + OFF_X + i * TILE, &map_x, 0, 128 * r + 16 * i, 0, BAR(B_XB + i));
        }
      }
      prefetch_map(&map_qkv);
    }
    STAMPP(60);
    asm volatile("setmaxnreg.dec.sync.aligned.u32 56;");
    STAMPP(63);
    if (warp == 11) {
#pragma unroll 1
      for (int j = 0; j < 8; j++) {
        if (elect()) {
          mbar_expect_tx(BAR(B_K + j), TILE);
          tma2d(sb + (j ^ 4) * TILE, &map_qkv, wcol + DM + DM * (j >> 2), 112 * (j & 3), BAR(B_K + j));
        }
      }
    }
    STAMPP(59);
    const int w = warp - 8, t = tid - 256;
    STAMPP(61);
    char* const kvr = buf + (A_KVR + p * KVR_B);
    if (t < 34) st_rlx4(kvr + (uint32_t)((r * 34 + t) * 16), 0, 0, 0, (t & 1) || ((r & 3) * 34 + t >> 3) == 8 ? 0xC1800000u : 0u);
    const uint32_t e1 = EPC ? (ld_rlx1(&g_cnt[C_ROW + r * 32]) >> 5) + 1 : ld_rlx1(&g_epoch[cta * 32]) + 1;
    const char* wrow = wo + (min(cta, 111) * 4 + w) * (DM * 2) + lane * 16;
    const uint4 u0 = ldg4(wrow);
    uint4 u1 = make_uint4(0, 0, 0, 0);
    if (lane < 24) u1 = ldg4(wrow + 512);
    if (lane < 7) asm volatile("prefetch.global.L2 [%0];" ::"l"(wq + (min(cta, 111) * 4 + w) * (DM * 6) + lane * 128));
    GTIME(0);
    const uint32_t par = e1 & 1;
    STAMPP(62);
    {
      float c[4];
      mma16816z(c, u0, 0x3F803F80u, 0x3F803F80u);
      mma16816(c, u1.x, u1.y, u1.z, u1.w, 0x3F803F80u, 0x3F803F80u);
      float s = c[0] + c[2];
      s += shx(s, 4); s += shx(s, 8); s += shx(s, 16);
      if (lane == 0) st_rlx1(buf + (A_WBAR + cta * 16 + w * 4), pack2(0.f, s * (-1.f / DM)) | par);
    }
    if (smem_u32(smem) != sb) __trap();
    STAMPP(19);
    auto pf = [&](auto T) {
      if (w == PFW && elect()) {
        if (T == 2) prefetch_map(&map_gu);
        if ((PFT & 15) == T) l2_prefetch(wg + cta * 12544, 12544);
        if ((PFT >> 4 & 15) == T) l2_prefetch(wu + cta * 12544, 12544);
        if ((PFT >> 8 & 15) == T) l2_prefetch(wd + cta * 12544, 12544);
        if (T == 2) prefetch_map(&map_gu32);
      }
    };
    uint4 xs[8];
#pragma unroll
    for (int i = 0; i < 8; i++) {
      const int G = 7 * p - kh + (lane & 7), row = (lane >> 3) + 4 * (i & 3);
      if (i % 4 == 0) WAIT(BAR(B_XB + w + (i & 4)), 0);
      xs[i] = lds4(sb + OFF_X + (w + (i & 4)) * TILE + (G >> 3) * 2048 + row * 128 + (((G ^ row) & 7) << 4));
    }
    if (lane == 0) mbar_arrive(BAR(B_XFREE) + (xs[7].x & zero));
    WAIT(BAR(B_XFREE), 0);
    if (w == 0 && elect()) {
      mbar_expect_tx(BAR(B_Q), 2 * STG);
#pragma unroll 1
      for (int j = 0; j < 4; j++) tma2d(sb + OFF_Q + j * TILE, &map_qkv, wcol, 112 * j, BAR(B_Q));
    }
#pragma unroll
    for (int i = 0; i < 4; i++) sts4(sb + OFF_KVB + 2048 * i + t * 16, 0, 0, 0, 0);
#pragma unroll
    for (int i = 0; i < 8; i++) {
      const int row = (lane >> 3) + 4 * (i & 3);
      sts4(sb + OFF_XS + (w + (i & 4)) * 2048 + row * 128 + (((lane ^ row) & 7) << 4), xs[i].x, xs[i].y, xs[i].z, xs[i].w);
    }
    pf(IC<0>{});
    if ((PFT & 15) == 1 && w == PFW) { WAIT(BAR(B_V + PFV), 0); pf(IC<1>{}); }
    const char* const kvt = kvr + (uint32_t)(w * 2176 + (lane & 28) * 16 + (t & 1) * 32 + (t & 2) * 8);
    const char* const kvz = kvr + (uint32_t)(w * 2176 + 1024 + (lane & 28) * 4);
    const char* const kvh = kvt + (uint32_t)(1152 + (lane & 28) * 16);
    {
      uint32_t c[3];
      auto counts = [&] {
#pragma unroll
        for (int i = 0; i < 2; i++) c[i] = ld_rlx1(kvr + (uint32_t)(t * 32) + 4096 * i + 28);
        c[2] = ld_rlx1(kvr + (uint32_t)((t & 15) * 32) + 8192 + 28);
      };
      counts();
      if (w == 0) {
        WAIT(BAR(B_KFREE), 0);
        if (elect()) {
          mbar_expect_tx(BAR(B_WO), 2 * STG);
          tma2d(sb + OFF_WO, &map_wo, wcol, 0, BAR(B_WO));
          tma2d(sb + OFF_WO + STG, &map_wo, wcol, 224, BAR(B_WO));
        }
      }
#pragma unroll 1
      while (stale(~(c[0] & c[1] & c[2]), budget, 0x80000000u)) counts();
    }
    if (lane == 0) mbar_arrive(BAR(B_INIT));
    STAMPP(1);
    pf(IC<2>{});
    uint4 m = ld_rlx4(buf + A_WBAR + (uint32_t)(t * 16));
    WAIT(BAR(B_VFREE), 0);
    auto load_w = [&](auto T) {
      sfor<4>([&](auto U) {
        constexpr int u = U;
        if ((WT >> 4 * u & 15) == T && elect()) {
          mbar_expect_tx(BAR(B_FULL + u), STG);
          tma3d(sb + u * STG, &map_gu, 224 * p + 32 * kh + 64 * (u >> 2), 112 * (u & 3), 0, BAR(B_FULL + u));
        }
      });
    };
#define WHAS(T) ((WT & 15) == T || (WT >> 4 & 15) == T || (WT >> 8 & 15) == T || (WT >> 12 & 15) == T || (WT >> 16 & 15) == T || (WT >> 20 & 15) == T)
    if (w == 0) load_w(IC<0>{});
    {
#pragma unroll 1
      while (stale(xor2(m.x, m.y, par) | xor2(m.z, m.w, par), budget)) m = ld_rlx4(buf + A_WBAR + (uint32_t)(t * 16));
      const uint32_t wa = sb + OFF_WBAR + (t >> 3) * 64 + (t & 1) * 32 + (t & 6) * 2;
      if (t < 112) {
        sts1(wa, __byte_perm(m.x, m.y, 0x7632));
        sts1(wa + 16, __byte_perm(m.z, m.w, 0x7632));
      }
      STAMPP(6);
    }
    bar_sync<2, 128>();
    const int gq = lane >> 2, tq = lane & 3, k = 28 * (w >> 1) + 16 * (w & 1) + gq;
    const uint32_t row = sb + OFF_KVB + k * 128, sw = (k & 7) << 4;
    uint32_t ad[4];
#pragma unroll
    for (int q = 0; q < 4; q++) {
      const int c = 28 * (w >> 1) + 2 * tq + 8 * q;
      ad[q] = row + (2 * (c < 32 ? (c & 6) * 4 + (c >> 3) * 2 : c < 48 ? 32 + (c & 2) * 4 + (c >> 1 & 6) : c) ^ sw);
      asm volatile("" : "+r"(ad[q]));
    }
    const bool lo = !(w & 1) || gq < 4;
    uint32_t m1 = tq & 2 ? ~0u : 0, m2 = lo ? m1 : 0;
    asm volatile("" : "+r"(m1), "+r"(m2));
    if (WHAS(1) && w == 0) { WAIT(BAR(B_QFREE), 0); load_w(IC<1>{}); }
    eq_wait(kvr + w * 2176 + KVP + 28, KVTHR, budget);
    STAMPX(2);
    {
      uint4 v[5];
#pragma unroll 1
      do {
#pragma unroll
        for (int i = 0; i < 4; i++) v[i] = ld_rlx4(i < 2 ? kvt + 512 * i : kvh + 64 * i - 128);
        v[4] = ld_rlx4(kvz);
      } while (stale(or3((v[0].w | v[1].w) & m1, (v[2].w | v[3].w) & m2, v[4].w), budget, ~0u));
      STAMPX(3);
#define F(x) __uint_as_float(x)
      const uint32_t a[4] = {pack2(F(v[0].x), F(v[0].y)), pack2(F(v[0].z), F(m1 ? v[1].z : v[0].w)), pack2(F(v[1].x), F(v[1].y)), pack2(F(v[1].z), F(v[1].w))};
      const uint32_t b[4] = {pack2(F(v[2].x), F(v[2].y)), pack2(F(v[2].z), F(m1 ? v[3].z : v[2].w)), pack2(F(v[3].x), F(v[3].y)), pack2(F(v[3].z), F(v[3].w))};
#pragma unroll
      for (int q = 0; q < 4; q++) {
        if (q < 3 || tq < 2) {
          sts1(ad[q], a[q]);
          if (lo) sts1(ad[q] + 1024, b[q]);
        }
      }
      if (tq == 2) {
        const uint32_t z = pack2(F(v[4].x), F(v[4].y));
        const uint32_t za = __byte_perm(z, 0, w & 2 ? 0x1044 : 0x4410), zb = __byte_perm(z, 0, w & 2 ? 0x3244 : 0x4432);
        sts4(row + (112 ^ sw), za, za, za, za);
        if (lo) sts4(row + 1024 + (112 ^ sw), zb, zb, zb, zb);
      }
      fence_async_smem();
      __syncwarp();
      if (lane == 0) mbar_arrive(BAR(B_KVB));
      STAMPP(4);
      pf(IC<3>{});
    }
    if (w == 0) {
      load_w(IC<2>{});
      WAIT(BAR(B_WOFREE), 0);
      load_w(IC<3>{});
      if (WHAS(4)) { WAIT(BAR(B_WB + 3), 0); load_w(IC<4>{}); }
      if (WHAS(5)) { WAIT(BAR(B_WB + 7), 0); load_w(IC<5>{}); }
      if (W4G < 4) { WAIT(BAR(B_HFREE), 0); WAIT(BAR(B_WB + 4 + W4G), 1); }
#pragma unroll 1
      for (int u = 4; u < 22; u++) {
        const int s = u < 14 ? u & 7 : u < 20 ? u - 14 : u - 20;
        if (u == 14) WAIT(BAR(B_WDOK), 0);
        WAIT(BAR(B_KFREE + s) + (u >= 8 ? 64 : 0), u >= 14 && u < 20);
        STAMPP(20 + u);
        if (elect()) {
          mbar_expect_tx(BAR(B_FULL + s), u < 14 ? STG : WDS);
          if (u < 12) tma3d(sb + s * STG, &map_gu, 224 * p + 32 * kh + 64 * (u >> 2), 112 * (u & 3), 0, BAR(B_FULL + s));
          else if (u < 14) tma3d(sb + s * STG, &map_gu32, 224 * p + 192 - 192 * kh, 224 * (u - 12), 0, BAR(B_FULL + s));
          else bulk_g2s(sb + s * STG, buf + (A_WD + (p * 8 + u - 14) * WDS), WDS, BAR(B_FULL + s));
        }
      }
      SPINS(26);
    } else {
#pragma unroll 1
      for (int j = 0; j < (w == 1 ? 4 : 0); j++) {
        const char* src = buf + (A_O + (j >> 1) * FRAG_B + (r * 2 + (j & 1)) * 2 * STG);
        const uint32_t full = BAR(B_WB + 4 * (j & 1));
        WAIT(BAR(j < 2 ? B_QFREE - j : B_ORD - 2 + j), 0);
        cnt_wait(&g_cnt[C_ROW + r * 32 + j], e1 * 32, budget);
        if (B6 && j == 2) bar_arrive<6, 160>();
        STAMPX(50 + 2 * j);
#pragma unroll
        for (int q = 0; q < 4; q++) {
          if (elect()) {
            mbar_expect_tx(full + 8 * q, TILE);
            bulk_g2s(sb + OFF_G + (j & 1) * 2 * STG + q * TILE, src + q * TILE, TILE, full + 8 * q);
          }
          if (RPK >= 4 && q == RPK % 4 && j == RPK / 4 && lane < 8) mbar_arrive(BAR(B_RPK));
        }
        STAMPP(51 + 2 * j);
      }
      if (w == 1) { SPINS(27); return; }
      const int g = w - 2;
      if ((PFT >> 8) == 4) { WAIT(BAR(B_WB + 3), 0); pf(IC<4>{}); }
      WAIT(BAR(RPK < 4 ? B_HFREE + RPK : B_RPK), 0);
      if (t < 120) {
        const int src = p ^ (r >> 2 & 1), part = (r & 1) + (~(r ^ r >> 1) & 2);
        char* zp = buf + (uint32_t)(A_WD + (p * 16 + r) * (WDS / 2) + t * 16 - 1024);
#pragma unroll 1
        for (int x = 1 + (r >> 2 & 2);; x++, zp += 896) {
          const char* wp = wd + (uint32_t)((224 * src + 32 * (src & 1) + 56 * part + (t & 7)) * 896 + (p ^ 2 * x & 7) * 112 + (t & 56) * 2);
          uint4 z[7];
#pragma unroll
          for (int i = 0; i < 7; i++) {
            if (i == 3 && part + (src & 1) == 4) wp -= 224 * 896;
            z[i] = ldg4(wp + i * 8 * 896);
          }
#pragma unroll
          for (int i = 0; i < 7; i++) st_rlx4(zp + i * 1792, z[i].x, z[i].y, z[i].z, z[i].w);
          if (!(x & 1)) break;
        }
      }
      STAMPP(5);
      asm volatile("fence.proxy.async.global;" ::: "memory");
      __syncwarp();
      if (lane == 0) asm volatile("red.release.gpu.global.add.u32 [%0], 1;" ::"l"(&g_cnt[C_WD + p * 32]) : "memory");
      STAMPP(7);
      cnt_wait<true>(&g_cnt[C_WD + p * 32], e1 * 32, budget);
      STAMPP(18);
      asm volatile("fence.proxy.async.global;" ::: "memory");
      if (lane < 2) mbar_arrive(BAR(B_WDOK));
#pragma unroll 1
      for (int j = 0; j < 4; j += j + 1) {
        const uint32_t bar = BAR(B_WB + 4 * g + j);
        const char* src = buf + (j < 3 ? A_HH + (cta ^ j) * 2 * STG + g * TILE : A_PS + (cta * 6 + 3 * g) * 7168);
        if (j != 1) cnt_wait(&g_cnt[(j < 3 ? C_ROW + r * 32 + 4 + 2 * (p & 6) : C_PS + cta * 8) + g], e1 * 8, budget);
        WAIT(j >= 2 ? BAR(B_HFREE + 2 * g + 1) : BAR(B_EMPTY + 6 + g), j >> 1);
        if (elect()) {
          mbar_expect_tx(bar, TILE);
          bulk_g2s(sb + (6 + g) * STG + (j & 1) * TILE, src, TILE, bar);
        }
      }
      SPINS(28 + g);
      if (!EPC && g) st_rlx1(&g_epoch[cta * 32], e1);
      if (g && lane == 0) DUMP(2);
    }
  }
}

typedef CUresult (*EncodeFn)(CUtensorMap*, CUtensorMapDataType, cuuint32_t, void*, const cuuint64_t*, const cuuint64_t*,
                             const cuuint32_t*, const cuuint32_t*, CUtensorMapInterleave, CUtensorMapSwizzle,
                             CUtensorMapL2promotion, CUtensorMapFloatOOBfill);

void make_map(EncodeFn enc, CUtensorMap* m, const void* p, int rank, const cuuint64_t* gd, const cuuint64_t* gs,
              const cuuint32_t* bd, CUtensorMapSwizzle sw) {
  const cuuint32_t es[5] = {1, 1, 1, 1, 1};
  ENC_CHECK(enc(m, CU_TENSOR_MAP_DATA_TYPE_BFLOAT16, rank, (void*)p, gd, gs, bd, es, CU_TENSOR_MAP_INTERLEAVE_NONE, sw,
                CU_TENSOR_MAP_L2_PROMOTION_NONE, CU_TENSOR_MAP_FLOAT_OOB_FILL_NONE));
}

}

extern "C" void kernel_launch(void* const* d_in, const int* in_sizes, int n_in, void* d_out, int out_size) {
  (void)in_sizes; (void)n_in; (void)out_size;
  static EncodeFn enc = nullptr;
  static char* buf = nullptr;
  if (!enc) {
    void* fn = nullptr;
    cudaDriverEntryPointQueryResult qr;
    cudaGetDriverEntryPoint("cuTensorMapEncodeTiled", &fn, cudaEnableDefault, &qr);
    enc = (EncodeFn)fn;
    cudaGetSymbolAddress((void**)&buf, g_buf);
    cudaFuncSetAttribute(fused_block_kernel<false>, cudaFuncAttributeMaxDynamicSharedMemorySize, SMEM_TOTAL);
    cudaFuncSetAttribute(fused_block_kernel<true>, cudaFuncAttributeMaxDynamicSharedMemorySize, SMEM_TOTAL);
  }
  const CUtensorMapSwizzle S128 = CU_TENSOR_MAP_SWIZZLE_128B;
  CUtensorMap mx, mqkv, mwor, mgu, mgu32;
  {
    cuuint64_t gd[3] = {64, SEQ, 7}, gs[2] = {DM * 2, 128};
    cuuint32_t bd[3] = {64, 16, 7};
    make_map(enc, &mx, d_in[0], 3, gd, gs, bd, S128);
  }
  {
    cuuint64_t gd[2] = {3 * DM, DM}, gs[1] = {3 * DM * 2};
    cuuint32_t bd[2] = {64, 112};
    make_map(enc, &mqkv, d_in[1], 2, gd, gs, bd, S128);
  }
  {
    cuuint64_t gd[2] = {DM, DM}, gs[1] = {DM * 2};
    cuuint32_t bd[2] = {64, 224};
    make_map(enc, &mwor, d_in[2], 2, gd, gs, bd, S128);
  }
  const char *wg = (const char*)d_in[4], *wu = (const char*)d_in[5];
  const bool swap = wu < wg;
  const char* gub = swap ? wu : wg;
  const cuuint64_t gud = swap ? (cuuint64_t)(wg - wu) : (cuuint64_t)(wu - wg);
  {
    cuuint64_t gd[3] = {FF, DM, 2}, gs[2] = {FF * 2, gud};
    cuuint32_t bd[3] = {64, 112, 2};
    make_map(enc, &mgu, gub, 3, gd, gs, bd, S128);
  }
  {
    cuuint64_t gd[3] = {FF, DM, 2}, gs[2] = {FF * 2, gud};
    cuuint32_t bd[3] = {32, 224, 2};
    make_map(enc, &mgu32, gub, 3, gd, gs, bd, CU_TENSOR_MAP_SWIZZLE_64B);
  }
  (swap ? fused_block_kernel<true> : fused_block_kernel<false>)<<<128, 384, SMEM_TOTAL>>>(
      buf, (const char*)d_in[2], mn_desc(sb), mn_desc64(sb), mn_desc0(sb), mn_desc(sb + OFF_Q), mn_desc0(sb), k_desc0(sb), wg, wu, (const char*)d_in[6], (const char*)d_in[1], (char*)d_out, mx, mqkv, mwor, mgu, mgu32);
}
```

```cpp
#include <cuda_runtime.h>
#include <cuda_bf16.h>
#include <cuda.h>
#include <stdint.h>
#include <stdio.h>
#include <utility>

#define SPIN_LIMIT (1 << 18)

namespace {

constexpr uint32_t sb = 1024;
constexpr int SEQ = 2048, DM = 448, FF = 1792;
constexpr int TILE = 14336;
constexpr int STG = 2 * TILE;
constexpr int SMEM_BAR = 8 * STG;
constexpr int SMEM_TOTAL = SMEM_BAR + 3072;
constexpr int OFF_X = 4 * STG, OFF_Q = 4 * STG, OFF_WO = 2 * STG, OFF_G = 4 * STG, OFF_PK = 6 * STG, OFF_KVB = OFF_PK + 32768, OFF_XS = OFF_KVB + 8192,
              OFF_M = SMEM_BAR + 512, OFF_WBAR = SMEM_BAR + 2048, OFF_POLL = SMEM_BAR + 2944;
constexpr int B_XB = 0  , B_K = 8  , B_V = 12  , B_Q = 16, B_WO = 17, B_FULL = 18  , B_WB = 26  ,
              B_KVB = 34, B_WDOK = 35, B_INIT = 36,
              B_KFREE = 37, B_OFREE = 38, B_QFREE = 39  , B_HFREE = 41  , B_EMPTY = 45  , B_XFREE = 53, B_VFREE = 54,
              B_ORD = 55  , B_WOFREE = 59, B_RPK = 60;

constexpr int KVR_B = 8704;
constexpr int FRAG_B = 16 * 4 * STG;
constexpr int A_CNT = 0, A_EPOCH = 8192, A_KVR = A_EPOCH + 16384, A_WBAR = A_KVR + 8 * KVR_B, A_O = A_WBAR + 2048, A_H = A_O + FRAG_B,
              A_HH = A_H + FRAG_B;
constexpr int HH_B = 128 * 2 * STG;
constexpr int A_PS = A_HH + HH_B;
constexpr int WDS = 25088;
constexpr int A_WD = A_PS + 128 * 3 * TILE;

__device__ uint4 g_buf[(A_WD + 64 * WDS) / 16];
#define g_epoch ((unsigned*)buf + A_EPOCH / 4)
constexpr int C_ROW = 0, C_WD = 512, C_PS = 1024;
#define g_cnt ((unsigned*)buf + A_CNT / 4)
#define ENC_CHECK(x) (void)(x)
#define STAMP(i)
#define STAMPX(i)
#define GTIME(i)
#define STAMPP(i)
#define STAMPD(i)
#define DUMP(row)

__device__ __forceinline__ uint32_t smem_u32(const void* p) { return (uint32_t)__cvta_generic_to_shared(p); }
__device__ __forceinline__ void mbar_init(uint32_t bar, uint32_t cnt) {
  asm volatile("mbarrier.init.shared::cta.b64 [%0], %1;" ::"r"(bar), "r"(cnt) : "memory");
}
__device__ __forceinline__ void mbar_expect_tx(uint32_t bar, uint32_t bytes) {
  asm volatile("mbarrier.arrive.expect_tx.shared::cta.b64 _, [%0], %1;" ::"r"(bar), "r"(bytes) : "memory");
}
__device__ __forceinline__ void mbar_arrive(uint32_t bar) {
  asm volatile("mbarrier.arrive.shared::cta.b64 _, [%0];" ::"r"(bar) : "memory");
}
__device__ __forceinline__ void mbar_wait(uint32_t bar, uint32_t parity, int& budget) {
  asm volatile("{\n.reg .pred p;\nW:\nmbarrier.try_wait.parity.shared::cta.b64 p, [%1], %2;\n"
               "add.s32 %0, %0, -1;\nsetp.gt.and.s32 p, %0, 0, !p;\n@p bra W;\n}"
               : "+r"(budget) : "r"(bar), "r"(parity) : "memory");
}
__device__ __forceinline__ bool elect() {
  uint32_t v;
  asm volatile("{\n.reg .pred p;\nelect.sync _|p, 0xffffffff;\nselp.u32 %0, 1, 0, p;\n}" : "=r"(v));
  return v;
}
__device__ __forceinline__ void tma2d(uint32_t dst, const CUtensorMap* m, int c0, int c1, uint32_t bar) {
  asm volatile("cp.async.bulk.tensor.2d.shared::cluster.global.mbarrier::complete_tx::bytes [%0], [%1, {%3, %4}], [%2];"
               ::"r"(dst), "l"(m), "r"(bar), "r"(c0), "r"(c1) : "memory");
}
__device__ __forceinline__ void tma3d(uint32_t dst, const CUtensorMap* m, int c0, int c1, int c2, uint32_t bar) {
  asm volatile("cp.async.bulk.tensor.3d.shared::cluster.global.mbarrier::complete_tx::bytes [%0], [%1, {%3, %4, %5}], [%2];"
               ::"r"(dst), "l"(m), "r"(bar), "r"(c0), "r"(c1), "r"(c2) : "memory");
}
__device__ __forceinline__ void bulk_g2s(uint32_t dst, const void* src, uint32_t bytes, uint32_t bar) {
  asm volatile("cp.async.bulk.shared::cluster.global.mbarrier::complete_tx::bytes [%0], [%1], %2, [%3];"
               ::"r"(dst), "l"(src), "r"(bytes), "r"(bar) : "memory");
}
__device__ __forceinline__ void l2_prefetch(const void* p, uint32_t bytes) {
  asm volatile("cp.async.bulk.prefetch.L2.global [%0], %1;" ::"l"(p), "r"(bytes) : "memory");
}
__device__ __forceinline__ void prefetch_map(const CUtensorMap* m) {
  asm volatile("prefetch.tensormap [%0];" ::"l"(m) : "memory");
}
__device__ __forceinline__ void fence_async_smem() { asm volatile("fence.proxy.async.shared::cta;" ::: "memory"); }
template <int ID, int N> __device__ __forceinline__ void bar_arrive() { asm volatile("bar.arrive %0, %1;" ::"n"(ID), "n"(N) : "memory"); }
__device__ __forceinline__ void bar_arrive_id(int id) { asm volatile("bar.arrive %0, 256;" ::"r"(id) : "memory"); }
__device__ __forceinline__ void bar_sync_wg(int id) { asm volatile("bar.sync %0, 128;" ::"r"(id) : "memory"); }
template <int ID, int N> __device__ __forceinline__ void bar_sync() { asm volatile("bar.sync %0, %1;" ::"n"(ID), "n"(N) : "memory"); }
__device__ __forceinline__ void wg_fence() { asm volatile("wgmma.fence.sync.aligned;" ::: "memory"); }
__device__ __forceinline__ void wg_commit() { asm volatile("wgmma.commit_group.sync.aligned;" ::: "memory"); }
template <int N> __device__ __forceinline__ void wg_wait() { asm volatile("wgmma.wait_group.sync.aligned %0;" ::"n"(N) : "memory"); }
template <int N> __device__ __forceinline__ void acc_fence(float (&d)[N]) {
#pragma unroll
  for (int i = 0; i < N; i++) asm volatile("" : "+f"(d[i])::"memory");
}
constexpr uint64_t mn_desc(uint32_t addr) {
  return (uint64_t)((addr & 0x3FFFF) >> 4) | ((uint64_t)(TILE >> 4) << 16) | ((uint64_t)64 << 32) | ((uint64_t)1 << 62);
}
constexpr uint64_t mn_desc64(uint32_t addr) {
  return (uint64_t)((addr & 0x3FFFF) >> 4) | ((uint64_t)(TILE >> 4) << 16) | ((uint64_t)32 << 32) | ((uint64_t)2 << 62);
}
constexpr uint64_t mn_desc0(uint32_t addr) {
  return (uint64_t)((addr & 0x3FFFF) >> 4) | ((uint64_t)(1792 >> 4) << 16) | ((uint64_t)8 << 32);
}
constexpr uint64_t k_desc0(uint32_t addr) {
  return (uint64_t)((addr & 0x3FFFF) >> 4) | ((uint64_t)8 << 16) | ((uint64_t)(1792 >> 4) << 32);
}
__device__ __forceinline__ uint4 ld_rlx4(const void* p) {
  uint4 v;
  asm volatile("ld.relaxed.gpu.global.v4.u32 {%0,%1,%2,%3}, [%4];" : "=r"(v.x), "=r"(v.y), "=r"(v.z), "=r"(v.w) : "l"(p) : "memory");
  return v;
}
__device__ __forceinline__ uint2 ld_rlx2(const void* p) {
  uint2 v;
  asm volatile("ld.relaxed.gpu.global.v2.u32 {%0,%1}, [%2];" : "=r"(v.x), "=r"(v.y) : "l"(p) : "memory");
  return v;
}
__device__ __forceinline__ uint32_t ld_rlx1(const void* p) {
  uint32_t v;
  asm volatile("ld.relaxed.gpu.global.u32 %0, [%1];" : "=r"(v) : "l"(p) : "memory");
  return v;
}
__device__ __forceinline__ void st_rlx4(void* p, uint32_t a, uint32_t b, uint32_t c, uint32_t d) {
  asm volatile("st.relaxed.gpu.global.v4.u32 [%0], {%1,%2,%3,%4};" ::"l"(p), "r"(a), "r"(b), "r"(c), "r"(d) : "memory");
}
__device__ __forceinline__ void st_rlx2(void* p, uint32_t a, uint32_t b) {
  asm volatile("st.relaxed.gpu.global.v2.u32 [%0], {%1,%2};" ::"l"(p), "r"(a), "r"(b) : "memory");
}
__device__ __forceinline__ void st_rlx1(void* p, uint32_t a) {
  asm volatile("st.relaxed.gpu.global.u32 [%0], %1;" ::"l"(p), "r"(a) : "memory");
}
__device__ __forceinline__ void red_inc(unsigned* p) {
  asm volatile("red.relaxed.gpu.global.inc.u32 [%0], 0xfffffffe;" ::"l"(p) : "memory");
}
__device__ __forceinline__ void red_add4(void* p, float a, float b, float c, float d) {
  asm volatile("red.relaxed.gpu.global.add.v4.f32 [%0], {%1,%2,%3,%4};" ::"l"(p), "f"(a), "f"(b), "f"(c), "f"(d) : "memory");
}
__device__ __forceinline__ void eq_wait(const void* p, uint32_t target, int& budget) {
  asm volatile("{\n.reg .pred p;\n.reg .b32 v;\nW:\nld.relaxed.gpu.global.b32 v, [%1];\nadd.s32 %0, %0, -1;\n"
               "setp.gt.s32 p, %0, 0;\nsetp.gt.and.u32 p, v, %2, p;\n@p bra W;\n}"
               : "+r"(budget) : "l"(p), "r"(target) : "memory");
}
template <bool ACQ = false>
__device__ __forceinline__ void cnt_wait(const unsigned* p, uint32_t target, int& budget) {
  if (ACQ)
    asm volatile("{\n.reg .pred p;\n.reg .s32 v;\nW:\nld.acquire.gpu.global.s32 v, [%1];\nadd.s32 %0, %0, -1;\n"
                 "setp.gt.s32 p, %0, 0;\nsub.s32 v, v, %2;\nsetp.lt.and.s32 p, v, 0, p;\n@p bra W;\n}"
                 : "+r"(budget) : "l"(p), "r"(target) : "memory");
  else
  asm volatile("{\n.reg .pred p;\n.reg .s32 v;\nW:\nld.relaxed.gpu.global.s32 v, [%1];\nadd.s32 %0, %0, -1;\n"
               "setp.gt.s32 p, %0, 0;\nsub.s32 v, v, %2;\nsetp.lt.and.s32 p, v, 0, p;\n@p bra W;\n}"
               : "+r"(budget) : "l"(p), "r"(target) : "memory");
}
#define PGAP 1
template <bool EQ = false>
__device__ __forceinline__ void cnt_poll(const void* p, uint32_t s, uint32_t a, uint32_t target, int& budget) {
  asm volatile("{\n.reg .pred p, e;\n.reg .s32 v;\nelect.sync _|e, 0xffffffff;\nW:\n@e cp.async.cg.shared.global [%2], [%1], 16;\n"
               "add.s32 %0, %0, -1;\nsetp.gt.s32 p, %0, 0;\n"
               "ld.volatile.shared.s32 v, [%3];\nsub.s32 v, v, %4;\nsetp.lt.and.s32 p, v, 0, p;\n"
               "@p bra W;\nE:\n}"
               : "+r"(budget) : "l"(p), "r"(s), "r"(a), "r"(target) : "memory");
}
__device__ __forceinline__ uint32_t or3(uint32_t a, uint32_t b, uint32_t c) {
  uint32_t r;
  asm("lop3.b32 %0, %1, %2, %3, 0xfe;" : "=r"(r) : "r"(a), "r"(b), "r"(c));
  return r;
}
__device__ __forceinline__ uint32_t xor2(uint32_t a, uint32_t b, uint32_t f) {
  uint32_t r;
  asm("lop3.b32 %0, %1, %2, %3, 0x7e;" : "=r"(r) : "r"(a), "r"(b), "r"(f));
  return r;
}
__device__ __forceinline__ bool stale(uint32_t bad, int& budget, uint32_t mask = 1) {
  uint32_t v;
  asm volatile("{\n.reg .pred p;\n.reg .b32 t;\nand.b32 t, %2, %3;\nsetp.ne.u32 p, t, 0;\nadd.s32 %1, %1, -1;\n"
               "setp.gt.and.s32 p, %1, 0, p;\nvote.sync.any.pred p, p, 0xffffffff;\nselp.u32 %0, 1, 0, p;\n}"
               : "=r"(v), "+r"(budget) : "r"(bad), "r"(mask));
  return v;
}
__device__ __forceinline__ uint32_t tag(uint32_t w, uint32_t par) {
  uint32_t r;
  asm("lop3.b32 %0, %1, %2, 1, 0xd8;" : "=r"(r) : "r"(w), "r"(par));
  return r;
}
__device__ __forceinline__ void sts1(uint32_t a, uint32_t v) { asm volatile("st.shared.u32 [%0], %1;" ::"r"(a), "r"(v) : "memory"); }
__device__ __forceinline__ void sts2(uint32_t a, uint32_t x, uint32_t y) {
  asm volatile("st.shared.v2.u32 [%0], {%1,%2};" ::"r"(a), "r"(x), "r"(y) : "memory");
}
__device__ __forceinline__ void sts4(uint32_t a, uint32_t x, uint32_t y, uint32_t z, uint32_t w) {
  asm volatile("st.shared.v4.u32 [%0], {%1,%2,%3,%4};" ::"r"(a), "r"(x), "r"(y), "r"(z), "r"(w) : "memory");
}
__device__ __forceinline__ uint32_t lds1(uint32_t a) {
  uint32_t v;
  asm volatile("ld.shared.u32 %0, [%1];" : "=r"(v) : "r"(a) : "memory");
  return v;
}
__device__ __forceinline__ uint2 lds2(uint32_t a) {
  uint2 v;
  asm volatile("ld.shared.v2.u32 {%0,%1}, [%2];" : "=r"(v.x), "=r"(v.y) : "r"(a) : "memory");
  return v;
}
__device__ __forceinline__ uint4 lds4(uint32_t a) {
  uint4 v;
  asm volatile("ld.shared.v4.u32 {%0,%1,%2,%3}, [%4];" : "=r"(v.x), "=r"(v.y), "=r"(v.z), "=r"(v.w) : "r"(a) : "memory");
  return v;
}
__device__ __forceinline__ uint4 ldsm4(uint32_t a) {
  uint4 v;
  asm volatile("ldmatrix.sync.aligned.m8n8.x4.shared.b16 {%0,%1,%2,%3}, [%4];" : "=r"(v.x), "=r"(v.y), "=r"(v.z), "=r"(v.w) : "r"(a) : "memory");
  return v;
}
__device__ __forceinline__ uint4 ldsm4t(uint32_t a) {
  uint4 v;
  asm volatile("ldmatrix.sync.aligned.m8n8.x4.trans.shared.b16 {%0,%1,%2,%3}, [%4];" : "=r"(v.x), "=r"(v.y), "=r"(v.z), "=r"(v.w) : "r"(a) : "memory");
  return v;
}
__device__ __forceinline__ uint32_t pack2(float lo, float hi) {
  uint32_t r;
  asm("cvt.rn.bf16x2.f32 %0, %1, %2;" : "=r"(r) : "f"(hi), "f"(lo));
  return r;
}
__device__ __forceinline__ float bf_lo(uint32_t w) { return __uint_as_float(w << 16); }
__device__ __forceinline__ float bf_hi(uint32_t w) { return __uint_as_float(w & 0xFFFF0000u); }
__device__ __forceinline__ uint32_t sub2(uint32_t a, uint32_t b) {
  uint32_t r;
  asm volatile("sub.rn.bf16x2 %0, %1, %2;" : "=r"(r) : "r"(a), "r"(b));
  return r;
}
__device__ __forceinline__ uint32_t add2(uint32_t a, uint32_t b) {
  uint32_t r;
  asm("add.rn.bf16x2 %0, %1, %2;" : "=r"(r) : "r"(a), "r"(b));
  return r;
}
__device__ __forceinline__ uint32_t fma2(uint32_t a, uint32_t b, uint32_t c) {
  uint32_t r;
  asm("fma.rn.bf16x2 %0, %1, %2, %3;" : "=r"(r) : "r"(a), "r"(b), "r"(c));
  return r;
}
__device__ __forceinline__ uint32_t transp(uint32_t a) {
  uint32_t r;
  asm volatile("movmatrix.sync.aligned.m8n8.trans.b16 %0, %1;" : "=r"(r) : "r"(a));
  return r;
}
__device__ __forceinline__ uint32_t sq2(uint32_t a) {
  uint32_t r;
  asm volatile("mul.rn.bf16x2 %0, %1, %1;" : "=r"(r) : "r"(a));
  return r;
}
__device__ __forceinline__ uint32_t sq2(uint32_t a, uint32_t c) {
  uint32_t r;
  asm volatile("fma.rn.bf16x2 %0, %1, %1, %2;" : "=r"(r) : "r"(a), "r"(c));
  return r;
}
__device__ __forceinline__ uint4 ldg4(const void* p) {
  uint4 v;
  asm volatile("ld.global.nc.v4.u32 {%0,%1,%2,%3}, [%4];" : "=r"(v.x), "=r"(v.y), "=r"(v.z), "=r"(v.w) : "l"(p));
  return v;
}
__device__ __forceinline__ void mma16816(float (&c)[4], uint32_t a0, uint32_t a1, uint32_t a2, uint32_t a3, uint32_t b0, uint32_t b1) {
  asm("mma.sync.aligned.m16n8k16.row.col.f32.bf16.bf16.f32 {%0,%1,%2,%3}, {%4,%5,%6,%7}, {%8,%9}, {%0,%1,%2,%3};"
      : "+f"(c[0]), "+f"(c[1]), "+f"(c[2]), "+f"(c[3]) : "r"(a0), "r"(a1), "r"(a2), "r"(a3), "r"(b0), "r"(b1));
}
__device__ __forceinline__ void mma16816z(float (&c)[4], const uint4& a, uint32_t b0, uint32_t b1) {
  asm("mma.sync.aligned.m16n8k16.row.col.f32.bf16.bf16.f32 {%0,%1,%2,%3}, {%4,%5,%6,%7}, {%8,%9}, {%10,%10,%10,%10};"
      : "=f"(c[0]), "=f"(c[1]), "=f"(c[2]), "=f"(c[3]) : "r"(a.x), "r"(a.y), "r"(a.z), "r"(a.w), "r"(b0), "r"(b1), "f"(0.f));
}
__device__ __forceinline__ float ex2f(float x) { float r; asm("ex2.approx.ftz.f32 %0, %1;" : "=f"(r) : "f"(x)); return r; }
__device__ __forceinline__ float tanhf_(float x) { float r; asm("tanh.approx.f32 %0, %1;" : "=f"(r) : "f"(x)); return r; }
__device__ __forceinline__ float rsqf(float x) { float r; asm("rsqrt.approx.ftz.f32 %0, %1;" : "=f"(r) : "f"(x)); return r; }
__device__ __forceinline__ float lg2f(float x) { float r; asm("lg2.approx.ftz.f32 %0, %1;" : "=f"(r) : "f"(x)); return r; }
__device__ __forceinline__ float rcpf(float x) { float r; asm("rcp.approx.ftz.f32 %0, %1;" : "=f"(r) : "f"(x)); return r; }
__device__ __forceinline__ float phi(float a, const float4& c) {
  return ex2f(fmaf(fminf(a, 0.f), c.x, c.y)) + fmaf(fmaxf(a, 0.f), c.z, c.w);
}
__host__ __device__ constexpr long long koff(int i, int u) { return i < 3 ? 2 * i * u : i == 3 ? 6 * u + ((6ll * u) << 32) : (2 * i - 1) * u; }
__device__ __forceinline__ float shx(float v, int m) { return __shfl_xor_sync(0xffffffffu, v, m); }
template <int V> struct IC { __host__ __device__ constexpr operator int() const { return V; } };
template <class F, int... I> __device__ __forceinline__ void sfor_impl(F&& f, std::integer_sequence<int, I...>) {
  (f(IC<I>{}), ...);
}
template <int N, class F> __device__ __forceinline__ void sfor(F&& f) { sfor_impl(f, std::make_integer_sequence<int, N>{}); }

template <long long OFF, int RO = 0, int N>
__device__ __forceinline__ void wgmma_rs_n56(float (&d)[N], const uint4& a, uint64_t base, int scale_d) {
  asm volatile("{\n.reg .pred p;\n.reg .b64 t;\nsetp.ne.b32 p, %33, 0;\nadd.s64 t, %32, %34;\n"
    "wgmma.mma_async.sync.aligned.m64n56k16.f32.bf16.bf16 {%0, %1, %2, %3, %4, %5, %6, %7, %8, %9, %10, %11, %12, %13, %14, %15, %16, %17, %18, %19, %20, %21, %22, %23, %24, %25, %26, %27}, {%28, %29, %30, %31}, t, p, 1, 1, 1;\n}\n"
    : "+f"(d[RO + 0]), "+f"(d[RO + 1]), "+f"(d[RO + 2]), "+f"(d[RO + 3]), "+f"(d[RO + 4]), "+f"(d[RO + 5]), "+f"(d[RO + 6]), "+f"(d[RO + 7]), "+f"(d[RO + 8]), "+f"(d[RO + 9]), "+f"(d[RO + 10]), "+f"(d[RO + 11]), "+f"(d[RO + 12]), "+f"(d[RO + 13]), "+f"(d[RO + 14]), "+f"(d[RO + 15]), "+f"(d[RO + 16]), "+f"(d[RO + 17]), "+f"(d[RO + 18]), "+f"(d[RO + 19]), "+f"(d[RO + 20]), "+f"(d[RO + 21]), "+f"(d[RO + 22]), "+f"(d[RO + 23]), "+f"(d[RO + 24]), "+f"(d[RO + 25]), "+f"(d[RO + 26]), "+f"(d[RO + 27])
    : "r"(a.x), "r"(a.y), "r"(a.z), "r"(a.w), "l"(base), "r"(scale_d), "n"(OFF >> 4));
}
template <long long OFF, int RO = 0, int N>
__device__ __forceinline__ void wgmma_rs_n64(float (&d)[N], const uint4& a, uint64_t base, int scale_d) {
  asm volatile("{\n.reg .pred p;\n.reg .b64 t;\nsetp.ne.b32 p, %37, 0;\nadd.s64 t, %36, %38;\n"
    "wgmma.mma_async.sync.aligned.m64n64k16.f32.bf16.bf16 {%0, %1, %2, %3, %4, %5, %6, %7, %8, %9, %10, %11, %12, %13, %14, %15, %16, %17, %18, %19, %20, %21, %22, %23, %24, %25, %26, %27, %28, %29, %30, %31}, {%32, %33, %34, %35}, t, p, 1, 1, 1;\n}\n"
    : "+f"(d[RO + 0]), "+f"(d[RO + 1]), "+f"(d[RO + 2]), "+f"(d[RO + 3]), "+f"(d[RO + 4]), "+f"(d[RO + 5]), "+f"(d[RO + 6]), "+f"(d[RO + 7]), "+f"(d[RO + 8]), "+f"(d[RO + 9]), "+f"(d[RO + 10]), "+f"(d[RO + 11]), "+f"(d[RO + 12]), "+f"(d[RO + 13]), "+f"(d[RO + 14]), "+f"(d[RO + 15]), "+f"(d[RO + 16]), "+f"(d[RO + 17]), "+f"(d[RO + 18]), "+f"(d[RO + 19]), "+f"(d[RO + 20]), "+f"(d[RO + 21]), "+f"(d[RO + 22]), "+f"(d[RO + 23]), "+f"(d[RO + 24]), "+f"(d[RO + 25]), "+f"(d[RO + 26]), "+f"(d[RO + 27]), "+f"(d[RO + 28]), "+f"(d[RO + 29]), "+f"(d[RO + 30]), "+f"(d[RO + 31])
    : "r"(a.x), "r"(a.y), "r"(a.z), "r"(a.w), "l"(base), "r"(scale_d), "n"(OFF >> 4));
}
template <long long OFF, int RO = 0, int N>
__device__ __forceinline__ void wgmma_rk_n64(float (&d)[N], const uint4& a, uint64_t base, int scale_d) {
  asm volatile("{\n.reg .pred p;\n.reg .b64 t;\nsetp.ne.b32 p, %37, 0;\nadd.s64 t, %36, %38;\n"
    "wgmma.mma_async.sync.aligned.m64n64k16.f32.bf16.bf16 {%0, %1, %2, %3, %4, %5, %6, %7, %8, %9, %10, %11, %12, %13, %14, %15, %16, %17, %18, %19, %20, %21, %22, %23, %24, %25, %26, %27, %28, %29, %30, %31}, {%32, %33, %34, %35}, t, p, 1, 1, 0;\n}\n"
    : "+f"(d[RO + 0]), "+f"(d[RO + 1]), "+f"(d[RO + 2]), "+f"(d[RO + 3]), "+f"(d[RO + 4]), "+f"(d[RO + 5]), "+f"(d[RO + 6]), "+f"(d[RO + 7]), "+f"(d[RO + 8]), "+f"(d[RO + 9]), "+f"(d[RO + 10]), "+f"(d[RO + 11]), "+f"(d[RO + 12]), "+f"(d[RO + 13]), "+f"(d[RO + 14]), "+f"(d[RO + 15]), "+f"(d[RO + 16]), "+f"(d[RO + 17]), "+f"(d[RO + 18]), "+f"(d[RO + 19]), "+f"(d[RO + 20]), "+f"(d[RO + 21]), "+f"(d[RO + 22]), "+f"(d[RO + 23]), "+f"(d[RO + 24]), "+f"(d[RO + 25]), "+f"(d[RO + 26]), "+f"(d[RO + 27]), "+f"(d[RO + 28]), "+f"(d[RO + 29]), "+f"(d[RO + 30]), "+f"(d[RO + 31])
    : "r"(a.x), "r"(a.y), "r"(a.z), "r"(a.w), "l"(base), "r"(scale_d), "n"(OFF >> 4));
}
template <long long OFF, int RO = 0, int N>
__device__ __forceinline__ void wgmma_rs_n128(float (&d)[N], const uint4& a, uint64_t base, int scale_d) {
  asm volatile("{\n.reg .pred p;\n.reg .b64 t;\nsetp.ne.b32 p, %69, 0;\nadd.s64 t, %68, %70;\n"
    "wgmma.mma_async.sync.aligned.m64n128k16.f32.bf16.bf16 {%0, %1, %2, %3, %4, %5, %6, %7, %8, %9, %10, %11, %12, %13, %14, %15, %16, %17, %18, %19, %20, %21, %22, %23, %24, %25, %26, %27, %28, %29, %30, %31, %32, %33, %34, %35, %36, %37, %38, %39, %40, %41, %42, %43, %44, %45, %46, %47, %48, %49, %50, %51, %52, %53, %54, %55, %56, %57, %58, %59, %60, %61, %62, %63}, {%64, %65, %66, %67}, t, p, 1, 1, 1;\n}\n"
    : "+f"(d[RO + 0]), "+f"(d[RO + 1]), "+f"(d[RO + 2]), "+f"(d[RO + 3]), "+f"(d[RO + 4]), "+f"(d[RO + 5]), "+f"(d[RO + 6]), "+f"(d[RO + 7]), "+f"(d[RO + 8]), "+f"(d[RO + 9]), "+f"(d[RO + 10]), "+f"(d[RO + 11]), "+f"(d[RO + 12]), "+f"(d[RO + 13]), "+f"(d[RO + 14]), "+f"(d[RO + 15]), "+f"(d[RO + 16]), "+f"(d[RO + 17]), "+f"(d[RO + 18]), "+f"(d[RO + 19]), "+f"(d[RO + 20]), "+f"(d[RO + 21]), "+f"(d[RO + 22]), "+f"(d[RO + 23]), "+f"(d[RO + 24]), "+f"(d[RO + 25]), "+f"(d[RO + 26]), "+f"(d[RO + 27]), "+f"(d[RO + 28]), "+f"(d[RO + 29]), "+f"(d[RO + 30]), "+f"(d[RO + 31]), "+f"(d[RO + 32]), "+f"(d[RO + 33]), "+f"(d[RO + 34]), "+f"(d[RO + 35]), "+f"(d[RO + 36]), "+f"(d[RO + 37]), "+f"(d[RO + 38]), "+f"(d[RO + 39]), "+f"(d[RO + 40]), "+f"(d[RO + 41]), "+f"(d[RO + 42]), "+f"(d[RO + 43]), "+f"(d[RO + 44]), "+f"(d[RO + 45]), "+f"(d[RO + 46]), "+f"(d[RO + 47]), "+f"(d[RO + 48]), "+f"(d[RO + 49]), "+f"(d[RO + 50]), "+f"(d[RO + 51]), "+f"(d[RO + 52]), "+f"(d[RO + 53]), "+f"(d[RO + 54]), "+f"(d[RO + 55]), "+f"(d[RO + 56]), "+f"(d[RO + 57]), "+f"(d[RO + 58]), "+f"(d[RO + 59]), "+f"(d[RO + 60]), "+f"(d[RO + 61]), "+f"(d[RO + 62]), "+f"(d[RO + 63])
    : "r"(a.x), "r"(a.y), "r"(a.z), "r"(a.w), "l"(base), "r"(scale_d), "n"(OFF >> 4));
}
template <int OFFA, int OFFB>
__device__ __forceinline__ void wgmma_ss_n64(float (&d)[32], uint64_t basea, uint64_t baseb, int scale_d) {
  asm volatile("{\n.reg .pred p;\n.reg .b64 t, u;\nsetp.ne.b32 p, %34, 0;\nadd.s64 t, %32, %35;\nadd.s64 u, %33, %36;\n"
    "wgmma.mma_async.sync.aligned.m64n64k16.f32.bf16.bf16 {%0, %1, %2, %3, %4, %5, %6, %7, %8, %9, %10, %11, %12, %13, %14, %15, %16, %17, %18, %19, %20, %21, %22, %23, %24, %25, %26, %27, %28, %29, %30, %31}, t, u, p, 1, 1, 1, 1;\n}\n"
    : "+f"(d[0]), "+f"(d[1]), "+f"(d[2]), "+f"(d[3]), "+f"(d[4]), "+f"(d[5]), "+f"(d[6]), "+f"(d[7]), "+f"(d[8]), "+f"(d[9]), "+f"(d[10]), "+f"(d[11]), "+f"(d[12]), "+f"(d[13]), "+f"(d[14]), "+f"(d[15]), "+f"(d[16]), "+f"(d[17]), "+f"(d[18]), "+f"(d[19]), "+f"(d[20]), "+f"(d[21]), "+f"(d[22]), "+f"(d[23]), "+f"(d[24]), "+f"(d[25]), "+f"(d[26]), "+f"(d[27]), "+f"(d[28]), "+f"(d[29]), "+f"(d[30]), "+f"(d[31])
    : "l"(basea), "l"(baseb), "r"(scale_d), "n"(OFFA >> 4), "n"(OFFB >> 4));
}

__device__ __forceinline__ void publish7(char* b16, char* b8, const uint32_t (&P)[14], uint32_t par) {
  st_rlx4(b16, tag(P[0], par), P[1], P[2], P[3]);
  st_rlx4(b16 + 512, tag(P[4], par), P[5], P[6], P[7]);
  st_rlx4(b16 + 1024, tag(P[8], par), P[9], P[10], P[11]);
  st_rlx2(b8, tag(P[12], par), P[13]);
}
template <int GOFF>
__device__ __forceinline__ void fix7(uint4* v, const char* g, uint32_t par, int& budget) {
  asm volatile("{\n.reg .pred p;\n.reg .b32 t, w<4>;\nsetp.eq.s32 p, %28, 0;\nC:\n@!p bra.uni L;\nadd.s32 %28, %28, -1;\n"
               "ld.relaxed.gpu.global.v4.u32 {%0,%1,%2,%3}, [%29+%31+0];\n"
               "ld.relaxed.gpu.global.v4.u32 {%4,%5,%6,%7}, [%29+%31+512];\n"
               "ld.relaxed.gpu.global.v4.u32 {%8,%9,%10,%11}, [%29+%31+1024];\n"
               "ld.relaxed.gpu.global.v4.u32 {%12,%13,%14,%15}, [%29+%31+1536];\n"
               "ld.relaxed.gpu.global.v4.u32 {%16,%17,%18,%19}, [%29+%31+2048];\n"
               "ld.relaxed.gpu.global.v4.u32 {%20,%21,%22,%23}, [%29+%31+2560];\n"
               "ld.relaxed.gpu.global.v4.u32 {%24,%25,%26,%27}, [%29+%31+3072];\n"
               "L:\nlop3.b32 w0, %0, %4, %30, 0x7e;\nlop3.b32 w1, %8, %12, %30, 0x7e;\nlop3.b32 w2, %16, %20, %30, 0x7e;\nxor.b32 w3, %24, %30;\n"
               "lop3.b32 t, w0, w1, w2, 0xfe;\nlop3.b32 t, t, w3, 1, 0xa8;\n"
               "setp.ne.u32 p, t, 0;\nsetp.gt.and.s32 p, %28, 0, p;\nvote.sync.any.pred p, p, 0xffffffff;\n@p bra.uni C;\n}"
               : "+r"(v[0].x), "+r"(v[0].y), "+r"(v[0].z), "+r"(v[0].w), "+r"(v[1].x), "+r"(v[1].y), "+r"(v[1].z), "+r"(v[1].w), "+r"(v[2].x), "+r"(v[2].y), "+r"(v[2].z), "+r"(v[2].w), "+r"(v[3].x), "+r"(v[3].y), "+r"(v[3].z), "+r"(v[3].w), "+r"(v[4].x), "+r"(v[4].y), "+r"(v[4].z), "+r"(v[4].w), "+r"(v[5].x), "+r"(v[5].y), "+r"(v[5].z), "+r"(v[5].w), "+r"(v[6].x), "+r"(v[6].y), "+r"(v[6].z), "+r"(v[6].w), "+r"(budget)
               : "l"(g), "r"(par), "n"(GOFF) : "memory");
}
template <int SOFF>
__device__ __forceinline__ void load7s(uint4* v, uint32_t s, uint32_t s8) {
  asm volatile("ld.shared.v4.u32 {%0,%1,%2,%3}, [%28+%30+0];\n"
               "ld.shared.v4.u32 {%4,%5,%6,%7}, [%28+%30+512];\n"
               "ld.shared.v4.u32 {%8,%9,%10,%11}, [%28+%30+1024];\n"
               "ld.shared.v2.u32 {%12,%13}, [%29+%30+1536];\nld.shared.v2.u32 {%14,%15}, [%29+%30+1792];\n"
               "ld.shared.v4.u32 {%16,%17,%18,%19}, [%28+%30+2048];\n"
               "ld.shared.v4.u32 {%20,%21,%22,%23}, [%28+%30+2560];\n"
               "ld.shared.v4.u32 {%24,%25,%26,%27}, [%28+%30+3072];\n"
               : "=r"(v[0].x), "=r"(v[0].y), "=r"(v[0].z), "=r"(v[0].w), "=r"(v[1].x), "=r"(v[1].y), "=r"(v[1].z), "=r"(v[1].w), "=r"(v[2].x), "=r"(v[2].y), "=r"(v[2].z), "=r"(v[2].w), "=r"(v[3].x), "=r"(v[3].y), "=r"(v[3].z), "=r"(v[3].w), "=r"(v[4].x), "=r"(v[4].y), "=r"(v[4].z), "=r"(v[4].w), "=r"(v[5].x), "=r"(v[5].y), "=r"(v[5].z), "=r"(v[5].w), "=r"(v[6].x), "=r"(v[6].y), "=r"(v[6].z), "=r"(v[6].w)
               : "r"(s), "r"(s8), "n"(SOFF) : "memory");
}
template <int GOFF>
__device__ __forceinline__ void fix7s(uint4* v, const char* g, uint32_t par, int& budget) {
  asm volatile("{\n.reg .pred p;\n.reg .b32 t, w<4>;\n.reg .b64 h;\nsetp.eq.s32 p, %28, 0;\nC:\n@!p bra.uni L;\n"
               "add.s32 %28, %28, -1;\nmov.u32 t, %%laneid;\nmad.wide.s32 h, t, -8, %29;\n"
               "ld.relaxed.gpu.global.v4.u32 {%0,%1,%2,%3}, [%29+%31+0];\n"
               "ld.relaxed.gpu.global.v4.u32 {%4,%5,%6,%7}, [%29+%31+512];\n"
               "ld.relaxed.gpu.global.v4.u32 {%8,%9,%10,%11}, [%29+%31+1024];\n"
               "ld.relaxed.gpu.global.v2.u32 {%12,%13}, [h+%31+1536];\nld.relaxed.gpu.global.v2.u32 {%14,%15}, [h+%31+1792];\n"
               "ld.relaxed.gpu.global.v4.u32 {%16,%17,%18,%19}, [%29+%31+2048];\n"
               "ld.relaxed.gpu.global.v4.u32 {%20,%21,%22,%23}, [%29+%31+2560];\n"
               "ld.relaxed.gpu.global.v4.u32 {%24,%25,%26,%27}, [%29+%31+3072];\nL:\n"
               "lop3.b32 w0, %0, %4, %30, 0x7e;\nlop3.b32 w1, %8, %12, %30, 0x7e;\nlop3.b32 w2, %14, %16, %30, 0x7e;\nlop3.b32 w3, %20, %24, %30, 0x7e;\n"
               "lop3.b32 t, w0, w1, w2, 0xfe;\nlop3.b32 t, t, w3, 1, 0xa8;\n"
               "setp.ne.u32 p, t, 0;\nsetp.gt.and.s32 p, %28, 0, p;\nvote.sync.any.pred p, p, 0xffffffff;\n@p bra.uni C;\n}"
               : "+r"(v[0].x), "+r"(v[0].y), "+r"(v[0].z), "+r"(v[0].w), "+r"(v[1].x), "+r"(v[1].y), "+r"(v[1].z), "+r"(v[1].w), "+r"(v[2].x), "+r"(v[2].y), "+r"(v[2].z), "+r"(v[2].w), "+r"(v[3].x), "+r"(v[3].y), "+r"(v[3].z), "+r"(v[3].w), "+r"(v[4].x), "+r"(v[4].y), "+r"(v[4].z), "+r"(v[4].w), "+r"(v[5].x), "+r"(v[5].y), "+r"(v[5].z), "+r"(v[5].w), "+r"(v[6].x), "+r"(v[6].y), "+r"(v[6].z), "+r"(v[6].w), "+r"(budget)
               : "l"(g), "r"(par), "n"(GOFF) : "memory");
}
template <int GOFF>
__device__ __forceinline__ void fix7t(uint4* v, const char* base, uint32_t off, uint32_t s, uint32_t s8, uint32_t par, int& budget) {
  asm volatile("{\n.reg .pred p;\n.reg .b32 t, w<4>;\n.reg .b64 g, h;\nC:\n"
               "lop3.b32 w0, %0, %4, %30, 0x7e;\nlop3.b32 w1, %8, %12, %30, 0x7e;\nlop3.b32 w2, %14, %16, %30, 0x7e;\nlop3.b32 w3, %20, %24, %30, 0x7e;\n"
               "lop3.b32 t, w0, w1, w2, 0xfe;\nlop3.b32 t, t, w3, 1, 0xa8;\n"
               "setp.ne.u32 p, t, 0;\nvote.sync.any.pred p, p, 0xffffffff;\n@!p bra.uni L;\n"
               "add.s32 %28, %28, -1;\nsetp.le.s32 p, %28, 0;\n@p bra.uni L;\n"
               "add.u32 t, %32, %33;\nmad.wide.u32 g, t, 1, %29;\nadd.u32 t, %32, %34;\nmad.wide.u32 h, t, 1, %29;\n"
               "ld.relaxed.gpu.global.v4.u32 {%0,%1,%2,%3}, [g+%31+0];\n"
               "ld.relaxed.gpu.global.v4.u32 {%4,%5,%6,%7}, [g+%31+512];\n"
               "ld.relaxed.gpu.global.v4.u32 {%8,%9,%10,%11}, [g+%31+1024];\n"
               "ld.relaxed.gpu.global.v2.u32 {%12,%13}, [h+%31+1536];\nld.relaxed.gpu.global.v2.u32 {%14,%15}, [h+%31+1792];\n"
               "ld.relaxed.gpu.global.v4.u32 {%16,%17,%18,%19}, [g+%31+2048];\n"
               "ld.relaxed.gpu.global.v4.u32 {%20,%21,%22,%23}, [g+%31+2560];\n"
               "ld.relaxed.gpu.global.v4.u32 {%24,%25,%26,%27}, [g+%31+3072];\nbra.uni C;\nL:\n}"
               : "+r"(v[0].x), "+r"(v[0].y), "+r"(v[0].z), "+r"(v[0].w), "+r"(v[1].x), "+r"(v[1].y), "+r"(v[1].z), "+r"(v[1].w), "+r"(v[2].x), "+r"(v[2].y), "+r"(v[2].z), "+r"(v[2].w), "+r"(v[3].x), "+r"(v[3].y), "+r"(v[3].z), "+r"(v[3].w), "+r"(v[4].x), "+r"(v[4].y), "+r"(v[4].z), "+r"(v[4].w), "+r"(v[5].x), "+r"(v[5].y), "+r"(v[5].z), "+r"(v[5].w), "+r"(v[6].x), "+r"(v[6].y), "+r"(v[6].z), "+r"(v[6].w), "+r"(budget)
               : "l"(base), "r"(par), "n"(GOFF - (int)sb - OFF_G), "r"(off), "r"(s), "r"(s8) : "memory");
}
template <int OFF>
__device__ __forceinline__ void fixq(uint4& v, uint32_t a, uint32_t s, const char* g, uint32_t par, int& budget) {
  asm volatile("{\n.reg .pred p;\n.reg .b32 t, u, w<28>;\nsetp.eq.s32 p, %4, 0;\nC:\n@!p bra.uni L;\nadd.s32 %4, %4, -1;\n"
               "ld.relaxed.gpu.global.v4.u32 {w0,w1,w2,w3}, [%7+%9+0];\n"
               "ld.relaxed.gpu.global.v4.u32 {w4,w5,w6,w7}, [%7+%9+512];\n"
               "ld.relaxed.gpu.global.v4.u32 {w8,w9,w10,w11}, [%7+%9+1024];\n"
               "ld.relaxed.gpu.global.v4.u32 {w12,w13,w14,w15}, [%7+%9+1536];\n"
               "ld.relaxed.gpu.global.v4.u32 {w16,w17,w18,w19}, [%7+%9+2048];\n"
               "ld.relaxed.gpu.global.v4.u32 {w20,w21,w22,w23}, [%7+%9+2560];\n"
               "ld.relaxed.gpu.global.v4.u32 {w24,w25,w26,w27}, [%7+%9+3072];\n"
               "st.shared.v4.u32 [%6+%9+0], {w0,w1,w2,w3};\n"
               "st.shared.v4.u32 [%6+%9+512], {w4,w5,w6,w7};\n"
               "st.shared.v4.u32 [%6+%9+1024], {w8,w9,w10,w11};\n"
               "st.shared.v4.u32 [%6+%9+1536], {w12,w13,w14,w15};\n"
               "st.shared.v4.u32 [%6+%9+2048], {w16,w17,w18,w19};\n"
               "st.shared.v4.u32 [%6+%9+2560], {w20,w21,w22,w23};\n"
               "st.shared.v4.u32 [%6+%9+3072], {w24,w25,w26,w27};\n"
               "fence.proxy.async.shared::cta;\nbar.warp.sync 0xffffffff;\n"
               "ld.shared.u32 %0, [%5+%9];\nld.shared.u32 %1, [%5+%9+896];\nld.shared.u32 %2, [%5+%9+1792];\nld.shared.u32 %3, [%5+%9+2688];\n"
               "L:\nlop3.b32 t, %0, %1, %8, 0x7e;\nlop3.b32 u, %2, %3, %8, 0x7e;\nlop3.b32 t, t, u, 1, 0xa8;\n"
               "setp.ne.u32 p, t, 0;\nsetp.gt.and.s32 p, %4, 0, p;\nvote.sync.any.pred p, p, 0xffffffff;\n@p bra.uni C;\n}"
               : "+r"(v.x), "+r"(v.y), "+r"(v.z), "+r"(v.w), "+r"(budget)
               : "r"(a), "r"(s), "l"(g), "r"(par), "n"(OFF) : "memory");
}
#define SPINS(i)
#define RETRY(i, ...) __VA_ARGS__
#define BAR(i) (sb + SMEM_BAR + 8 * (i))
#define WAIT(b, ph) mbar_wait(b, ph, budget)

template <bool SWAP>
__global__ void __launch_bounds__(384, 1)
fused_block_kernel(char* const buf, const char* __restrict__ wo, const uint64_t d128, const uint64_t d64, const uint64_t d0,
                   const uint64_t dq, const uint64_t d1, const uint64_t dko,
                   const char* __restrict__ wg, const char* __restrict__ wu, const char* __restrict__ wd, const char* __restrict__ wq, char* __restrict__ out,
                   const __grid_constant__ CUtensorMap map_x, const __grid_constant__ CUtensorMap map_qkv,
                   const __grid_constant__ CUtensorMap map_wo, const __grid_constant__ CUtensorMap map_gu,
                   const __grid_constant__ CUtensorMap map_gu32) {
  extern __shared__ __align__(1024) uint8_t smem[];
  const int tid = threadIdx.x, lane = tid & 31;
  const int warp = __shfl_sync(0xffffffffu, tid >> 5, 0);
#define KVTHR 0xC0800000
#define KVP 1152
#define OFP 1
#define PP 0
#define WT 0xff4422
#define HORD 0
#define ORED1 8
#define B6 1
#define LA0 1
#define LA1 2
#define W4G 4
#define PFT 0x222
#define PFW 2
#define PFV 3
#define EPC 1
#define QG 1
#define TAILV 0
#define FPOS 21
#define HLD 1
#define GGATE 2
#define RPK 1
#define OPUB 14
#define HRED 5
#define HRED1 5
#define ORED 2
  const int cta = (blockIdx.x & 56) * 2 + (blockIdx.x & 1) * 8 + (blockIdx.x & 6) + (blockIdx.x >> 6), r = cta >> 3, p = cta & 7;
  const int kh = p & 1;
  const int wcol = 56 * p - 8 * kh;
  int budget = SPIN_LIMIT;
  const uint32_t zero = d0 >> 48;
  STAMP(0);
  if (warp < 8) {
    STAMP(60);
    bar_sync<0, 384>();
    STAMP(63);
    asm volatile("setmaxnreg.inc.sync.aligned.u32 224;");
    STAMP(61);
    const int g = warp >> 2, gq = lane >> 2, tq = lane & 3;
    const uint64_t dk = d128 + kh;
    uint4 A[28];
    float rs0, rs1, m0, m1;
    float acc0[28], acc1[28];
    uint32_t mb0, mb1;
    {
      uint32_t la[4];
#pragma unroll
      for (int i = 0; i < 4; i++) {
        la[i] = sb + OFF_X + warp * TILE + (lane & 15) * 128 + (((2 * i + (lane >> 4)) ^ (lane & 7)) << 4);
        asm volatile("" : "+r"(la[i]));
      }
      STAMP(62);
      WAIT(BAR(B_XB + warp), 0);
      STAMP(1);
#pragma unroll
      for (int ks = 0; ks < 28; ks++) A[ks] = ldsm4(la[ks & 3] + (ks >> 2) * 2048);
      float cs[4][4] = {};
#pragma unroll
      for (int ks = 0; ks < 28; ks++) mma16816(cs[ks & 3], A[ks].x, A[ks].y, A[ks].z, A[ks].w, 0x3F803F80u, 0x3F803F80u);
      m0 = ((cs[0][0] + cs[1][0]) + (cs[2][0] + cs[3][0])) * (1.f / DM);
      m1 = ((cs[0][2] + cs[1][2]) + (cs[2][2] + cs[3][2])) * (1.f / DM);
      mb0 = pack2(m0, m0); mb1 = pack2(m1, m1);
      if (lane == 0) mbar_arrive(BAR(B_XFREE) + (mb0 & zero));
      if (tq < 2) sts1(sb + OFF_M + warp * 64 + gq * 4 + tq * 32, __float_as_uint(tq ? m1 : m0));
    }
    STAMP(2);
    uint32_t pa[7];
    {
      const uint32_t prow = sb + OFF_PK + warp * 4096 + gq * 128 + (gq << 4), t = tq >> 1;
      const uint32_t b2 = (prow + ((4 * tq + 8) & 15)) ^ (t << 4);
      pa[0] = prow + 4 * tq; pa[1] = pa[0] ^ 16; pa[2] = pa[0] ^ 32;
      pa[3] = (prow + 4 * (tq & 1)) ^ (48 + 16 * t);
      pa[4] = b2 ^ 64; pa[5] = b2 ^ 80 ^ (t << 5); pa[6] = b2 ^ 96;
#pragma unroll
      for (int j = 0; j < 7; j++) asm volatile("" : "+r"(pa[j]));
    }
    auto sqs = [&](int q) {
      uint4 s;
#pragma unroll
      for (int ks = 7 * q; ks < 7 * q + 7; ks++) {
        if (ks % 7 == 0) s = make_uint4(sq2(A[ks].x), sq2(A[ks].y), sq2(A[ks].z), sq2(A[ks].w));
        else s = make_uint4(sq2(A[ks].x, s.x), sq2(A[ks].y, s.y), sq2(A[ks].z, s.z), sq2(A[ks].w, s.w));
      }
      s.x = add2(s.x, s.z);
      s.y = add2(s.y, s.w);
      rs0 = (q ? rs0 : 0.f) + (bf_lo(s.x) + bf_hi(s.x));
      rs1 = (q ? rs1 : 0.f) + (bf_lo(s.y) + bf_hi(s.y));
      if (q == 3) {
        rs0 += shx(rs0, 1); rs1 += shx(rs1, 1);
        rs0 += shx(rs0, 2); rs1 += shx(rs1, 2);
      }
      asm volatile("" : "+f"(rs0), "+f"(rs1));
    };
    auto sub = [&](int q) {
#pragma unroll
      for (int ks = 7 * q; ks < 7 * q + 7; ks++)
        A[ks] = make_uint4(sub2(A[ks].x, mb0), sub2(A[ks].y, mb1), sub2(A[ks].z, mb0), sub2(A[ks].w, mb1));
    };
    uint32_t sdw;
    float4 c0, c1;
    auto stats = [&] {
      const float d0 = m0 - bf_lo(mb0), d1 = m1 - bf_lo(mb1);
      const float q0 = fmaxf(rs0 * (1.f / DM) - d0 * d0, 0.f) + 1e-5f;
      const float q1 = fmaxf(rs1 * (1.f / DM) - d1 * d1, 0.f) + 1e-5f;
      rs0 = rsqf(q0);
      rs1 = rsqf(q1);
      const float sd = (tq & 2 ? q1 * rs1 : q0 * rs0);
      sdw = pack2(sd, sd - bf_lo(pack2(sd, 0.f)));
      c0 = make_float4(rs0 * 1.4426950408889634f, lg2f(rs0), rs0 * rs0, 1e-6f * rs0);
      c1 = make_float4(rs1 * 1.4426950408889634f, lg2f(rs1), rs1 * rs1, 1e-6f * rs1);
      asm volatile("" : "+r"(sdw), "+f"(c0.x), "+f"(c0.y), "+f"(c0.z), "+f"(c0.w), "+f"(c1.x), "+f"(c1.y), "+f"(c1.z), "+f"(c1.w));
    };
    sub(0);
    sub(1);
    sqs(0);
    sfor<4>([&](auto J) {
      constexpr int j = J;
      WAIT(BAR(B_K + j), 0);
      STAMP(26 + j);
      if (j == 0 && g) bar_sync<7, 256>();
      wg_fence();
      sfor<7>([&](auto I) { wgmma_rs_n56<2 * STG + (7 * j + I) * 2048>(acc0, A[7 * j + I], dk, j + I != 0); });
      if (j == 0 && !g) bar_arrive<7, 256>();
      if (j < 2) sub(j + 2);
      if (j < 3) sqs(j + 1);
      if (j == 2) stats();
    });
    wg_commit();
    STAMP(3);
    WAIT(BAR(B_V), 0);
    STAMP(10);
    wg_fence();
    sfor<7>([&](auto I) { wgmma_rs_n56<I * 2048>(acc1, A[I], dk, I != 0); });
    wg_commit();
    WAIT(BAR(B_XFREE), 0);
    wg_wait<1>();
    acc_fence(acc0);
    STAMP(4);
    if (lane == 0) mbar_arrive(BAR(B_KFREE));
    sfor<7>([&](auto J) {
      constexpr int j = J;
      sfor<3>([&](auto I) {
        constexpr int ks = 7 + 3 * j + I;
        if (ks % 7 == 0) { WAIT(BAR(B_V + ks / 7), 0); STAMP(49 + ks / 7); wg_fence(); }
        wgmma_rs_n56<ks * 2048>(acc1, A[ks], dk, 1);
      });
      sts1(pa[j], pack2(phi(acc0[4 * j], c0), phi(acc0[4 * j + 1], c0)));
      sts1(pa[j] + 1024, pack2(phi(acc0[4 * j + 2], c1), phi(acc0[4 * j + 3], c1)));
    });
    wg_commit();
    if (QG == 0 && g == 1) bar_arrive<3, 256>();
    sts1(((pa[0] & ~15u) ^ (48 + 64 * (tq & 1))) + 2048 + 8 + ((tq >> 1) << 10), sdw);
    wg_wait<0>();
    acc_fence(acc1);
    STAMP(5);
    STAMP(54);
#pragma unroll
    for (int j = 0; j < 7; j++) {
      sts1(pa[j] + 2048, pack2(acc1[4 * j], acc1[4 * j + 1]));
      sts1(pa[j] + 3072, pack2(acc1[4 * j + 2], acc1[4 * j + 3]));
    }
    fence_async_smem();
    if (lane == 0) mbar_arrive(BAR(B_VFREE));
    if (g == 0) {
      bar_arrive<1, 256>();
      bar_sync<3, 256>();
    } else {
      bar_sync<1, 256>();
      STAMP(55);
      float kv[32];
      wg_fence();
      sfor<8>([&](auto I) {
        constexpr int o = OFF_PK + I * 4096;
        wgmma_ss_n64<o, o + 2048>(kv, d128, d128, I != 0);
      });
      wg_commit();
      if (QG == 1) bar_arrive<3, 256>();
      WAIT(BAR(B_INIT), 0);
      char* da = buf + (A_KVR + p * KVR_B + (warp & 3) * 2176) + (uint32_t)(gq * 64 + (tq & 1) * 32 + (tq & 2) * 8);
      char *db = da + (uint32_t)(1152 + gq * 64), *dz = da + (uint32_t)(1008 - gq * 48);
      asm volatile("" : "+l"(da), "+l"(db), "+l"(dz));
      wg_wait<0>();
      acc_fence(kv);
      if (QG == 2) bar_arrive<3, 256>();
      STAMP(56);
      auto put = [&](const float* v, int n) {
        const int b = n & 2;
        if (!b || (tid & 48) != 48) {
          if (n & 1) red_add4(b ? db + 64 : da + 512, v[b + 8], v[b + 9], tq & 2 ? v[b + 5] : v[b + 12], tq & 2 ? 1.f : v[b + 13]);
          else red_add4(b ? db : da, v[b], v[b + 1], v[b + 4], tq & 2 ? 1.f : v[b + 5]);
        }
      };
#pragma unroll
      for (int i = 0; i < 16; i++) kv[i] = warp & 2 ? kv[16 + i] : kv[i];
#pragma unroll
      for (int n = 0; n < 4; n++) put(kv, n);
      if (tq == 2) red_add4(dz, kv[12] + kv[13], kv[14] + kv[15], 0.f, 1.f);
      STAMP(53);
      if (QG == 3) bar_arrive<3, 256>();
    }
    STAMP(6);
    const uint32_t par = EPC ? ~ld_rlx1(&g_cnt[C_ROW + r * 32 + g]) >> 5 & 1 : ~ld_rlx1(&g_epoch[cta * 32]) & 1;
    WAIT(BAR(B_Q), 0);
    wg_fence();
    sfor<28>([&](auto I) { wgmma_rs_n56<I * 2048>(acc0, A[I], dq + kh, I != 0); });
    wg_commit();
    const uint32_t wb = BAR(B_WB) + 32 * g;
    const int wq4 = warp & 3;
    char* const oblk = buf + (A_O + (r * 2 + g) * 2 * STG);
    const uint32_t gsub = sb + OFF_G + g * 2 * STG + wq4 * 3584 + lane * 16, gsub8 = gsub - lane * 8;
    const char* const olane = oblk + (uint32_t)(wq4 * 3584 + lane * 16);
    char* const ob = oblk + (uint32_t)((p >> 1) * TILE + wq4 * 3584 + kh * 896 + gq * 16);
    char *ob16 = ob + tq * 128, *ob8 = ob + 512 + (tq >> 1) * 128 + (tq & 1) * 8, *ob4 = ob + 768 + tq * 4;
    unsigned* cnt = &g_cnt[C_ROW + r * 32];
    asm volatile("" : "+l"(ob16), "+l"(ob8), "+l"(ob4), "+l"(cnt));
    wg_wait<0>();
    acc_fence(acc0);
    STAMP(7);
    if (lane < 2) mbar_arrive(BAR(B_QFREE + lane));
    uint32_t R[14];
    {
      uint4 Q[4];
#pragma unroll
      for (int j = 0; j < 7; j++) {
        const uint32_t lo = pack2(phi(acc0[4 * j], c0), phi(acc0[4 * j + 1], c0));
        const uint32_t hi = pack2(phi(acc0[4 * j + 2], c1), phi(acc0[4 * j + 3], c1));
        if (j & 1) { Q[j >> 1].z = lo; Q[j >> 1].w = hi; } else { Q[j >> 1].x = lo; Q[j >> 1].y = hi; }
      }
      Q[3].z = 0; Q[3].w = 0;
      STAMP(8);
      WAIT(BAR(B_KVB), 0);
      STAMP(9);
      float o[32];
      wg_fence();
      sfor<4>([&](auto I) { wgmma_rs_n64<OFF_KVB + I * 2048>(o, Q[I], d128, I != 0); });
      wg_commit();
      if (ORED == 1 && !g && lane == 0) red_inc(cnt);
      wg_wait<0>();
      if (ORED == 2 && !g && lane == 0) red_inc(cnt);
      acc_fence(o);
      if (ORED == 3 && !g && lane == 0) red_inc(cnt);
      const float da0 = rcpf(o[28] + c0.w), db0 = rcpf(o[29] + c0.w), da1 = rcpf(o[30] + c1.w), db1 = rcpf(o[31] + c1.w);
      uint32_t P[14];
#pragma unroll
      for (int j = 0; j < 7; j++) {
        const bool first = j < 2 || (j < 4 && tq < 3);
        const float s0 = first ? da0 : db0, s1 = first ? da1 : db1;
        P[2 * j] = pack2(o[4 * j] * s0, o[4 * j + 1] * s0);
        P[2 * j + 1] = pack2(o[4 * j + 2] * s1, o[4 * j + 3] * s1);
        if (0x53 >> j & 1) { P[2 * j] = tag(P[2 * j], par); P[2 * j + 1] = tag(P[2 * j + 1], par); }
      }
      auto publish = [&] {
#pragma unroll
        for (int h = 0; h < 2; h++) {
          if (ORED == 4 + h && !g && lane == 0) red_inc(cnt);
          st_rlx4(ob16 + 1792 * h, P[h], P[2 + h], P[4 + h], P[6 + h]);
          st_rlx2(ob8 + 1792 * h, P[8 + h], P[10 + h]);
          st_rlx1(ob4 + 1792 * h, P[12 + h]);
        }
      };
      if (!g) {
        publish();
        if (ORED == 6 && lane == 0) red_inc(cnt);
        STAMP(11);
        if (lane == 0) mbar_arrive(BAR(B_OFREE));
        const int sec = min(lane, 27);
        uint32_t ta = sb + OFF_G + wq4 * 3584 + sec * 32 + (0x3625410 >> (sec & 28) & 7) * 4;
        uint32_t gs = gsub;
        const char* ol = olane;
        asm volatile("" : "+r"(ta), "+l"(ol));
#pragma unroll 1
        for (int h = 0; h < 2; h++) {
          sfor<4>([&](auto Q) {
            constexpr int so = Q * TILE;
            WAIT(BAR(B_WB + Q) + 32 * h, 0);
            STAMPD(1 + 4 * h + Q);
            uint4 tg = make_uint4(lds1(ta + so), lds1(ta + so + 896), lds1(ta + so + 1792), lds1(ta + so + 2688));
            RETRY(4 * h + Q, fixq<so>(tg, ta, gs, ol, par, budget));
            bar_arrive_id(8 + Q + 4 * h);
          });
          ol += 2 * STG;
          ta += 2 * STG;
          gs += 2 * STG;
        }
        bar_sync<3, 256>();
      } else {
        const uint32_t wa = sb + (lane >> 4) * 1024 + (lane & 7) * 128 + ((((2 * wq4 + (lane >> 3 & 1) + kh) ^ lane) & 7) << 4);
        uint4 X[8];
#pragma unroll
        for (int i = 0; i < 8; i++) X[i] = ldsm4t(wa + OFF_XS + i * 2048);
        if (OFP == 0 && lane == 0) mbar_arrive(BAR(B_OFREE));
        WAIT(BAR(B_WO), 0);
        const uint32_t keep = wq4 < 3 ? 0x3F803F80u : 0;
#pragma unroll
        for (int ks = 0; ks < 28; ks++) {
          if (ks == ORED1 && lane == 0) red_inc(cnt + 1);
          if (ks == OPUB) {
            WAIT(BAR(B_WO), 0);
            publish();
            STAMP(11);
            WAIT(BAR(B_WO), 0);
          }
          A[ks] = ldsm4t(wa + OFF_WO + ks * 2048);
        }
#pragma unroll
        for (int i = 0; i < 14; i++) {
          const uint4 w = lds4(sb + OFF_WBAR + i * 64 + tq * 16);
          A[2 * i] = make_uint4(add2(A[2 * i].x, w.x), fma2(A[2 * i].y, keep, w.x), add2(A[2 * i].z, w.y), fma2(A[2 * i].w, keep, w.y));
          A[2 * i + 1] = make_uint4(add2(A[2 * i + 1].x, w.z), fma2(A[2 * i + 1].y, keep, w.z), add2(A[2 * i + 1].z, w.w), fma2(A[2 * i + 1].w, keep, w.w));
          asm volatile("" : "+r"(A[2 * i].x), "+r"(A[2 * i].y), "+r"(A[2 * i].z), "+r"(A[2 * i].w),
                            "+r"(A[2 * i + 1].x), "+r"(A[2 * i + 1].y), "+r"(A[2 * i + 1].z), "+r"(A[2 * i + 1].w)::"memory");
          if (OFP == i + 1 && lane == 0) mbar_arrive(BAR(B_OFREE));
        }
        __syncwarp();
        if (lane < 2) mbar_arrive(BAR(B_WOFREE));
        STAMP(10);
        float hacc[2][32];
        uint32_t ma = sb + OFF_M + tq * 8;
        asm volatile("" : "+r"(ma));
#pragma unroll
        for (int j = 0; j < 16; j++) {
          const uint2 m = lds2(ma + 32 * j);
          const uint32_t lo = j & 1 ? X[j / 2].z : X[j / 2].x, hi = keep ? (j & 1 ? X[j / 2].w : X[j / 2].y) : 0;
          float* a = &hacc[j / 8][4 * (j & 7)];
          a[0] = bf_lo(lo) - __uint_as_float(m.x);
          a[1] = bf_hi(lo) - __uint_as_float(m.y);
          a[2] = bf_lo(hi) - __uint_as_float(m.x);
          a[3] = bf_hi(hi) - __uint_as_float(m.y);
        }
        acc_fence(hacc[0]);
        acc_fence(hacc[1]);
        char* hb = oblk + (uint32_t)(FRAG_B - 2 * STG + (p >> 1) * TILE + (wq4 < 3 ? kh * 2048 + wq4 * 512 + lane * 16 : 1536 + kh * 256 + lane * 8));
        asm volatile("" : "+l"(hb));
        STAMP(16);
        auto hmma = [&](auto N) {
          constexpr int h = N / 4, q = N % 4;
          bar_sync<8 + N, 256>();
          STAMP(1 + N);
          wg_fence();
          sfor<7>([&](auto I) { wgmma_rk_n64<OFF_G + N * TILE + I * 256>(hacc[h], A[7 * q + I], dko, 1); });
        };
        sfor<2>([&](auto H) {
          constexpr int h = H;
          sfor<4>([&](auto Q) { if (!h || Q >= HORD) hmma(IC<4 * h + Q>{}); });
          wg_commit();
          if (!h && HORD) {
            sfor<HORD>([&](auto Q) { hmma(IC<4 + Q>{}); });
            wg_commit();
          }
          if (B6 && h) bar_sync<6, 160>();
          if ((h ? HRED1 : HRED) == 4 && lane == 0) red_inc(cnt + 2 + h);
          wg_wait<!h && HORD>();
          if ((h ? HRED1 : HRED) == 5 && lane == 0) red_inc(cnt + 2 + h);
          acc_fence(hacc[h]);
          STAMP(12 + 2 * h);
          if (lane < 2) mbar_arrive(BAR(B_ORD + h));
          if (wq4 < 3) {
#pragma unroll
            for (int i = 0; i < 4; i++) {
              const float* a = hacc[h] + 8 * i;
              st_rlx4(hb + h * 2 * STG + 3584 * i, tag(transp(pack2(a[0], a[1])), par), transp(pack2(a[4], a[5])), transp(pack2(a[2], a[3])), transp(pack2(a[6], a[7])));
            }
          } else {
#pragma unroll
            for (int i = 0; i < 4; i++) {
              const float* a = hacc[h] + 8 * i;
              st_rlx2(hb + h * 2 * STG + 3584 * i, tag(transp(pack2(a[0], a[1])), par), transp(pack2(a[4], a[5])));
            }
            if (gq == 0) {
#pragma unroll
              for (int j = 0; j < 8; j++) sts2(ma + 256 * h + 32 * j, __float_as_uint(hacc[h][4 * j + 2]), __float_as_uint(hacc[h][4 * j + 3]));
            }
          }
          if ((h ? HRED1 : HRED) == 6 && lane == 0) red_inc(cnt + 2 + h);
          STAMP(13 + 2 * h);
          if (h) bar_sync<5, 128>(); else bar_arrive<3, 256>();
        });
      }
      const char* const rb = olane + (FRAG_B + (p >> 1) * TILE);
#pragma unroll
      for (int i = 0; i < 3; i++) {
        const uint4 v = ld_rlx4(rb + kh * 2048 + 512 * i);
        R[4 * i] = v.x; R[4 * i + 1] = v.y; R[4 * i + 2] = v.z; R[4 * i + 3] = v.w;
      }
      const uint2 v = ld_rlx2(rb + 1536 + kh * 256 - lane * 8);
      R[12] = v.x; R[13] = v.y;
    }
    char* hdst = buf + (A_HH + cta * 2 * STG + warp * 3584) + (uint32_t)(lane * 16);
    {
#define GLU(gt, up, e) fmaf((up) * (e), tanhf_((gt) * (e)), (up) * (e))
      float acc[64];
      uint4 own[5];
#pragma unroll
      for (int i = 0; i < 5; i++) asm volatile("" : "=r"(own[i].x), "=r"(own[i].y), "=r"(own[i].z), "=r"(own[i].w));
      sfor<4>([&](auto I) { WAIT(BAR(B_FULL + I), 0); });
      auto ld = [&](auto Q, bool wait) {
        constexpr int q = Q;
        if (q < 4) {
          if (wait) WAIT(wb + 8 * q, 1);
          load7s<q % 4 * TILE>(&A[7 * (q % 4)], gsub, gsub8);
        }
      };
      WAIT(wb, 1);
      STAMP(58);
      ld(IC<0>{}, false);
      sfor<LA0 - 1>([&](auto Q) { ld(IC<Q + 1>{}, true); });
      if (g) sfor<LA1 - LA0>([&](auto Q) { ld(IC<Q + LA0>{}, true); });
#pragma unroll 1
      for (int c = 0; c < 3; c++) {
        const uint32_t half = (c & 1) * 4;
        if (c == 0) {
          sfor<4>([&](auto KQ) {
            constexpr int kq = KQ;
            WAIT(wb + 8 * ((kq + LA0) % 4), 1);
            RETRY(8 + kq + 4 * g, fix7t<A_H + kq * TILE>(&A[7 * kq], buf, r * 4 * STG, gsub, gsub8, par, budget));
            if (lane == 0) mbar_arrive(BAR(B_HFREE + kq / 2) + 16 * g);
            STAMPD(30 + kq);
            if (LA0 == LA1 || !g) ld(IC<kq + LA0>{}, false);
            else ld(IC<kq + LA1>{}, true);
            wg_fence();
            sfor<7>([&](auto I) { wgmma_rs_n128<kq * STG + koff(I, 1024)>(acc, A[7 * kq + I], d128, kq + I != 0); });
            wg_commit();
          });
          WAIT(wb, 1);
          sfor<4>([&](auto Q) { sqs(Q); });
          rs0 = 0.5f * rsqf(rs0 * (1.f / DM) + 1e-5f);
          rs1 = 0.5f * rsqf(rs1 * (1.f / DM) + 1e-5f);
          wg_wait<1>();
          if (lane < 3) mbar_arrive(BAR(B_EMPTY + lane));
        } else {
          const uint64_t dc = d128 + half * (STG >> 4);
          if (GGATE && c == 1) WAIT(BAR(B_HFREE + 1 + GGATE), 0);
          sfor<4>([&](auto KQ) {
            constexpr int kq = KQ;
            WAIT(BAR(B_FULL + kq) + 8 * half, c >> 1);
            STAMPD(30 + 4 * c + kq);
            wg_fence();
            sfor<7>([&](auto I) { wgmma_rs_n128<kq * STG + koff(I, 1024)>(acc, A[7 * kq + I], dc, kq + I != 0); });
            wg_commit();
            if (kq > 0) {
              wg_wait<1>();
              if (lane == 0) mbar_arrive(BAR(B_EMPTY + kq - 1) + 8 * half);
            }
          });
        }
        wg_wait<0>();
        acc_fence(acc);
        if (lane == 0) mbar_arrive(BAR(B_EMPTY + 3) + 8 * half);
        STAMPD(17 + c);
        constexpr int GO = SWAP ? 32 : 0, UO = SWAP ? 0 : 32;
        own[0] = own[4];
#pragma unroll
        for (int i = 0; i < 4; i++) {
          uint32_t w[4];
#pragma unroll
          for (int t = 0; t < 2; t++) {
            const int b = 8 * i + 4 * t;
            w[2 * t] = pack2(GLU(acc[GO + b], acc[UO + b], rs0), GLU(acc[GO + b + 1], acc[UO + b + 1], rs0));
            w[2 * t + 1] = pack2(GLU(acc[GO + b + 2], acc[UO + b + 2], rs1), GLU(acc[GO + b + 3], acc[UO + b + 3], rs1));
          }
          if (i == 3 && c == 1) hdst += STG - 3584;
          own[i + 1] = make_uint4(tag(w[0], par), w[1], w[2], w[3]);
          st_rlx4(hdst + i * 512, own[i + 1].x, w[1], w[2], w[3]);
        }
        hdst += 2048;
        if (c == 1 && lane == 0) red_inc(&g_cnt[C_ROW + r * 32 + 4 + 2 * (p & 6) + g]);
      }
      float acct[32];
      sfor<2>([&](auto H) {
        constexpr int h = H;
        WAIT(BAR(B_FULL + 4 + h), 1);
        wg_fence();
        sfor<14>([&](auto I) { wgmma_rs_n64<(4 + h) * STG + I / 7 * (TILE / 2) + koff(I % 7, 512)>(acct, A[14 * h + I], d64, h + I != 0); });
        wg_commit();
      });
      auto ldh = [&](int k) {
        WAIT(wb + 8 * k, 0);
#pragma unroll
        for (int i = 0; i < 7; i++) A[7 * k + 7 + i] = lds4(gsub - g * STG + 2 * STG + k * TILE + i * 512);
      };
      wg_wait<1>();
      if (lane == 0) mbar_arrive(BAR(B_EMPTY + 4));
      if (HLD >= 1) ldh(0);
      wg_wait<0>();
      acc_fence(acct);
      if (lane == 0) mbar_arrive(BAR(B_EMPTY + 5));
      if (HLD == 2) ldh(1);
      STAMP(20);
      constexpr int GO = SWAP ? 16 : 0, UO = SWAP ? 0 : 16;
#pragma unroll
      for (int i = 0; i < 2; i++) {
        uint32_t w[4];
#pragma unroll
        for (int t = 0; t < 2; t++) {
          const int b = 8 * i + 4 * t;
          w[2 * t] = pack2(GLU(acct[GO + b], acct[UO + b], rs0), GLU(acct[GO + b + 1], acct[UO + b + 1], rs0));
          w[2 * t + 1] = pack2(GLU(acct[GO + b + 2], acct[UO + b + 2], rs1), GLU(acct[GO + b + 3], acct[UO + b + 3], rs1));
        }
        st_rlx4(hdst + i * 512, tag(w[0], par), w[1], w[2], w[3]);
        A[5 + i] = make_uint4(w[0], w[1], w[2], w[3]);
      }
#pragma unroll
      for (int i = 0; i < 5; i++) A[i] = own[i];
    }
    STAMP(21);
    {
      const char* const hnb = hdst + (1 - 2 * kh) * 2 * STG;
      uint32_t eye = tq == gq >> 1 ? 0x3F80u << (16 * (gq & 1)) : 0;
      auto add = [&](float (&a)[28], const uint32_t (&v)[14]) {
#pragma unroll
        for (int j = 0; j < 7; j++)
          asm("mma.sync.aligned.m16n8k8.row.col.f32.bf16.bf16.f32 {%0,%1,%2,%3}, {%4,%5}, {%6}, {%0,%1,%2,%3};"
              : "+f"(a[4 * j]), "+f"(a[4 * j + 1]), "+f"(a[4 * j + 2]), "+f"(a[4 * j + 3]) : "r"(v[2 * j]), "r"(v[2 * j + 1]), "r"(eye));
      };
      auto add2x = [&](float (&a)[28], const uint32_t (&v)[14], const uint32_t (&u)[14]) {
#pragma unroll
        for (int j = 0; j < 7; j++)
          asm("mma.sync.aligned.m16n8k16.row.col.f32.bf16.bf16.f32 {%0,%1,%2,%3}, {%4,%5,%6,%7}, {%8,%8}, {%0,%1,%2,%3};"
              : "+f"(a[4 * j]), "+f"(a[4 * j + 1]), "+f"(a[4 * j + 2]), "+f"(a[4 * j + 3])
              : "r"(v[2 * j]), "r"(v[2 * j + 1]), "r"(u[2 * j]), "r"(u[2 * j + 1]), "r"(eye));
      };
      auto addu = [&](float (&a)[28], const uint32_t (&v)[14], bool first = false) {
#pragma unroll
        for (int j = 0; j < 14; j++) {
          a[2 * j] = first ? bf_lo(v[j]) : a[2 * j] + bf_lo(v[j]);
          a[2 * j + 1] = first ? bf_hi(v[j]) : a[2 * j + 1] + bf_hi(v[j]);
        }
        acc_fence(a);
      };
      auto send = [&](float (&acc)[28], int x) {
        acc_fence(acc);
        char* const pd = buf + (A_PS + ((cta ^ 2 * x) * 6 + 3 * g + x - 1) * 7168 + (warp & 3) * 1792);
        uint32_t P[14];
#pragma unroll
        for (int j = 0; j < 14; j++) P[j] = pack2(acc[2 * j], acc[2 * j + 1]);
        publish7(pd + (uint32_t)(lane * 16), pd + 1536 + (uint32_t)(lane * 8), P, par);
        if (x < 3 && lane == 0) red_inc(&g_cnt[C_PS + (cta ^ 2 * x) * 8 + g]);
      };
      sfor<4>([&](auto K) {
        constexpr int k = K;
        if (k > 1) {
          wg_wait<1>();
          if (lane == 0) mbar_arrive(BAR(B_EMPTY + k - 2));
        }
        if (k) RETRY(16 + k + 4 * g, fix7<-2560 - (k < 3) * STG>(&A[7 * k], k > 1 ? hnb : hdst, par, budget));
        if (k == 2 && lane < 2) mbar_arrive(BAR(B_HFREE + 1) + 16 * g);
        if (HLD == 0 ? k < 2 : HLD == 1 ? k == 1 : HLD == 3 ? k == 0 : false) {
          constexpr int kk = HLD ? 1 : k;
          WAIT(wb + 8 * kk, 0);
#pragma unroll
          for (int i = 0; i < 7; i++) A[7 * kk + 7 + i] = lds4(gsub - g * STG + 2 * STG + kk * TILE + i * 512);
        }
        if (k == 2) {
#pragma unroll
          for (int i = 0; i < 7; i++) A[21 + i] = ld_rlx4(hnb - 2560 + 512 * i);
        }
        WAIT(BAR(B_FULL + k), 0);
        STAMP(42 + k);
        wg_fence();
        sfor<7>([&](auto I) { wgmma_rs_n56<k * STG + I * 3584>(acc0, A[7 * k + I], d0, k + I != 0); });
        if (k == 3) wg_commit();
        sfor<7>([&](auto I) { wgmma_rs_n56<k * STG + I * 3584 + 896>(acc1, A[7 * k + I], d0, k + I != 0); });
        wg_commit();
      });
      wg_wait<1>();
      send(acc0, 1);
      sfor<4>([&](auto K) {
        constexpr int k = K, s = (k + 4) % 6;
        WAIT(BAR(B_FULL + s), k >= 2);
        STAMP(46 + k);
        wg_fence();
        sfor<7>([&](auto I) { wgmma_rs_n56<s * STG + I * 3584>(acc0, A[7 * k + I], d1, k + I != 0); });
        wg_commit();
        if (k == 0) {
          wg_wait<1>();
          send(acc1, 2);
          const float m0 = __uint_as_float(lds1(sb + OFF_M + warp * 64 + gq * 4)), m1 = __uint_as_float(lds1(sb + OFF_M + warp * 64 + gq * 4 + 32));
#pragma unroll
          for (int i = 0; i < 28; i++) acc1[i] = i & 2 ? -m1 : -m0;
          if (TAILV >= 4) addu(acc1, R);
          acc_fence(acc1);
        }
      });
      if (g) bar_arrive<7, 256>();
      wg_wait<0>();
      STAMP(22);
      send(acc0, 3);
      if (!g) bar_sync<7, 256>();
      uint32_t P[3][14];
      const char* const ps = buf + (A_PS + (cta * 6 + 3 * g) * 7168 + (warp & 3) * 1792) + (uint32_t)(lane * 16);
      auto fetch = [&](int x) {
#pragma unroll
        for (int i = 0; i < 3; i++) {
          const uint4 v = ld_rlx4(ps + 7168 * x + 512 * i);
          P[x][4 * i] = v.x; P[x][4 * i + 1] = v.y; P[x][4 * i + 2] = v.z; P[x][4 * i + 3] = v.w;
        }
        const uint2 v = ld_rlx2(ps + 7168 * x + 1536 - lane * 8);
        P[x][12] = v.x; P[x][13] = v.y;
      };
      const uint32_t pss = sb + (6 + g) * STG + (warp & 3) * 1792;
      auto fetchs = [&] {
        WAIT(wb + 24, 0);
#pragma unroll
        for (int x = 0; x < 2; x++) {
          const uint32_t a = pss + TILE + 7168 * x;
#pragma unroll
          for (int i = 0; i < 3; i++) {
            const uint4 v = lds4(a + 512 * i + lane * 16);
            P[x][4 * i] = v.x; P[x][4 * i + 1] = v.y; P[x][4 * i + 2] = v.z; P[x][4 * i + 3] = v.w;
          }
          const uint2 v = lds2(a + 1536 + lane * 8);
          P[x][12] = v.x; P[x][13] = v.y;
        }
      };
      WAIT(BAR(B_FULL + 5), 0);
      wg_fence();
      sfor<28>([&](auto I) {
        if (I == FPOS) {
          fetchs();
          fetch(2);
          wg_fence();
        }
        wgmma_rs_n56<(I / 7 + 4) % 6 * STG + I % 7 * 3584 + 896>(acc1, A[I], d1, 1);
      });
      wg_commit();
      STAMP(23);
      WAIT(BAR(B_FULL + 5), 0);
      auto check = [&](int x) {
#pragma unroll 1
        while (stale(xor2(P[x][0], P[x][4], par) | xor2(P[x][8], P[x][12], par), budget)) fetch(x);
      };
      uint32_t ob = pss + 7168 + (lane & 15) * 112 + (lane & 16);
      char* op = out + (uint32_t)((128 * r + (tid >> 5) * 16 + (lane >> 3)) * 896 + 112 * p + (lane & 7) * 16);
      uint32_t ia = pss + 7168 + (lane >> 3) * 112 + (lane & 7) * 16;
      asm volatile("" : "+r"(ob), "+l"(op), "+r"(ia));
      check(0);
      check(1);
      uint32_t o[14];
      if (TAILV == 0) {
        wg_wait<0>();
        acc_fence(acc1);
        STAMP(24);
        add(acc1, R);
        add(acc1, P[0]);
        add(acc1, P[1]);
        acc_fence(acc1);
        WAIT(BAR(B_FULL + 5), 0);
        check(2);
        STAMP(57);
        add(acc1, P[2]);
#pragma unroll
        for (int j = 0; j < 14; j++) o[j] = pack2(acc1[2 * j], acc1[2 * j + 1]);
      } else if (TAILV <= 4) {
        wg_wait<0>();
        acc_fence(acc1);
        STAMP(24);
        add2x(acc1, P[0], P[1]);
        acc_fence(acc1);
        WAIT(BAR(B_FULL + 5), 0);
        check(2);
        STAMP(57);
        if (TAILV == 3) add2x(acc1, R, P[2]); else add(acc1, P[2]);
#pragma unroll
        for (int j = 0; j < 14; j++) o[j] = pack2(acc1[2 * j], acc1[2 * j + 1]);
      } else {
        addu(acc0, P[0], true);
        addu(acc0, P[1]);
        check(2);
        STAMP(57);
        addu(acc0, P[2]);
        wg_wait<0>();
        acc_fence(acc1);
        STAMP(24);
#pragma unroll
        for (int j = 0; j < 14; j++) o[j] = pack2(acc1[2 * j] + acc0[2 * j], acc1[2 * j + 1] + acc0[2 * j + 1]);
      }
#pragma unroll
      for (int i = 0; i < 3; i++)
        asm volatile("stmatrix.sync.aligned.m8n8.x4.shared.b16 [%0], {%1,%2,%3,%4};" ::"r"(ob + 32 * i), "r"(o[4 * i]), "r"(o[4 * i + 1]), "r"(o[4 * i + 2]), "r"(o[4 * i + 3]) : "memory");
      asm volatile("stmatrix.sync.aligned.m8n8.x2.shared.b16 [%0], {%1,%2};" ::"r"(ob + 96), "r"(o[12]), "r"(o[13]) : "memory");
      __syncwarp();
      {
        uint4 v[4];
#pragma unroll
        for (int i = 0; i < 4; i++) v[i] = lds4(ia + 448 * i);
        if ((lane & 7) < 7) {
#pragma unroll
          for (int i = 0; i < 4; i++) *(uint4*)(op + 3584 * i) = v[i];
        }
      }
      STAMP(25);
      SPINS(24 + g);
      GTIME(1);
    }
  } else {
    {
      const uint32_t c = 0x100000 - (tid < 256 + B_KVB ? 1 : tid < 256 + B_KFREE ? 4 : tid == 256 + B_XFREE ? 12 : 8);
      if (tid < 320) sts2(BAR(tid - 256), c << 1, c << 11);
      fence_async_smem();
      bar_arrive<0, 384>();
      bar_sync<2, 128>();
#pragma unroll
      for (int i = warp - 8; i < warp; i += 4) {
        if (elect()) {
          mbar_expect_tx(BAR(B_XB + i), TILE);
          tma3d(sb + OFF_X + i * TILE, &map_x, 0, 128 * r + 16 * i, 0, BAR(B_XB + i));
        }
      }
      prefetch_map(&map_qkv);
    }
    STAMPP(60);
    asm volatile("setmaxnreg.dec.sync.aligned.u32 56;");
    STAMPP(63);
    if (warp == 11) {
#pragma unroll 1
      for (int j = 0; j < 8; j++) {
        if (elect()) {
          mbar_expect_tx(BAR(B_K + j), TILE);
          tma2d(sb + (j ^ 4) * TILE, &map_qkv, wcol + DM + DM * (j >> 2), 112 * (j & 3), BAR(B_K + j));
        }
      }
    }
    STAMPP(59);
    const int w = warp - 8, t = tid - 256;
    STAMPP(61);
    char* const kvr = buf + (A_KVR + p * KVR_B);
    if (t < 34) st_rlx4(kvr + (uint32_t)((r * 34 + t) * 16), 0, 0, 0, (t & 1) || ((r & 3) * 34 + t >> 3) == 8 ? 0xC1800000u : 0u);
    const uint32_t e1 = EPC ? (ld_rlx1(&g_cnt[C_ROW + r * 32]) >> 5) + 1 : ld_rlx1(&g_epoch[cta * 32]) + 1;
    const char* wrow = wo + (min(cta, 111) * 4 + w) * (DM * 2) + lane * 16;
    const uint4 u0 = ldg4(wrow);
    uint4 u1 = make_uint4(0, 0, 0, 0);
    if (lane < 24) u1 = ldg4(wrow + 512);
    if (lane < 7) asm volatile("prefetch.global.L2 [%0];" ::"l"(wq + (min(cta, 111) * 4 + w) * (DM * 6) + lane * 128));
    GTIME(0);
    const uint32_t par = e1 & 1;
    STAMPP(62);
    {
      float c[4];
      mma16816z(c, u0, 0x3F803F80u, 0x3F803F80u);
      mma16816(c, u1.x, u1.y, u1.z, u1.w, 0x3F803F80u, 0x3F803F80u);
      float s = c[0] + c[2];
      s += shx(s, 4); s += shx(s, 8); s += shx(s, 16);
      if (lane == 0) st_rlx1(buf + (A_WBAR + cta * 16 + w * 4), pack2(0.f, s * (-1.f / DM)) | par);
    }
    if (smem_u32(smem) != sb) __trap();
    STAMPP(19);
    auto pf = [&](auto T) {
      if (w == PFW && elect()) {
        if (T == 2) prefetch_map(&map_gu);
        if ((PFT & 15) == T) l2_prefetch(wg + cta * 12544, 12544);
        if ((PFT >> 4 & 15) == T) l2_prefetch(wu + cta * 12544, 12544);
        if ((PFT >> 8 & 15) == T) l2_prefetch(wd + cta * 12544, 12544);
        if (T == 2) prefetch_map(&map_gu32);
      }
    };
    uint4 xs[8];
#pragma unroll
    for (int i = 0; i < 8; i++) {
      const int G = 7 * p - kh + (lane & 7), row = (lane >> 3) + 4 * (i & 3);
      if (i % 4 == 0) WAIT(BAR(B_XB + w + (i & 4)), 0);
      xs[i] = lds4(sb + OFF_X + (w + (i & 4)) * TILE + (G >> 3) * 2048 + row * 128 + (((G ^ row) & 7) << 4));
    }
    if (lane == 0) mbar_arrive(BAR(B_XFREE) + (xs[7].x & zero));
    WAIT(BAR(B_XFREE), 0);
    if (w == 0 && elect()) {
      mbar_expect_tx(BAR(B_Q), 2 * STG);
#pragma unroll 1
      for (int j = 0; j < 4; j++) tma2d(sb + OFF_Q + j * TILE, &map_qkv, wcol, 112 * j, BAR(B_Q));
    }
#pragma unroll
    for (int i = 0; i < 4; i++) sts4(sb + OFF_KVB + 2048 * i + t * 16, 0, 0, 0, 0);
#pragma unroll
    for (int i = 0; i < 8; i++) {
      const int row = (lane >> 3) + 4 * (i & 3);
      sts4(sb + OFF_XS + (w + (i & 4)) * 2048 + row * 128 + (((lane ^ row) & 7) << 4), xs[i].x, xs[i].y, xs[i].z, xs[i].w);
    }
    pf(IC<0>{});
    if ((PFT & 15) == 1 && w == PFW) { WAIT(BAR(B_V + PFV), 0); pf(IC<1>{}); }
    const char* const kvt = kvr + (uint32_t)(w * 2176 + (lane & 28) * 16 + (t & 1) * 32 + (t & 2) * 8);
    const char* const kvz = kvr + (uint32_t)(w * 2176 + 1024 + (lane & 28) * 4);
    const char* const kvh = kvt + (uint32_t)(1152 + (lane & 28) * 16);
    {
      uint32_t c[3];
      auto counts = [&] {
#pragma unroll
        for (int i = 0; i < 2; i++) c[i] = ld_rlx1(kvr + (uint32_t)(t * 32) + 4096 * i + 28);
        c[2] = ld_rlx1(kvr + (uint32_t)((t & 15) * 32) + 8192 + 28);
      };
      counts();
      if (w == 0) {
        WAIT(BAR(B_KFREE), 0);
        if (elect()) {
          mbar_expect_tx(BAR(B_WO), 2 * STG);
          tma2d(sb + OFF_WO, &map_wo, wcol, 0, BAR(B_WO));
          tma2d(sb + OFF_WO + STG, &map_wo, wcol, 224, BAR(B_WO));
        }
      }
#pragma unroll 1
      while (stale(~(c[0] & c[1] & c[2]), budget, 0x80000000u)) counts();
    }
    if (lane == 0) mbar_arrive(BAR(B_INIT));
    STAMPP(1);
    pf(IC<2>{});
    uint4 m = ld_rlx4(buf + A_WBAR + (uint32_t)(t * 16));
    WAIT(BAR(B_VFREE), 0);
    auto load_w = [&](auto T) {
      sfor<4>([&](auto U) {
        constexpr int u = U;
        if ((WT >> 4 * u & 15) == T && elect()) {
          mbar_expect_tx(BAR(B_FULL + u), STG);
          tma3d(sb + u * STG, &map_gu, 224 * p + 32 * kh + 64 * (u >> 2), 112 * (u & 3), 0, BAR(B_FULL + u));
        }
      });
    };
#define WHAS(T) ((WT & 15) == T || (WT >> 4 & 15) == T || (WT >> 8 & 15) == T || (WT >> 12 & 15) == T || (WT >> 16 & 15) == T || (WT >> 20 & 15) == T)
    if (w == 0) load_w(IC<0>{});
    {
#pragma unroll 1
      while (stale(xor2(m.x, m.y, par) | xor2(m.z, m.w, par), budget)) m = ld_rlx4(buf + A_WBAR + (uint32_t)(t * 16));
      const uint32_t wa = sb + OFF_WBAR + (t >> 3) * 64 + (t & 1) * 32 + (t & 6) * 2;
      if (t < 112) {
        sts1(wa, __byte_perm(m.x, m.y, 0x7632));
        sts1(wa + 16, __byte_perm(m.z, m.w, 0x7632));
      }
      STAMPP(6);
    }
    bar_sync<2, 128>();
    const int gq = lane >> 2, tq = lane & 3, k = 28 * (w >> 1) + 16 * (w & 1) + gq;
    const uint32_t row = sb + OFF_KVB + k * 128, sw = (k & 7) << 4;
    uint32_t ad[4];
#pragma unroll
    for (int q = 0; q < 4; q++) {
      const int c = 28 * (w >> 1) + 2 * tq + 8 * q;
      ad[q] = row + (2 * (c < 32 ? (c & 6) * 4 + (c >> 3) * 2 : c < 48 ? 32 + (c & 2) * 4 + (c >> 1 & 6) : c) ^ sw);
      asm volatile("" : "+r"(ad[q]));
    }
    const bool lo = !(w & 1) || gq < 4;
    uint32_t m1 = tq & 2 ? ~0u : 0, m2 = lo ? m1 : 0;
    asm volatile("" : "+r"(m1), "+r"(m2));
    if (WHAS(1) && w == 0) { WAIT(BAR(B_QFREE), 0); load_w(IC<1>{}); }
    eq_wait(kvr + w * 2176 + KVP + 28, KVTHR, budget);
    STAMPX(2);
    {
      uint4 v[5];
#pragma unroll 1
      do {
#pragma unroll
        for (int i = 0; i < 4; i++) v[i] = ld_rlx4(i < 2 ? kvt + 512 * i : kvh + 64 * i - 128);
        v[4] = ld_rlx4(kvz);
      } while (stale(or3((v[0].w | v[1].w) & m1, (v[2].w | v[3].w) & m2, v[4].w), budget, ~0u));
      STAMPX(3);
#define F(x) __uint_as_float(x)
      const uint32_t a[4] = {pack2(F(v[0].x), F(v[0].y)), pack2(F(v[0].z), F(m1 ? v[1].z : v[0].w)), pack2(F(v[1].x), F(v[1].y)), pack2(F(v[1].z), F(v[1].w))};
      const uint32_t b[4] = {pack2(F(v[2].x), F(v[2].y)), pack2(F(v[2].z), F(m1 ? v[3].z : v[2].w)), pack2(F(v[3].x), F(v[3].y)), pack2(F(v[3].z), F(v[3].w))};
#pragma unroll
      for (int q = 0; q < 4; q++) {
        if (q < 3 || tq < 2) {
          sts1(ad[q], a[q]);
          if (lo) sts1(ad[q] + 1024, b[q]);
        }
      }
      if (tq == 2) {
        const uint32_t z = pack2(F(v[4].x), F(v[4].y));
        const uint32_t za = __byte_perm(z, 0, w & 2 ? 0x1044 : 0x4410), zb = __byte_perm(z, 0, w & 2 ? 0x3244 : 0x4432);
        sts4(row + (112 ^ sw), za, za, za, za);
        if (lo) sts4(row + 1024 + (112 ^ sw), zb, zb, zb, zb);
      }
      fence_async_smem();
      __syncwarp();
      if (lane == 0) mbar_arrive(BAR(B_KVB));
      STAMPP(4);
      pf(IC<3>{});
    }
    if (w == 0) {
      load_w(IC<2>{});
      WAIT(BAR(B_WOFREE), 0);
      load_w(IC<3>{});
      if (WHAS(4)) { WAIT(BAR(B_WB + 3), 0); load_w(IC<4>{}); }
      if (WHAS(5)) { WAIT(BAR(B_WB + 7), 0); load_w(IC<5>{}); }
      if (W4G < 4) { WAIT(BAR(B_HFREE), 0); WAIT(BAR(B_WB + 4 + W4G), 1); }
#pragma unroll 1
      for (int u = 4; u < 22; u++) {
        const int s = u < 14 ? u & 7 : u < 20 ? u - 14 : u - 20;
        if (u == 14) WAIT(BAR(B_WDOK), 0);
        WAIT(BAR(B_KFREE + s) + (u >= 8 ? 64 : 0), u >= 14 && u < 20);
        STAMPP(20 + u);
        if (elect()) {
          mbar_expect_tx(BAR(B_FULL + s), u < 14 ? STG : WDS);
          if (u < 12) tma3d(sb + s * STG, &map_gu, 224 * p + 32 * kh + 64 * (u >> 2), 112 * (u & 3), 0, BAR(B_FULL + s));
          else if (u < 14) tma3d(sb + s * STG, &map_gu32, 224 * p + 192 - 192 * kh, 224 * (u - 12), 0, BAR(B_FULL + s));
          else bulk_g2s(sb + s * STG, buf + (A_WD + (p * 8 + u - 14) * WDS), WDS, BAR(B_FULL + s));
        }
      }
      SPINS(26);
    } else {
#pragma unroll 1
      for (int j = 0; j < (w == 1 ? 4 : 0); j++) {
        const char* src = buf + (A_O + (j >> 1) * FRAG_B + (r * 2 + (j & 1)) * 2 * STG);
        const uint32_t full = BAR(B_WB + 4 * (j & 1));
        WAIT(BAR(j < 2 ? B_QFREE - j : B_ORD - 2 + j), 0);
        cnt_wait(&g_cnt[C_ROW + r * 32 + j], e1 * 32, budget);
        if (B6 && j == 2) bar_arrive<6, 160>();
        STAMPX(50 + 2 * j);
#pragma unroll
        for (int q = 0; q < 4; q++) {
          if (elect()) {
            mbar_expect_tx(full + 8 * q, TILE);
            bulk_g2s(sb + OFF_G + (j & 1) * 2 * STG + q * TILE, src + q * TILE, TILE, full + 8 * q);
          }
          if (RPK >= 4 && q == RPK % 4 && j == RPK / 4 && lane < 8) mbar_arrive(BAR(B_RPK));
        }
        STAMPP(51 + 2 * j);
      }
      if (w == 1) { SPINS(27); return; }
      const int g = w - 2;
      if ((PFT >> 8) == 4) { WAIT(BAR(B_WB + 3), 0); pf(IC<4>{}); }
      WAIT(BAR(RPK < 4 ? B_HFREE + RPK : B_RPK), 0);
      if (t < 120) {
        const int src = p ^ (r >> 2 & 1), part = (r & 1) + (~(r ^ r >> 1) & 2);
        char* zp = buf + (uint32_t)(A_WD + (p * 16 + r) * (WDS / 2) + t * 16 - 1024);
#pragma unroll 1
        for (int x = 1 + (r >> 2 & 2);; x++, zp += 896) {
          const char* wp = wd + (uint32_t)((224 * src + 32 * (src & 1) + 56 * part + (t & 7)) * 896 + (p ^ 2 * x & 7) * 112 + (t & 56) * 2);
          uint4 z[7];
#pragma unroll
          for (int i = 0; i < 7; i++) {
            if (i == 3 && part + (src & 1) == 4) wp -= 224 * 896;
            z[i] = ldg4(wp + i * 8 * 896);
          }
#pragma unroll
          for (int i = 0; i < 7; i++) st_rlx4(zp + i * 1792, z[i].x, z[i].y, z[i].z, z[i].w);
          if (!(x & 1)) break;
        }
      }
      STAMPP(5);
      asm volatile("fence.proxy.async.global;" ::: "memory");
      __syncwarp();
      if (lane == 0) asm volatile("red.release.gpu.global.add.u32 [%0], 1;" ::"l"(&g_cnt[C_WD + p * 32]) : "memory");
      STAMPP(7);
      cnt_wait<true>(&g_cnt[C_WD + p * 32], e1 * 32, budget);
      STAMPP(18);
      asm volatile("fence.proxy.async.global;" ::: "memory");
      if (lane < 2) mbar_arrive(BAR(B_WDOK));
#pragma unroll 1
      for (int j = 0; j < 4; j += j + 1) {
        const uint32_t bar = BAR(B_WB + 4 * g + j);
        const char* src = buf + (j < 3 ? A_HH + (cta ^ j) * 2 * STG + g * TILE : A_PS + (cta * 6 + 3 * g) * 7168);
        if (j != 1) cnt_wait(&g_cnt[(j < 3 ? C_ROW + r * 32 + 4 + 2 * (p & 6) : C_PS + cta * 8) + g], e1 * 8, budget);
        WAIT(j >= 2 ? BAR(B_HFREE + 2 * g + 1) : BAR(B_EMPTY + 6 + g), j >> 1);
        if (elect()) {
          mbar_expect_tx(bar, TILE);
          bulk_g2s(sb + (6 + g) * STG + (j & 1) * TILE, src, TILE, bar);
        }
      }
      SPINS(28 + g);
      if (!EPC && g) st_rlx1(&g_epoch[cta * 32], e1);
      if (g && lane == 0) DUMP(2);
    }
  }
}

typedef CUresult (*EncodeFn)(CUtensorMap*, CUtensorMapDataType, cuuint32_t, void*, const cuuint64_t*, const cuuint64_t*,
                             const cuuint32_t*, const cuuint32_t*, CUtensorMapInterleave, CUtensorMapSwizzle,
                             CUtensorMapL2promotion, CUtensorMapFloatOOBfill);

void make_map(EncodeFn enc, CUtensorMap* m, const void* p, int rank, const cuuint64_t* gd, const cuuint64_t* gs,
              const cuuint32_t* bd, CUtensorMapSwizzle sw) {
  const cuuint32_t es[5] = {1, 1, 1, 1, 1};
  ENC_CHECK(enc(m, CU_TENSOR_MAP_DATA_TYPE_BFLOAT16, rank, (void*)p, gd, gs, bd, es, CU_TENSOR_MAP_INTERLEAVE_NONE, sw,
                CU_TENSOR_MAP_L2_PROMOTION_NONE, CU_TENSOR_MAP_FLOAT_OOB_FILL_NONE));
}

}

extern "C" void kernel_launch(void* const* d_in, const int* in_sizes, int n_in, void* d_out, int out_size) {
  (void)in_sizes; (void)n_in; (void)out_size;
  static EncodeFn enc = nullptr;
  static char* buf = nullptr;
  if (!enc) {
    void* fn = nullptr;
    cudaDriverEntryPointQueryResult qr;
    cudaGetDriverEntryPoint("cuTensorMapEncodeTiled", &fn, cudaEnableDefault, &qr);
    enc = (EncodeFn)fn;
    cudaGetSymbolAddress((void**)&buf, g_buf);
    cudaFuncSetAttribute(fused_block_kernel<false>, cudaFuncAttributeMaxDynamicSharedMemorySize, SMEM_TOTAL);
    cudaFuncSetAttribute(fused_block_kernel<true>, cudaFuncAttributeMaxDynamicSharedMemorySize, SMEM_TOTAL);
  }
  const CUtensorMapSwizzle S128 = CU_TENSOR_MAP_SWIZZLE_128B;
  CUtensorMap mx, mqkv, mwor, mgu, mgu32;
  {
    cuuint64_t gd[3] = {64, SEQ, 7}, gs[2] = {DM * 2, 128};
    cuuint32_t bd[3] = {64, 16, 7};
    make_map(enc, &mx, d_in[0], 3, gd, gs, bd, S128);
  }
  {
    cuuint64_t gd[2] = {3 * DM, DM}, gs[1] = {3 * DM * 2};
    cuuint32_t bd[2] = {64, 112};
    make_map(enc, &mqkv, d_in[1], 2, gd, gs, bd, S128);
  }
  {
    cuuint64_t gd[2] = {DM, DM}, gs[1] = {DM * 2};
    cuuint32_t bd[2] = {64, 224};
    make_map(enc, &mwor, d_in[2], 2, gd, gs, bd, S128);
  }
  const char *wg = (const char*)d_in[4], *wu = (const char*)d_in[5];
  const bool swap = wu < wg;
  const char* gub = swap ? wu : wg;
  const cuuint64_t gud = swap ? (cuuint64_t)(wg - wu) : (cuuint64_t)(wu - wg);
  {
    cuuint64_t gd[3] = {FF, DM, 2}, gs[2] = {FF * 2, gud};
    cuuint32_t bd[3] = {64, 112, 2};
    make_map(enc, &mgu, gub, 3, gd, gs, bd, S128);
  }
  {
    cuuint64_t gd[3] = {FF, DM, 2}, gs[2] = {FF * 2, gud};
    cuuint32_t bd[3] = {32, 224, 2};
    make_map(enc, &mgu32, gub, 3, gd, gs, bd, CU_TENSOR_MAP_SWIZZLE_64B);
  }
  (swap ? fused_block_kernel<true> : fused_block_kernel<false>)<<<128, 384, SMEM_TOTAL>>>(
      buf, (const char*)d_in[2], mn_desc(sb), mn_desc64(sb), mn_desc0(sb), mn_desc(sb + OFF_Q), mn_desc0(sb), k_desc0(sb), wg, wu, (const char*)d_in[6], (const char*)d_in[1], (char*)d_out, mx, mqkv, mwor, mgu, mgu32);
}
```

```cpp
#include <cuda_runtime.h>
#include <cuda_bf16.h>
#include <cuda.h>
#include <stdint.h>
#include <stdio.h>
#include <utility>

#define SPIN_LIMIT (1 << 18)

namespace {

constexpr uint32_t sb = 1024;
constexpr int SEQ = 2048, DM = 448, FF = 1792;
constexpr int TILE = 14336;
constexpr int STG = 2 * TILE;
constexpr int SMEM_BAR = 8 * STG;
constexpr int SMEM_TOTAL = SMEM_BAR + 3072;
constexpr int OFF_X = 4 * STG, OFF_Q = 4 * STG, OFF_WO = 2 * STG, OFF_G = 4 * STG, OFF_PK = 6 * STG, OFF_KVB = OFF_PK + 32768, OFF_XS = OFF_KVB + 8192,
              OFF_M = SMEM_BAR + 512;
constexpr int B_XB = 0  , B_K = 8  , B_V = 12  , B_Q = 16, B_WO = 17, B_FULL = 18  , B_WB = 26  ,
              B_KVB = 34, B_WDOK = 35, B_INIT = 36,
              B_KFREE = 37, B_QFREE = 38, B_WOFREE = 39, B_OFREE = 40, B_HFREE = 41  , B_EMPTY = 45  , B_XFREE = 53, B_VFREE = 54,
              B_ORD = 55  ;

constexpr int KVR_B = 8704;
constexpr int FRAG_B = 16 * 4 * STG;
constexpr int A_CNT = 0, A_EPOCH = 8192, A_KVR = A_EPOCH + 16384, A_O = A_KVR + 8 * KVR_B + 2048, A_H = A_O + FRAG_B,
              A_HH = A_H + FRAG_B;
constexpr int HH_B = 128 * 2 * STG;
constexpr int A_PS = A_HH + HH_B;
constexpr int WDS = 25088;
constexpr int A_WD = A_PS + 128 * 3 * TILE;
constexpr int A_WOC = A_WD + 64 * WDS;

__device__ uint4 g_buf[(A_WOC + 16 * STG) / 16];
constexpr int C_ROW = 0, C_WD = 512, C_PS = 1024;
#define g_cnt ((unsigned*)buf + A_CNT / 4)
#define ENC_CHECK(x) (void)(x)
#define STAMP(i)
#define STAMPX(i)
#define GTIME(i)
#define STAMPP(i)
#define STAMPD(i)
#define DUMP(row)

__device__ __forceinline__ uint32_t smem_u32(const void* p) { return (uint32_t)__cvta_generic_to_shared(p); }
__device__ __forceinline__ void mbar_init(uint32_t bar, uint32_t cnt) {
  asm volatile("mbarrier.init.shared::cta.b64 [%0], %1;" ::"r"(bar), "r"(cnt) : "memory");
}
__device__ __forceinline__ void mbar_expect_tx(uint32_t bar, uint32_t bytes) {
  asm volatile("mbarrier.arrive.expect_tx.shared::cta.b64 _, [%0], %1;" ::"r"(bar), "r"(bytes) : "memory");
}
__device__ __forceinline__ void mbar_arrive(uint32_t bar) {
  asm volatile("mbarrier.arrive.shared::cta.b64 _, [%0];" ::"r"(bar) : "memory");
}
__device__ __forceinline__ void mbar_wait(uint32_t bar, uint32_t parity, int& budget) {
  asm volatile("{\n.reg .pred p;\nW:\nmbarrier.try_wait.parity.shared::cta.b64 p, [%1], %2;\n"
               "add.s32 %0, %0, -1;\nsetp.gt.and.s32 p, %0, 0, !p;\n@p bra W;\n}"
               : "+r"(budget) : "r"(bar), "r"(parity) : "memory");
}
__device__ __forceinline__ bool elect() {
  uint32_t v;
  asm volatile("{\n.reg .pred p;\nelect.sync _|p, 0xffffffff;\nselp.u32 %0, 1, 0, p;\n}" : "=r"(v));
  return v;
}
__device__ __forceinline__ void tma2d(uint32_t dst, const CUtensorMap* m, int c0, int c1, uint32_t bar) {
  asm volatile("cp.async.bulk.tensor.2d.shared::cluster.global.mbarrier::complete_tx::bytes [%0], [%1, {%3, %4}], [%2];"
               ::"r"(dst), "l"(m), "r"(bar), "r"(c0), "r"(c1) : "memory");
}
__device__ __forceinline__ void tma3d(uint32_t dst, const CUtensorMap* m, int c0, int c1, int c2, uint32_t bar) {
  asm volatile("cp.async.bulk.tensor.3d.shared::cluster.global.mbarrier::complete_tx::bytes [%0], [%1, {%3, %4, %5}], [%2];"
               ::"r"(dst), "l"(m), "r"(bar), "r"(c0), "r"(c1), "r"(c2) : "memory");
}
__device__ __forceinline__ void bulk_g2s(uint32_t dst, const void* src, uint32_t bytes, uint32_t bar) {
  asm volatile("cp.async.bulk.shared::cluster.global.mbarrier::complete_tx::bytes [%0], [%1], %2, [%3];"
               ::"r"(dst), "l"(src), "r"(bytes), "r"(bar) : "memory");
}
__device__ __forceinline__ void l2_prefetch(const void* p, uint32_t bytes) {
  asm volatile("cp.async.bulk.prefetch.L2.global [%0], %1;" ::"l"(p), "r"(bytes) : "memory");
}
__device__ __forceinline__ void prefetch_map(const CUtensorMap* m) {
  asm volatile("prefetch.tensormap [%0];" ::"l"(m) : "memory");
}
__device__ __forceinline__ void fence_async_smem() { asm volatile("fence.proxy.async.shared::cta;" ::: "memory"); }
template <int ID, int N> __device__ __forceinline__ void bar_arrive() { asm volatile("bar.arrive %0, %1;" ::"n"(ID), "n"(N) : "memory"); }
__device__ __forceinline__ void bar_arrive_id(int id) { asm volatile("bar.arrive %0, 256;" ::"r"(id) : "memory"); }
__device__ __forceinline__ void bar_sync_id(int id) { asm volatile("bar.sync %0, 256;" ::"r"(id) : "memory"); }
__device__ __forceinline__ void bar_sync_wg(int id) { asm volatile("bar.sync %0, 128;" ::"r"(id) : "memory"); }
template <int ID, int N> __device__ __forceinline__ void bar_sync() { asm volatile("bar.sync %0, %1;" ::"n"(ID), "n"(N) : "memory"); }
__device__ __forceinline__ void wg_fence() { asm volatile("wgmma.fence.sync.aligned;" ::: "memory"); }
__device__ __forceinline__ void wg_commit() { asm volatile("wgmma.commit_group.sync.aligned;" ::: "memory"); }
template <int N> __device__ __forceinline__ void wg_wait() { asm volatile("wgmma.wait_group.sync.aligned %0;" ::"n"(N) : "memory"); }
template <int N> __device__ __forceinline__ void acc_fence(float (&d)[N]) {
#pragma unroll
  for (int i = 0; i < N; i++) asm volatile("" : "+f"(d[i])::"memory");
}
constexpr uint64_t mn_desc(uint32_t addr) {
  return (uint64_t)((addr & 0x3FFFF) >> 4) | ((uint64_t)(TILE >> 4) << 16) | ((uint64_t)64 << 32) | ((uint64_t)1 << 62);
}
constexpr uint64_t mn_desc64(uint32_t addr) {
  return (uint64_t)((addr & 0x3FFFF) >> 4) | ((uint64_t)(TILE >> 4) << 16) | ((uint64_t)32 << 32) | ((uint64_t)2 << 62);
}
constexpr uint64_t mn_desc0(uint32_t addr) {
  return (uint64_t)((addr & 0x3FFFF) >> 4) | ((uint64_t)(1792 >> 4) << 16) | ((uint64_t)8 << 32);
}
constexpr uint64_t k_desc0(uint32_t addr) {
  return (uint64_t)((addr & 0x3FFFF) >> 4) | ((uint64_t)8 << 16) | ((uint64_t)(1792 >> 4) << 32);
}
__device__ __forceinline__ uint4 ld_rlx4(const void* p) {
  uint4 v;
  asm volatile("ld.relaxed.gpu.global.v4.u32 {%0,%1,%2,%3}, [%4];" : "=r"(v.x), "=r"(v.y), "=r"(v.z), "=r"(v.w) : "l"(p) : "memory");
  return v;
}
__device__ __forceinline__ uint2 ld_rlx2(const void* p) {
  uint2 v;
  asm volatile("ld.relaxed.gpu.global.v2.u32 {%0,%1}, [%2];" : "=r"(v.x), "=r"(v.y) : "l"(p) : "memory");
  return v;
}
__device__ __forceinline__ uint32_t ld_rlx1(const void* p) {
  uint32_t v;
  asm volatile("ld.relaxed.gpu.global.u32 %0, [%1];" : "=r"(v) : "l"(p) : "memory");
  return v;
}
__device__ __forceinline__ void st_rlx4(void* p, uint32_t a, uint32_t b, uint32_t c, uint32_t d) {
  asm volatile("st.relaxed.gpu.global.v4.u32 [%0], {%1,%2,%3,%4};" ::"l"(p), "r"(a), "r"(b), "r"(c), "r"(d) : "memory");
}
__device__ __forceinline__ void st_rlx2(void* p, uint32_t a, uint32_t b) {
  asm volatile("st.relaxed.gpu.global.v2.u32 [%0], {%1,%2};" ::"l"(p), "r"(a), "r"(b) : "memory");
}
__device__ __forceinline__ void st_rlx1(void* p, uint32_t a) {
  asm volatile("st.relaxed.gpu.global.u32 [%0], %1;" ::"l"(p), "r"(a) : "memory");
}
__device__ __forceinline__ void red_inc(unsigned* p, uint32_t skip) {
  asm volatile("{\n.reg .pred p;\nsetp.eq.u32 p, %1, 0;\n@p red.relaxed.gpu.global.inc.u32 [%0], 0xfffffffe;\n}" ::"l"(p), "r"(skip) : "memory");
}
__device__ __forceinline__ void red_release(unsigned* p) {
  asm volatile("red.release.gpu.global.inc.u32 [%0], 0xfffffffe;" ::"l"(p) : "memory");
}
__device__ __forceinline__ void st_rlx42(void* p, uint32_t a, uint32_t b, uint32_t c, uint32_t d, uint32_t all) {
  asm volatile("{\n.reg .pred p;\nsetp.ne.u32 p, %5, 0;\n@p st.relaxed.gpu.global.v4.u32 [%0], {%1,%2,%3,%4};\n"
               "@!p st.relaxed.gpu.global.v2.u32 [%0], {%1,%2};\n}" ::"l"(p), "r"(a), "r"(b), "r"(c), "r"(d), "r"(all) : "memory");
}
__device__ __forceinline__ void red_add4(void* p, float a, float b, float c, float d) {
  asm volatile("red.relaxed.gpu.global.add.v4.f32 [%0], {%1,%2,%3,%4};" ::"l"(p), "f"(a), "f"(b), "f"(c), "f"(d) : "memory");
}
__device__ __forceinline__ void eq_wait(const void* p, uint32_t target, int& budget) {
  asm volatile("{\n.reg .pred p;\n.reg .b32 v;\nW:\nld.relaxed.gpu.global.b32 v, [%1];\nadd.s32 %0, %0, -1;\n"
               "setp.gt.s32 p, %0, 0;\nsetp.gt.and.u32 p, v, %2, p;\n@p bra W;\n}"
               : "+r"(budget) : "l"(p), "r"(target) : "memory");
}
template <bool ACQ = false>
__device__ __forceinline__ void cnt_wait(const unsigned* p, uint32_t target, int& budget) {
  if (ACQ)
    asm volatile("{\n.reg .pred p;\n.reg .s32 v;\nW:\nld.acquire.gpu.global.s32 v, [%1];\nadd.s32 %0, %0, -1;\n"
                 "setp.gt.s32 p, %0, 0;\nsub.s32 v, v, %2;\nsetp.lt.and.s32 p, v, 0, p;\n@p bra W;\n}"
                 : "+r"(budget) : "l"(p), "r"(target) : "memory");
  else
  asm volatile("{\n.reg .pred p;\n.reg .s32 v;\nW:\nld.relaxed.gpu.global.s32 v, [%1];\nadd.s32 %0, %0, -1;\n"
               "setp.gt.s32 p, %0, 0;\nsub.s32 v, v, %2;\nsetp.lt.and.s32 p, v, 0, p;\n@p bra W;\n}"
               : "+r"(budget) : "l"(p), "r"(target) : "memory");
}
__device__ __forceinline__ uint32_t or3(uint32_t a, uint32_t b, uint32_t c) {
  uint32_t r;
  asm("lop3.b32 %0, %1, %2, %3, 0xfe;" : "=r"(r) : "r"(a), "r"(b), "r"(c));
  return r;
}
__device__ __forceinline__ uint32_t xor2(uint32_t a, uint32_t b, uint32_t f) {
  uint32_t r;
  asm("lop3.b32 %0, %1, %2, %3, 0x7e;" : "=r"(r) : "r"(a), "r"(b), "r"(f));
  return r;
}
__device__ __forceinline__ bool stale(uint32_t bad, int& budget, uint32_t mask = 1) {
  uint32_t v;
  asm volatile("{\n.reg .pred p;\n.reg .b32 t;\nand.b32 t, %2, %3;\nsetp.ne.u32 p, t, 0;\nadd.s32 %1, %1, -1;\n"
               "setp.gt.and.s32 p, %1, 0, p;\nvote.sync.any.pred p, p, 0xffffffff;\nselp.u32 %0, 1, 0, p;\n}"
               : "=r"(v), "+r"(budget) : "r"(bad), "r"(mask));
  return v;
}
__device__ __forceinline__ uint32_t tag(uint32_t w, uint32_t par) {
  uint32_t r;
  asm("lop3.b32 %0, %1, %2, 1, 0xd8;" : "=r"(r) : "r"(w), "r"(par));
  return r;
}
__device__ __forceinline__ void sts1(uint32_t a, uint32_t v) { asm volatile("st.shared.u32 [%0], %1;" ::"r"(a), "r"(v) : "memory"); }
__device__ __forceinline__ void sts2(uint32_t a, uint32_t x, uint32_t y) {
  asm volatile("st.shared.v2.u32 [%0], {%1,%2};" ::"r"(a), "r"(x), "r"(y) : "memory");
}
__device__ __forceinline__ void sts4(uint32_t a, uint32_t x, uint32_t y, uint32_t z, uint32_t w) {
  asm volatile("st.shared.v4.u32 [%0], {%1,%2,%3,%4};" ::"r"(a), "r"(x), "r"(y), "r"(z), "r"(w) : "memory");
}
__device__ __forceinline__ uint32_t lds1(uint32_t a) {
  uint32_t v;
  asm volatile("ld.shared.u32 %0, [%1];" : "=r"(v) : "r"(a) : "memory");
  return v;
}
__device__ __forceinline__ uint2 lds2(uint32_t a) {
  uint2 v;
  asm volatile("ld.shared.v2.u32 {%0,%1}, [%2];" : "=r"(v.x), "=r"(v.y) : "r"(a) : "memory");
  return v;
}
__device__ __forceinline__ uint4 lds4(uint32_t a) {
  uint4 v;
  asm volatile("ld.shared.v4.u32 {%0,%1,%2,%3}, [%4];" : "=r"(v.x), "=r"(v.y), "=r"(v.z), "=r"(v.w) : "r"(a) : "memory");
  return v;
}
__device__ __forceinline__ uint4 ldsm4(uint32_t a) {
  uint4 v;
  asm volatile("ldmatrix.sync.aligned.m8n8.x4.shared.b16 {%0,%1,%2,%3}, [%4];" : "=r"(v.x), "=r"(v.y), "=r"(v.z), "=r"(v.w) : "r"(a) : "memory");
  return v;
}
__device__ __forceinline__ uint4 ldsm4t(uint32_t a) {
  uint4 v;
  asm volatile("ldmatrix.sync.aligned.m8n8.x4.trans.shared.b16 {%0,%1,%2,%3}, [%4];" : "=r"(v.x), "=r"(v.y), "=r"(v.z), "=r"(v.w) : "r"(a) : "memory");
  return v;
}
__device__ __forceinline__ uint32_t pack2(float lo, float hi) {
  uint32_t r;
  asm("cvt.rn.bf16x2.f32 %0, %1, %2;" : "=r"(r) : "f"(hi), "f"(lo));
  return r;
}
__device__ __forceinline__ float bf_lo(uint32_t w) { return __uint_as_float(w << 16); }
__device__ __forceinline__ float bf_hi(uint32_t w) { return __uint_as_float(w & 0xFFFF0000u); }
__device__ __forceinline__ uint32_t sub2(uint32_t a, uint32_t b) {
  uint32_t r;
  asm volatile("sub.rn.bf16x2 %0, %1, %2;" : "=r"(r) : "r"(a), "r"(b));
  return r;
}
__device__ __forceinline__ uint32_t add2(uint32_t a, uint32_t b) {
  uint32_t r;
  asm("add.rn.bf16x2 %0, %1, %2;" : "=r"(r) : "r"(a), "r"(b));
  return r;
}
__device__ __forceinline__ uint32_t fma2(uint32_t a, uint32_t b, uint32_t c) {
  uint32_t r;
  asm("fma.rn.bf16x2 %0, %1, %2, %3;" : "=r"(r) : "r"(a), "r"(b), "r"(c));
  return r;
}
__device__ __forceinline__ uint32_t transp(uint32_t a) {
  uint32_t r;
  asm volatile("movmatrix.sync.aligned.m8n8.trans.b16 %0, %1;" : "=r"(r) : "r"(a));
  return r;
}
__device__ __forceinline__ uint32_t sq2(uint32_t a) {
  uint32_t r;
  asm volatile("mul.rn.bf16x2 %0, %1, %1;" : "=r"(r) : "r"(a));
  return r;
}
__device__ __forceinline__ uint32_t sq2(uint32_t a, uint32_t c) {
  uint32_t r;
  asm volatile("fma.rn.bf16x2 %0, %1, %1, %2;" : "=r"(r) : "r"(a), "r"(c));
  return r;
}
__device__ __forceinline__ uint4 ldg4(const void* p) {
  uint4 v;
  asm volatile("ld.global.nc.v4.u32 {%0,%1,%2,%3}, [%4];" : "=r"(v.x), "=r"(v.y), "=r"(v.z), "=r"(v.w) : "l"(p));
  return v;
}
__device__ __forceinline__ void mma16816(float (&c)[4], uint32_t a0, uint32_t a1, uint32_t a2, uint32_t a3, uint32_t b0, uint32_t b1) {
  asm("mma.sync.aligned.m16n8k16.row.col.f32.bf16.bf16.f32 {%0,%1,%2,%3}, {%4,%5,%6,%7}, {%8,%9}, {%0,%1,%2,%3};"
      : "+f"(c[0]), "+f"(c[1]), "+f"(c[2]), "+f"(c[3]) : "r"(a0), "r"(a1), "r"(a2), "r"(a3), "r"(b0), "r"(b1));
}
__device__ __forceinline__ void mma16816z(float (&c)[4], const uint4& a, uint32_t b0, uint32_t b1) {
  asm("mma.sync.aligned.m16n8k16.row.col.f32.bf16.bf16.f32 {%0,%1,%2,%3}, {%4,%5,%6,%7}, {%8,%9}, {%10,%10,%10,%10};"
      : "=f"(c[0]), "=f"(c[1]), "=f"(c[2]), "=f"(c[3]) : "r"(a.x), "r"(a.y), "r"(a.z), "r"(a.w), "r"(b0), "r"(b1), "f"(0.f));
}
__device__ __forceinline__ float ex2f(float x) { float r; asm("ex2.approx.ftz.f32 %0, %1;" : "=f"(r) : "f"(x)); return r; }
__device__ __forceinline__ float tanhf_(float x) { float r; asm("tanh.approx.f32 %0, %1;" : "=f"(r) : "f"(x)); return r; }
__device__ __forceinline__ float rsqf(float x) { float r; asm("rsqrt.approx.ftz.f32 %0, %1;" : "=f"(r) : "f"(x)); return r; }
__device__ __forceinline__ float lg2f(float x) { float r; asm("lg2.approx.ftz.f32 %0, %1;" : "=f"(r) : "f"(x)); return r; }
__device__ __forceinline__ float rcpf(float x) { float r; asm("rcp.approx.ftz.f32 %0, %1;" : "=f"(r) : "f"(x)); return r; }
__device__ __forceinline__ float phi(float a, const float4& c) {
  return ex2f(fmaf(fminf(a, 0.f), c.x, c.y)) + fmaf(fmaxf(a, 0.f), c.z, c.w);
}
__host__ __device__ constexpr long long koff(int i, int u) { return i < 3 ? 2 * i * u : i == 3 ? 6 * u + ((6ll * u) << 32) : (2 * i - 1) * u; }
__device__ __forceinline__ float shx(float v, int m) { return __shfl_xor_sync(0xffffffffu, v, m); }
template <int V> struct IC { __host__ __device__ constexpr operator int() const { return V; } };
template <class F, int... I> __device__ __forceinline__ void sfor_impl(F&& f, std::integer_sequence<int, I...>) {
  (f(IC<I>{}), ...);
}
template <int N, class F> __device__ __forceinline__ void sfor(F&& f) { sfor_impl(f, std::make_integer_sequence<int, N>{}); }

template <long long OFF, int RO = 0, int N>
__device__ __forceinline__ void wgmma_rs_n56(float (&d)[N], const uint4& a, uint64_t base, int scale_d) {
  asm volatile("{\n.reg .pred p;\n.reg .b64 t;\nsetp.ne.b32 p, %33, 0;\nadd.s64 t, %32, %34;\n"
    "wgmma.mma_async.sync.aligned.m64n56k16.f32.bf16.bf16 {%0, %1, %2, %3, %4, %5, %6, %7, %8, %9, %10, %11, %12, %13, %14, %15, %16, %17, %18, %19, %20, %21, %22, %23, %24, %25, %26, %27}, {%28, %29, %30, %31}, t, p, 1, 1, 1;\n}\n"
    : "+f"(d[RO + 0]), "+f"(d[RO + 1]), "+f"(d[RO + 2]), "+f"(d[RO + 3]), "+f"(d[RO + 4]), "+f"(d[RO + 5]), "+f"(d[RO + 6]), "+f"(d[RO + 7]), "+f"(d[RO + 8]), "+f"(d[RO + 9]), "+f"(d[RO + 10]), "+f"(d[RO + 11]), "+f"(d[RO + 12]), "+f"(d[RO + 13]), "+f"(d[RO + 14]), "+f"(d[RO + 15]), "+f"(d[RO + 16]), "+f"(d[RO + 17]), "+f"(d[RO + 18]), "+f"(d[RO + 19]), "+f"(d[RO + 20]), "+f"(d[RO + 21]), "+f"(d[RO + 22]), "+f"(d[RO + 23]), "+f"(d[RO + 24]), "+f"(d[RO + 25]), "+f"(d[RO + 26]), "+f"(d[RO + 27])
    : "r"(a.x), "r"(a.y), "r"(a.z), "r"(a.w), "l"(base), "r"(scale_d), "n"(OFF >> 4));
}
template <long long OFF, int RO = 0, int N>
__device__ __forceinline__ void wgmma_rs_n64(float (&d)[N], const uint4& a, uint64_t base, int scale_d) {
  asm volatile("{\n.reg .pred p;\n.reg .b64 t;\nsetp.ne.b32 p, %37, 0;\nadd.s64 t, %36, %38;\n"
    "wgmma.mma_async.sync.aligned.m64n64k16.f32.bf16.bf16 {%0, %1, %2, %3, %4, %5, %6, %7, %8, %9, %10, %11, %12, %13, %14, %15, %16, %17, %18, %19, %20, %21, %22, %23, %24, %25, %26, %27, %28, %29, %30, %31}, {%32, %33, %34, %35}, t, p, 1, 1, 1;\n}\n"
    : "+f"(d[RO + 0]), "+f"(d[RO + 1]), "+f"(d[RO + 2]), "+f"(d[RO + 3]), "+f"(d[RO + 4]), "+f"(d[RO + 5]), "+f"(d[RO + 6]), "+f"(d[RO + 7]), "+f"(d[RO + 8]), "+f"(d[RO + 9]), "+f"(d[RO + 10]), "+f"(d[RO + 11]), "+f"(d[RO + 12]), "+f"(d[RO + 13]), "+f"(d[RO + 14]), "+f"(d[RO + 15]), "+f"(d[RO + 16]), "+f"(d[RO + 17]), "+f"(d[RO + 18]), "+f"(d[RO + 19]), "+f"(d[RO + 20]), "+f"(d[RO + 21]), "+f"(d[RO + 22]), "+f"(d[RO + 23]), "+f"(d[RO + 24]), "+f"(d[RO + 25]), "+f"(d[RO + 26]), "+f"(d[RO + 27]), "+f"(d[RO + 28]), "+f"(d[RO + 29]), "+f"(d[RO + 30]), "+f"(d[RO + 31])
    : "r"(a.x), "r"(a.y), "r"(a.z), "r"(a.w), "l"(base), "r"(scale_d), "n"(OFF >> 4));
}
template <long long OFF, int RO = 0, int N>
__device__ __forceinline__ void wgmma_rk_n64(float (&d)[N], const uint4& a, uint64_t base, int scale_d) {
  asm volatile("{\n.reg .pred p;\n.reg .b64 t;\nsetp.ne.b32 p, %37, 0;\nadd.s64 t, %36, %38;\n"
    "wgmma.mma_async.sync.aligned.m64n64k16.f32.bf16.bf16 {%0, %1, %2, %3, %4, %5, %6, %7, %8, %9, %10, %11, %12, %13, %14, %15, %16, %17, %18, %19, %20, %21, %22, %23, %24, %25, %26, %27, %28, %29, %30, %31}, {%32, %33, %34, %35}, t, p, 1, 1, 0;\n}\n"
    : "+f"(d[RO + 0]), "+f"(d[RO + 1]), "+f"(d[RO + 2]), "+f"(d[RO + 3]), "+f"(d[RO + 4]), "+f"(d[RO + 5]), "+f"(d[RO + 6]), "+f"(d[RO + 7]), "+f"(d[RO + 8]), "+f"(d[RO + 9]), "+f"(d[RO + 10]), "+f"(d[RO + 11]), "+f"(d[RO + 12]), "+f"(d[RO + 13]), "+f"(d[RO + 14]), "+f"(d[RO + 15]), "+f"(d[RO + 16]), "+f"(d[RO + 17]), "+f"(d[RO + 18]), "+f"(d[RO + 19]), "+f"(d[RO + 20]), "+f"(d[RO + 21]), "+f"(d[RO + 22]), "+f"(d[RO + 23]), "+f"(d[RO + 24]), "+f"(d[RO + 25]), "+f"(d[RO + 26]), "+f"(d[RO + 27]), "+f"(d[RO + 28]), "+f"(d[RO + 29]), "+f"(d[RO + 30]), "+f"(d[RO + 31])
    : "r"(a.x), "r"(a.y), "r"(a.z), "r"(a.w), "l"(base), "r"(scale_d), "n"(OFF >> 4));
}
template <long long OFF, int RO = 0, int N>
__device__ __forceinline__ void wgmma_rs_n128(float (&d)[N], const uint4& a, uint64_t base, int scale_d) {
  asm volatile("{\n.reg .pred p;\n.reg .b64 t;\nsetp.ne.b32 p, %69, 0;\nadd.s64 t, %68, %70;\n"
    "wgmma.mma_async.sync.aligned.m64n128k16.f32.bf16.bf16 {%0, %1, %2, %3, %4, %5, %6, %7, %8, %9, %10, %11, %12, %13, %14, %15, %16, %17, %18, %19, %20, %21, %22, %23, %24, %25, %26, %27, %28, %29, %30, %31, %32, %33, %34, %35, %36, %37, %38, %39, %40, %41, %42, %43, %44, %45, %46, %47, %48, %49, %50, %51, %52, %53, %54, %55, %56, %57, %58, %59, %60, %61, %62, %63}, {%64, %65, %66, %67}, t, p, 1, 1, 1;\n}\n"
    : "+f"(d[RO + 0]), "+f"(d[RO + 1]), "+f"(d[RO + 2]), "+f"(d[RO + 3]), "+f"(d[RO + 4]), "+f"(d[RO + 5]), "+f"(d[RO + 6]), "+f"(d[RO + 7]), "+f"(d[RO + 8]), "+f"(d[RO + 9]), "+f"(d[RO + 10]), "+f"(d[RO + 11]), "+f"(d[RO + 12]), "+f"(d[RO + 13]), "+f"(d[RO + 14]), "+f"(d[RO + 15]), "+f"(d[RO + 16]), "+f"(d[RO + 17]), "+f"(d[RO + 18]), "+f"(d[RO + 19]), "+f"(d[RO + 20]), "+f"(d[RO + 21]), "+f"(d[RO + 22]), "+f"(d[RO + 23]), "+f"(d[RO + 24]), "+f"(d[RO + 25]), "+f"(d[RO + 26]), "+f"(d[RO + 27]), "+f"(d[RO + 28]), "+f"(d[RO + 29]), "+f"(d[RO + 30]), "+f"(d[RO + 31]), "+f"(d[RO + 32]), "+f"(d[RO + 33]), "+f"(d[RO + 34]), "+f"(d[RO + 35]), "+f"(d[RO + 36]), "+f"(d[RO + 37]), "+f"(d[RO + 38]), "+f"(d[RO + 39]), "+f"(d[RO + 40]), "+f"(d[RO + 41]), "+f"(d[RO + 42]), "+f"(d[RO + 43]), "+f"(d[RO + 44]), "+f"(d[RO + 45]), "+f"(d[RO + 46]), "+f"(d[RO + 47]), "+f"(d[RO + 48]), "+f"(d[RO + 49]), "+f"(d[RO + 50]), "+f"(d[RO + 51]), "+f"(d[RO + 52]), "+f"(d[RO + 53]), "+f"(d[RO + 54]), "+f"(d[RO + 55]), "+f"(d[RO + 56]), "+f"(d[RO + 57]), "+f"(d[RO + 58]), "+f"(d[RO + 59]), "+f"(d[RO + 60]), "+f"(d[RO + 61]), "+f"(d[RO + 62]), "+f"(d[RO + 63])
    : "r"(a.x), "r"(a.y), "r"(a.z), "r"(a.w), "l"(base), "r"(scale_d), "n"(OFF >> 4));
}
template <long long OFF, int RO = 0, int N>
__device__ __forceinline__ void wgmma_rk_n128(float (&d)[N], const uint4& a, uint64_t base, int scale_d) {
  asm volatile("{\n.reg .pred p;\n.reg .b64 t;\nsetp.ne.b32 p, %69, 0;\nadd.s64 t, %68, %70;\n"
    "wgmma.mma_async.sync.aligned.m64n128k16.f32.bf16.bf16 {%0, %1, %2, %3, %4, %5, %6, %7, %8, %9, %10, %11, %12, %13, %14, %15, %16, %17, %18, %19, %20, %21, %22, %23, %24, %25, %26, %27, %28, %29, %30, %31, %32, %33, %34, %35, %36, %37, %38, %39, %40, %41, %42, %43, %44, %45, %46, %47, %48, %49, %50, %51, %52, %53, %54, %55, %56, %57, %58, %59, %60, %61, %62, %63}, {%64, %65, %66, %67}, t, p, 1, 1, 0;\n}\n"
    : "+f"(d[RO + 0]), "+f"(d[RO + 1]), "+f"(d[RO + 2]), "+f"(d[RO + 3]), "+f"(d[RO + 4]), "+f"(d[RO + 5]), "+f"(d[RO + 6]), "+f"(d[RO + 7]), "+f"(d[RO + 8]), "+f"(d[RO + 9]), "+f"(d[RO + 10]), "+f"(d[RO + 11]), "+f"(d[RO + 12]), "+f"(d[RO + 13]), "+f"(d[RO + 14]), "+f"(d[RO + 15]), "+f"(d[RO + 16]), "+f"(d[RO + 17]), "+f"(d[RO + 18]), "+f"(d[RO + 19]), "+f"(d[RO + 20]), "+f"(d[RO + 21]), "+f"(d[RO + 22]), "+f"(d[RO + 23]), "+f"(d[RO + 24]), "+f"(d[RO + 25]), "+f"(d[RO + 26]), "+f"(d[RO + 27]), "+f"(d[RO + 28]), "+f"(d[RO + 29]), "+f"(d[RO + 30]), "+f"(d[RO + 31]), "+f"(d[RO + 32]), "+f"(d[RO + 33]), "+f"(d[RO + 34]), "+f"(d[RO + 35]), "+f"(d[RO + 36]), "+f"(d[RO + 37]), "+f"(d[RO + 38]), "+f"(d[RO + 39]), "+f"(d[RO + 40]), "+f"(d[RO + 41]), "+f"(d[RO + 42]), "+f"(d[RO + 43]), "+f"(d[RO + 44]), "+f"(d[RO + 45]), "+f"(d[RO + 46]), "+f"(d[RO + 47]), "+f"(d[RO + 48]), "+f"(d[RO + 49]), "+f"(d[RO + 50]), "+f"(d[RO + 51]), "+f"(d[RO + 52]), "+f"(d[RO + 53]), "+f"(d[RO + 54]), "+f"(d[RO + 55]), "+f"(d[RO + 56]), "+f"(d[RO + 57]), "+f"(d[RO + 58]), "+f"(d[RO + 59]), "+f"(d[RO + 60]), "+f"(d[RO + 61]), "+f"(d[RO + 62]), "+f"(d[RO + 63])
    : "r"(a.x), "r"(a.y), "r"(a.z), "r"(a.w), "l"(base), "r"(scale_d), "n"(OFF >> 4));
}
template <int OFFA, int OFFB>
__device__ __forceinline__ void wgmma_ss_n64(float (&d)[32], uint64_t basea, uint64_t baseb, int scale_d) {
  asm volatile("{\n.reg .pred p;\n.reg .b64 t, u;\nsetp.ne.b32 p, %34, 0;\nadd.s64 t, %32, %35;\nadd.s64 u, %33, %36;\n"
    "wgmma.mma_async.sync.aligned.m64n64k16.f32.bf16.bf16 {%0, %1, %2, %3, %4, %5, %6, %7, %8, %9, %10, %11, %12, %13, %14, %15, %16, %17, %18, %19, %20, %21, %22, %23, %24, %25, %26, %27, %28, %29, %30, %31}, t, u, p, 1, 1, 1, 1;\n}\n"
    : "+f"(d[0]), "+f"(d[1]), "+f"(d[2]), "+f"(d[3]), "+f"(d[4]), "+f"(d[5]), "+f"(d[6]), "+f"(d[7]), "+f"(d[8]), "+f"(d[9]), "+f"(d[10]), "+f"(d[11]), "+f"(d[12]), "+f"(d[13]), "+f"(d[14]), "+f"(d[15]), "+f"(d[16]), "+f"(d[17]), "+f"(d[18]), "+f"(d[19]), "+f"(d[20]), "+f"(d[21]), "+f"(d[22]), "+f"(d[23]), "+f"(d[24]), "+f"(d[25]), "+f"(d[26]), "+f"(d[27]), "+f"(d[28]), "+f"(d[29]), "+f"(d[30]), "+f"(d[31])
    : "l"(basea), "l"(baseb), "r"(scale_d), "n"(OFFA >> 4), "n"(OFFB >> 4));
}

__device__ __forceinline__ void publish7(char* b16, char* b8, const uint32_t (&P)[14], uint32_t par) {
  st_rlx4(b16, tag(P[0], par), P[1], P[2], P[3]);
  st_rlx4(b16 + 512, tag(P[4], par), P[5], P[6], P[7]);
  st_rlx4(b16 + 1024, tag(P[8], par), P[9], P[10], P[11]);
  st_rlx2(b8, tag(P[12], par), P[13]);
}
template <int GOFF>
__device__ __forceinline__ void fix7(uint4* v, const char* g, uint32_t par, int& budget) {
  asm volatile("{\n.reg .pred p;\n.reg .b32 t, w<4>;\nsetp.eq.s32 p, %28, 0;\nC:\n@!p bra.uni L;\nadd.s32 %28, %28, -1;\n"
               "ld.relaxed.gpu.global.v4.u32 {%0,%1,%2,%3}, [%29+%31+0];\n"
               "ld.relaxed.gpu.global.v4.u32 {%4,%5,%6,%7}, [%29+%31+512];\n"
               "ld.relaxed.gpu.global.v4.u32 {%8,%9,%10,%11}, [%29+%31+1024];\n"
               "ld.relaxed.gpu.global.v4.u32 {%12,%13,%14,%15}, [%29+%31+1536];\n"
               "ld.relaxed.gpu.global.v4.u32 {%16,%17,%18,%19}, [%29+%31+2048];\n"
               "ld.relaxed.gpu.global.v4.u32 {%20,%21,%22,%23}, [%29+%31+2560];\n"
               "ld.relaxed.gpu.global.v4.u32 {%24,%25,%26,%27}, [%29+%31+3072];\n"
               "L:\nlop3.b32 w0, %0, %4, %30, 0x7e;\nlop3.b32 w1, %8, %12, %30, 0x7e;\nlop3.b32 w2, %16, %20, %30, 0x7e;\nxor.b32 w3, %24, %30;\n"
               "lop3.b32 t, w0, w1, w2, 0xfe;\nlop3.b32 t, t, w3, 1, 0xa8;\n"
               "setp.ne.u32 p, t, 0;\nsetp.gt.and.s32 p, %28, 0, p;\nvote.sync.any.pred p, p, 0xffffffff;\n@p bra.uni C;\n}"
               : "+r"(v[0].x), "+r"(v[0].y), "+r"(v[0].z), "+r"(v[0].w), "+r"(v[1].x), "+r"(v[1].y), "+r"(v[1].z), "+r"(v[1].w), "+r"(v[2].x), "+r"(v[2].y), "+r"(v[2].z), "+r"(v[2].w), "+r"(v[3].x), "+r"(v[3].y), "+r"(v[3].z), "+r"(v[3].w), "+r"(v[4].x), "+r"(v[4].y), "+r"(v[4].z), "+r"(v[4].w), "+r"(v[5].x), "+r"(v[5].y), "+r"(v[5].z), "+r"(v[5].w), "+r"(v[6].x), "+r"(v[6].y), "+r"(v[6].z), "+r"(v[6].w), "+r"(budget)
               : "l"(g), "r"(par), "n"(GOFF) : "memory");
}
template <int SOFF>
__device__ __forceinline__ void load7s(uint4* v, uint32_t s, uint32_t s8) {
  asm volatile("ld.shared.v4.u32 {%0,%1,%2,%3}, [%28+%30+0];\n"
               "ld.shared.v4.u32 {%4,%5,%6,%7}, [%28+%30+512];\n"
               "ld.shared.v4.u32 {%8,%9,%10,%11}, [%28+%30+1024];\n"
               "ld.shared.v2.u32 {%12,%13}, [%29+%30+1536];\nld.shared.v2.u32 {%14,%15}, [%29+%30+1792];\n"
               "ld.shared.v4.u32 {%16,%17,%18,%19}, [%28+%30+2048];\n"
               "ld.shared.v4.u32 {%20,%21,%22,%23}, [%28+%30+2560];\n"
               "ld.shared.v4.u32 {%24,%25,%26,%27}, [%28+%30+3072];\n"
               : "=r"(v[0].x), "=r"(v[0].y), "=r"(v[0].z), "=r"(v[0].w), "=r"(v[1].x), "=r"(v[1].y), "=r"(v[1].z), "=r"(v[1].w), "=r"(v[2].x), "=r"(v[2].y), "=r"(v[2].z), "=r"(v[2].w), "=r"(v[3].x), "=r"(v[3].y), "=r"(v[3].z), "=r"(v[3].w), "=r"(v[4].x), "=r"(v[4].y), "=r"(v[4].z), "=r"(v[4].w), "=r"(v[5].x), "=r"(v[5].y), "=r"(v[5].z), "=r"(v[5].w), "=r"(v[6].x), "=r"(v[6].y), "=r"(v[6].z), "=r"(v[6].w)
               : "r"(s), "r"(s8), "n"(SOFF) : "memory");
}
template <int GOFF>
__device__ __forceinline__ void fix7t(uint4* v, const char* base, uint32_t s, uint32_t s8, uint32_t par, int& budget) {
  asm volatile("{\n.reg .pred p;\n.reg .b32 t, w<4>;\n.reg .b64 g, h;\nsetp.eq.s32 p, %28, 0;\nC:\n@!p bra.uni L;\nadd.s32 %28, %28, -1;\n"
               "mad.wide.u32 g, %32, 1, %29;\nmad.wide.u32 h, %33, 1, %29;\n"
               "ld.relaxed.gpu.global.v4.u32 {%0,%1,%2,%3}, [g+%31+0];\n"
               "ld.relaxed.gpu.global.v4.u32 {%4,%5,%6,%7}, [g+%31+512];\n"
               "ld.relaxed.gpu.global.v4.u32 {%8,%9,%10,%11}, [g+%31+1024];\n"
               "ld.relaxed.gpu.global.v2.u32 {%12,%13}, [h+%31+1536];\nld.relaxed.gpu.global.v2.u32 {%14,%15}, [h+%31+1792];\n"
               "ld.relaxed.gpu.global.v4.u32 {%16,%17,%18,%19}, [g+%31+2048];\n"
               "ld.relaxed.gpu.global.v4.u32 {%20,%21,%22,%23}, [g+%31+2560];\n"
               "ld.relaxed.gpu.global.v4.u32 {%24,%25,%26,%27}, [g+%31+3072];\nL:\n"
               "lop3.b32 w0, %0, %4, %30, 0x7e;\nlop3.b32 w1, %8, %12, %30, 0x7e;\nlop3.b32 w2, %14, %16, %30, 0x7e;\nlop3.b32 w3, %20, %24, %30, 0x7e;\n"
               "lop3.b32 t, w0, w1, w2, 0xfe;\nlop3.b32 t, t, w3, 1, 0xa8;\n"
               "setp.ne.u32 p, t, 0;\nsetp.gt.and.s32 p, %28, 0, p;\nvote.sync.any.pred p, p, 0xffffffff;\n@p bra.uni C;\n}"
               : "+r"(v[0].x), "+r"(v[0].y), "+r"(v[0].z), "+r"(v[0].w), "+r"(v[1].x), "+r"(v[1].y), "+r"(v[1].z), "+r"(v[1].w), "+r"(v[2].x), "+r"(v[2].y), "+r"(v[2].z), "+r"(v[2].w), "+r"(v[3].x), "+r"(v[3].y), "+r"(v[3].z), "+r"(v[3].w), "+r"(v[4].x), "+r"(v[4].y), "+r"(v[4].z), "+r"(v[4].w), "+r"(v[5].x), "+r"(v[5].y), "+r"(v[5].z), "+r"(v[5].w), "+r"(v[6].x), "+r"(v[6].y), "+r"(v[6].z), "+r"(v[6].w), "+r"(budget)
               : "l"(base), "r"(par), "n"(GOFF - (int)sb - OFF_G), "r"(s), "r"(s8) : "memory");
}
__device__ __forceinline__ void fixq(uint32_t a, uint32_t s, const char* g, uint32_t par, int& budget) {
  asm volatile("{\n.reg .pred p;\n.reg .b32 t, u, w<28>;\nsetp.eq.s32 p, %0, 0;\n"
               "ld.shared.u32 w0, [%1];\nld.shared.u32 w1, [%1+896];\nld.shared.u32 w2, [%1+1792];\nld.shared.u32 w3, [%1+2688];\n"
               "C:\n@!p bra.uni L;\nadd.s32 %0, %0, -1;\n"
               "ld.relaxed.gpu.global.v4.u32 {w0,w1,w2,w3}, [%3+0];\n"
               "ld.relaxed.gpu.global.v4.u32 {w4,w5,w6,w7}, [%3+512];\n"
               "ld.relaxed.gpu.global.v4.u32 {w8,w9,w10,w11}, [%3+1024];\n"
               "ld.relaxed.gpu.global.v4.u32 {w12,w13,w14,w15}, [%3+1536];\n"
               "ld.relaxed.gpu.global.v4.u32 {w16,w17,w18,w19}, [%3+2048];\n"
               "ld.relaxed.gpu.global.v4.u32 {w20,w21,w22,w23}, [%3+2560];\n"
               "ld.relaxed.gpu.global.v4.u32 {w24,w25,w26,w27}, [%3+3072];\n"
               "st.shared.v4.u32 [%2+0], {w0,w1,w2,w3};\n"
               "st.shared.v4.u32 [%2+512], {w4,w5,w6,w7};\n"
               "st.shared.v4.u32 [%2+1024], {w8,w9,w10,w11};\n"
               "st.shared.v4.u32 [%2+1536], {w12,w13,w14,w15};\n"
               "st.shared.v4.u32 [%2+2048], {w16,w17,w18,w19};\n"
               "st.shared.v4.u32 [%2+2560], {w20,w21,w22,w23};\n"
               "st.shared.v4.u32 [%2+3072], {w24,w25,w26,w27};\n"
               "fence.proxy.async.shared::cta;\nbar.warp.sync 0xffffffff;\n"
               "ld.shared.u32 w0, [%1];\nld.shared.u32 w1, [%1+896];\nld.shared.u32 w2, [%1+1792];\nld.shared.u32 w3, [%1+2688];\n"
               "L:\n"
               "lop3.b32 t, w0, w1, %4, 0x7e;\nlop3.b32 u, w2, w3, %4, 0x7e;\nlop3.b32 t, t, u, 1, 0xa8;\n"
               "setp.ne.u32 p, t, 0;\nsetp.gt.and.s32 p, %0, 0, p;\nvote.sync.any.pred p, p, 0xffffffff;\n@p bra.uni C;\n}"
               : "+r"(budget)
               : "r"(a), "r"(s), "l"(g), "r"(par) : "memory");
}
#define SPINS(i)
#define RETRY(i, ...) __VA_ARGS__
#define BAR(i) (sb + SMEM_BAR + 8 * (i))
#define WAIT(b, ph) mbar_wait(b, ph, budget)

struct Pos { uint32_t v[8]; };
template <bool SWAP>
__global__ void __launch_bounds__(384, 1)
fused_block_kernel(char* const buf, const char* __restrict__ wo, const uint64_t d128, const uint64_t d64, const uint64_t d0,
                   const uint64_t dq, const uint64_t d1, const uint64_t dko,
                   const char* __restrict__ wg, const char* __restrict__ wu, const char* __restrict__ wd, const char* __restrict__ wq, char* __restrict__ out,
                   const __grid_constant__ CUtensorMap map_x, const __grid_constant__ CUtensorMap map_qkv,
                   const __grid_constant__ Pos pos, const __grid_constant__ CUtensorMap map_gu,
                   const __grid_constant__ CUtensorMap map_gu32) {
  extern __shared__ __align__(1024) uint8_t smem[];
  const int tid = threadIdx.x, lane = tid & 31;
  const int warp = __shfl_sync(0xffffffffu, tid >> 5, 0);
#define KVTHR 0xC0800000
#define KVP 1152
#define OFP 1
#define PP 0
#define WT 0xff4422
#define HORD 0
#define ORED1 24
#define B6 1
#define LA0 1
#define LA1 2
#define W4G 4
#define PFT 0x222
#define PFW 2
#define PFV 3
#define EPC 1
#define QG 1
#define TAILV 0
#define FPOS 21
#define HLD 1
#define ORD 1
#define HF 1
#define MH 1
#define MG 1
#define SQM 0x8421
#define XW 1
#define WOP 0
#define LDP 1
#define W2U 2
#define W2G 3
#define RPKB B_HFREE
#define RPL 0
#define SUBM 0x843
#define SQS 0x8421
#define STP 3
#define GGATE 2
#define RPK 1
#define OPUB 27
#define HRED 5
#define HRED1 5
#define ORED 2
  const int cta = (blockIdx.x & 56) * 2 + (blockIdx.x & 1) * 8 + (blockIdx.x & 6) + (blockIdx.x >> 6), r = cta >> 3, p = cta & 7;
  const int kh = p & 1;
  const int wcol = 56 * p - 8 * kh;
  int budget = SPIN_LIMIT;
  const uint32_t zero = d0 >> 48;
  STAMP(0);
  if (warp >= 8) {
    {
      const uint32_t c = 0x100000 - (tid < 256 + B_KVB ? 1 : tid < 256 + B_KFREE ? 4 : tid == 256 + B_XFREE ? 12 : 8);
      if (tid < 320) sts2(BAR(tid - 256), c << 1, c << 11);
      fence_async_smem();
      bar_arrive<0, 384>();
      bar_sync<2, 128>();
#pragma unroll
      for (int i = warp - 8; i < warp; i += 4) {
        if (elect()) {
          mbar_expect_tx(BAR(B_XB + i), TILE);
          tma3d(sb + OFF_X + i * TILE, &map_x, 0, 128 * r + 16 * i, 0, BAR(B_XB + i));
        }
      }
      prefetch_map(&map_qkv);
    }
    STAMPP(60);
    asm volatile("setmaxnreg.dec.sync.aligned.u32 56;");
    STAMPP(63);
    if (warp == 11) {
#pragma unroll 1
      for (int j = 0; j < 8; j++) {
        if (elect()) {
          mbar_expect_tx(BAR(B_K + j), TILE);
          tma2d(sb + (j ^ 4) * TILE, &map_qkv, wcol + DM + DM * (j >> 2), 112 * (j & 3), BAR(B_K + j));
        }
      }
    }
    STAMPP(59);
    const int w = warp - 8, t = tid - 256;
    STAMPP(61);
    char* const kvr = buf + (A_KVR + p * KVR_B);
    if (t < 34) st_rlx4(kvr + (uint32_t)((r * 34 + t) * 16), 0, 0, 0, (t & 1) || ((r & 3) * 34 + t >> 3) == 8 ? 0xC1800000u : 0u);
    const uint32_t e1 = (ld_rlx1(&g_cnt[C_ROW + r * 32]) >> 5) + 1;
    const int krow = min(cta, 111) * 4 + w;
    const char* wrow = wo + (uint32_t)(krow * (DM * 2) + (lane - (lane >> 3)) * 16);
    uint4 u0 = make_uint4(0, 0, 0, 0), u1 = u0;
    if ((lane & 7) < 7) {
      u0 = ldg4(wrow);
      u1 = ldg4(wrow + 448);
    }
    if (lane < 7) asm volatile("prefetch.global.L2 [%0];" ::"l"(wq + (uint32_t)(krow * (DM * 6) + lane * 128)));
    GTIME(0);
    STAMPP(62);
    {
      float c[4];
      mma16816z(c, u0, 0x3F803F80u, 0x3F803F80u);
      mma16816(c, u1.x, u1.y, u1.z, u1.w, 0x3F803F80u, 0x3F803F80u);
      float s = c[0] + c[2];
      s += shx(s, 4); s += shx(s, 8); s += shx(s, 16);
      const uint32_t nw = pack2(s * (1.f / DM), s * (1.f / DM));
      char* const wc = buf + (A_WOC + krow * 128) + (uint32_t)((lane >> 3) * 2 * STG + (((lane ^ krow) & 7) << 4));
      st_rlx4(wc, tag(sub2(u0.x, nw), e1), tag(sub2(u0.y, nw), e1), tag(sub2(u0.z, nw), e1), tag(sub2(u0.w, nw), e1));
      st_rlx4(wc + 8 * STG, tag(sub2(u1.x, nw), e1), tag(sub2(u1.y, nw), e1), tag(sub2(u1.z, nw), e1), tag(sub2(u1.w, nw), e1));
    }
    if (smem_u32(smem) != sb) __trap();
    STAMPP(19);
    uint4 xs[8];
    {
      const uint32_t G = 7 * p + (lane & 7), a = sb + OFF_X + w * TILE + (G >> 3) * 2048 + (lane >> 3) * 128 + (((G ^ lane >> 3) & 7) << 4), b = a ^ 64;
#pragma unroll
      for (int i = 0; i < 8; i++) {
        if (i % 4 == 0) WAIT(BAR(B_XB + w + (i & 4)), 0);
        xs[i] = lds4((i & 1 ? b : a) + (i & 4) * TILE + (i & 3) * 512);
      }
    }
    if (lane == 0) mbar_arrive(BAR(B_XFREE) + (xs[7].x & zero));
    WAIT(BAR(B_XFREE), 0);
    if (w == 0 && elect()) {
      mbar_expect_tx(BAR(B_Q), 2 * STG);
#pragma unroll 1
      for (int j = 0; j < 4; j++) tma2d(sb + OFF_Q + j * TILE, &map_qkv, wcol, 112 * j, BAR(B_Q));
    }
#pragma unroll
    for (int i = 0; i < 4; i++) sts4(sb + OFF_KVB + 2048 * i + t * 16, 0, 0, 0, 0);
    if ((lane & 7) < 7) {
      const uint32_t a = sb + OFF_XS + w * 2048 + (lane >> 3) * 128 + (((lane ^ lane >> 3) & 7) << 4), b = a ^ 64;
#pragma unroll
      for (int i = 0; i < 8; i++) sts4((i & 1 ? b : a) + (i & 4) * 2048 + (i & 3) * 512, xs[i].x, xs[i].y, xs[i].z, xs[i].w);
    }
    const char* const kvt = kvr + (uint32_t)(w * 2176 + (lane & 28) * 16 + (t & 1) * 32 + (t & 2) * 8);
    const char* const kvz = kvr + (uint32_t)(w * 2176 + 1024 + (lane & 28) * 4);
    const char* const kvh = kvt + (uint32_t)(1152 + (lane & 28) * 16);
    {
      uint32_t c[3];
      bool first = w == 0;
#pragma unroll 1
      do {
#pragma unroll
        for (int i = 0; i < 2; i++) c[i] = ld_rlx1(kvr + (uint32_t)(t * 32) + 4096 * i + 28);
        c[2] = ld_rlx1(kvr + (uint32_t)((t & 15) * 32) + 8192 + 28);
        if (first) {
          WAIT(BAR(B_KFREE), 0);
          STAMPX(6);
          if (elect()) {
            mbar_expect_tx(BAR(B_WO), 2 * STG);
            bulk_g2s(sb + OFF_WO, buf + (A_WOC + p * 2 * STG), 2 * STG, BAR(B_WO));
          }
        }
        first = false;
      } while (stale(~(c[0] & c[1] & c[2]), budget, 0x80000000u));
    }
    if (lane == 0) mbar_arrive(BAR(B_INIT));
    STAMPP(1);
    if (w == 2 && elect()) {
      prefetch_map(&map_gu);
      l2_prefetch(wg + cta * 12544, 12544);
      l2_prefetch(wu + cta * 12544, 12544);
      l2_prefetch(wd + cta * 12544, 12544);
      prefetch_map(&map_gu32);
    }
    WAIT(BAR(B_VFREE), 0);
    bar_sync<2, 128>();
    const int gq = lane >> 2, tq = lane & 3, k = 28 * (w >> 1) + 16 * (w & 1) + gq;
    const uint32_t row = sb + OFF_KVB + k * 128, sw = (k & 7) << 4;
    uint32_t ad[4];
    {
      const uint32_t t4 = pos.v[(w & 2) * 2 + tq] ^ (sw | row & 128) * 0x01010101u;
#pragma unroll
      for (int q = 0; q < 4; q++) {
        ad[q] = __byte_perm(row, t4, 0x3214 + q);
        asm volatile("" : "+r"(ad[q]));
      }
    }
    const bool lo = !(w & 1) || gq < 4;
    uint32_t m1 = tq & 2 ? ~0u : 0, m2 = lo ? m1 : 0;
    asm volatile("" : "+r"(m1), "+r"(m2));
    eq_wait(kvr + w * 2176 + KVP + 28, KVTHR, budget);
    STAMPX(2);
    {
      uint4 v[5];
#pragma unroll 1
      do {
#pragma unroll
        for (int i = 0; i < 4; i++) v[i] = ld_rlx4(i < 2 ? kvt + 512 * i : kvh + 64 * i - 128);
        v[4] = ld_rlx4(kvz);
      } while (stale(or3((v[0].w | v[1].w) & m1, (v[2].w | v[3].w) & m2, v[4].w), budget, ~0u));
      STAMPX(3);
#define F(x) __uint_as_float(x)
      const uint32_t a[4] = {pack2(F(v[0].x), F(v[0].y)), pack2(F(v[0].z), F(m1 ? v[1].z : v[0].w)), pack2(F(v[1].x), F(v[1].y)), pack2(F(v[1].z), F(v[1].w))};
      const uint32_t b[4] = {pack2(F(v[2].x), F(v[2].y)), pack2(F(v[2].z), F(m1 ? v[3].z : v[2].w)), pack2(F(v[3].x), F(v[3].y)), pack2(F(v[3].z), F(v[3].w))};
#pragma unroll
      for (int q = 0; q < 4; q++) {
        if (q < 3 || tq < 2) {
          sts1(ad[q], a[q]);
          if (lo) sts1(ad[q] + 1024, b[q]);
        }
      }
      if (tq == 2) {
        const uint32_t z = pack2(F(v[4].x), F(v[4].y));
        const uint32_t za = __byte_perm(z, 0, w & 2 ? 0x1044 : 0x4410), zb = __byte_perm(z, 0, w & 2 ? 0x3244 : 0x4432);
        sts4(row + (112 ^ sw), za, za, za, za);
        if (lo) sts4(row + 1024 + (112 ^ sw), zb, zb, zb, zb);
      }
      fence_async_smem();
      __syncwarp();
      if (lane == 0) mbar_arrive(BAR(B_KVB));
      STAMPP(4);
    }
    if (w == 0) {
#pragma unroll 1
      for (int u = 0; u < 22; u++) {
        const int s = u < 14 ? u & 7 : u < 20 ? u - 14 : u - 20;
        if (u == W2U || u == 14) WAIT(BAR(u == W2U ? B_WB + W2G : B_WDOK), 0);
        WAIT(BAR(B_KFREE + s) + (u >= 8 ? 64 : 0), u >= 14 && u < 20);
        STAMPP(20 + u);
        if (elect()) {
          mbar_expect_tx(BAR(B_FULL + s), u < 14 ? STG : WDS);
          if (u < 12) tma3d(sb + s * STG, &map_gu, 224 * p + 32 * kh + 64 * (u >> 2), 112 * (u & 3), 0, BAR(B_FULL + s));
          else if (u < 14) tma3d(sb + s * STG, &map_gu32, 224 * p + 192 - 192 * kh, 224 * (u - 12), 0, BAR(B_FULL + s));
          else bulk_g2s(sb + s * STG, buf + (A_WD + (p * 8 + u - 14) * WDS), WDS, BAR(B_FULL + s));
        }
      }
      SPINS(26);
    } else {
#pragma unroll 1
      for (int j = 0; j < (w == 1 ? 4 : 0); j++) {
        WAIT(BAR(j < 2 ? B_QFREE + 2 * j : B_ORD - 2 + j), 0);
        const char* src = buf + (uint32_t)(A_O + (j >> 1) * FRAG_B + (r * 2 + (j & 1)) * 2 * STG);
        uint32_t dst = sb + OFF_G + (j & 1) * 2 * STG, full = BAR(B_WB + 4 * (j & 1));
        if (lane < 4) mbar_expect_tx(full + 8 * lane, TILE);
        asm volatile("" : "+l"(src), "+r"(dst), "+r"(full));
        cnt_wait(&g_cnt[C_ROW + r * 32 + j], e1 * 32, budget);
        STAMPX(50 + 2 * j);
#pragma unroll 1
        do {
          if (elect()) bulk_g2s(dst, src, TILE, full);
          dst += TILE;
          src += TILE;
          full += 8;
        } while ((full - BAR(B_WB)) & 24);
        if (j == 2) bar_arrive<6, 160>();
        STAMPP(51 + 2 * j);
      }
      if (w == 1) { SPINS(27); return; }
      const int g = w - 2;
      WAIT(BAR(B_HFREE), 0);
      {
        const int t = tid < 376 ? tid - 256 : tid - 264;
        const int src = p ^ (r >> 2 & 1), part = (r & 1) + (~(r ^ r >> 1) & 2);
        char* zp = buf + (uint32_t)(A_WD + (p * 16 + r) * (WDS / 2) + t * 16 - 1024);
#pragma unroll 1
        for (int x = 1 + (r >> 2 & 2);; x++, zp += 896) {
          const char* wp = wd + (uint32_t)((224 * src + 32 * (src & 1) + 56 * part + (t & 7)) * 896 + (p ^ 2 * x & 7) * 112 + (t & 56) * 2);
          uint4 z[7];
#pragma unroll
          for (int i = 0; i < 7; i++) {
            if (i == 3 && part + (src & 1) == 4) wp -= 224 * 896;
            z[i] = ldg4(wp + i * 8 * 896);
          }
#pragma unroll
          for (int i = 0; i < 7; i++) st_rlx4(zp + i * 1792, z[i].x, z[i].y, z[i].z, z[i].w);
          if (!(x & 1)) break;
        }
      }
      STAMPP(5);
      asm volatile("fence.proxy.async.global;" ::: "memory");
      __syncwarp();
      if (lane == 0) red_release(&g_cnt[C_WD + p * 32]);
      STAMPP(7);
      cnt_wait<true>(&g_cnt[C_WD + p * 32], e1 * 32, budget);
      STAMPP(18);
      asm volatile("fence.proxy.async.global;" ::: "memory");
      if (lane < 2) mbar_arrive(BAR(B_WDOK));
#pragma unroll 1
      for (int j = 0; j < 4; j += j + 1) {
        const uint32_t bar = BAR(B_WB + 4 * g + j);
        const char* src = buf + (j < 3 ? A_HH + (cta ^ j) * 2 * STG + g * TILE : A_PS + (cta * 6 + 3 * g) * 7168);
        if (j != 1) cnt_wait(&g_cnt[(j < 3 ? C_ROW + r * 32 + 4 + 2 * (p & 6) : C_PS + cta * 8) + g], e1 * 8, budget);
        WAIT(j >= 2 ? BAR(B_HFREE + 2 * g + 1) : BAR(B_EMPTY + 6 + g), j >> 1);
        if (elect()) {
          mbar_expect_tx(bar, TILE);
          bulk_g2s(sb + (6 + g) * STG + (j & 1) * TILE, src, TILE, bar);
        }
      }
      SPINS(28 + g);
      if (g && lane == 0) DUMP(2);
    }
  } else {
    STAMP(60);
    bar_sync<0, 384>();
    STAMP(63);
    asm volatile("setmaxnreg.inc.sync.aligned.u32 224;");
    STAMP(61);
    const int g = warp >> 2, gq = lane >> 2, tq = lane & 3;
    const uint64_t dk = d128 + kh;
    uint4 A[28];
    float rs0, rs1, m0, m1;
    float acc0[28], acc1[28];
    uint32_t mb0, mb1;
    {
      uint32_t la[4];
#pragma unroll
      for (int i = 0; i < 4; i++) {
        la[i] = sb + OFF_X + warp * TILE + (lane & 15) * 128 + (((2 * i + (lane >> 4)) ^ (lane & 7)) << 4);
        asm volatile("" : "+r"(la[i]));
      }
      STAMP(62);
      WAIT(BAR(B_XB + warp), 0);
      STAMP(1);
#pragma unroll
      for (int ks = 0; ks < 28; ks++) A[ks] = ldsm4(la[ks & 3] + (ks >> 2) * 2048);
      float cs[4][4] = {};
#pragma unroll
      for (int ks = 0; ks < 28; ks++) mma16816(cs[ks & 3], A[ks].x, A[ks].y, A[ks].z, A[ks].w, 0x3F803F80u, 0x3F803F80u);
      m0 = ((cs[0][0] + cs[1][0]) + (cs[2][0] + cs[3][0])) * (1.f / DM);
      m1 = ((cs[0][2] + cs[1][2]) + (cs[2][2] + cs[3][2])) * (1.f / DM);
      mb0 = pack2(m0, m0); mb1 = pack2(m1, m1);
      if (lane == 0) mbar_arrive(BAR(B_XFREE) + (mb0 & zero));
    }
    STAMP(2);
    uint32_t pa[7];
    {
      const uint32_t prow = sb + OFF_PK + warp * 4096 + gq * 128 + (gq << 4), t = tq >> 1;
      const uint32_t b2 = (prow + ((4 * tq + 8) & 15)) ^ (t << 4);
      pa[0] = prow + 4 * tq; pa[1] = pa[0] ^ 16; pa[2] = pa[0] ^ 32;
      pa[3] = (prow + 4 * (tq & 1)) ^ (48 + 16 * t);
      pa[4] = b2 ^ 64; pa[5] = b2 ^ 80 ^ (t << 5); pa[6] = b2 ^ 96;
#pragma unroll
      for (int j = 0; j < 7; j++) asm volatile("" : "+r"(pa[j]));
    }
    auto sqs = [&](int q) {
      uint4 s;
#pragma unroll
      for (int ks = 7 * q; ks < 7 * q + 7; ks++) {
        if (ks % 7 == 0) s = make_uint4(sq2(A[ks].x), sq2(A[ks].y), sq2(A[ks].z), sq2(A[ks].w));
        else s = make_uint4(sq2(A[ks].x, s.x), sq2(A[ks].y, s.y), sq2(A[ks].z, s.z), sq2(A[ks].w, s.w));
      }
      s.x = add2(s.x, s.z);
      s.y = add2(s.y, s.w);
      rs0 = (q ? rs0 : 0.f) + (bf_lo(s.x) + bf_hi(s.x));
      rs1 = (q ? rs1 : 0.f) + (bf_lo(s.y) + bf_hi(s.y));
      if (q == 3) {
        rs0 += shx(rs0, 1); rs1 += shx(rs1, 1);
        rs0 += shx(rs0, 2); rs1 += shx(rs1, 2);
      }
      asm volatile("" : "+f"(rs0), "+f"(rs1));
    };
    auto sub = [&](int q) {
#pragma unroll
      for (int ks = 7 * q; ks < 7 * q + 7; ks++)
        A[ks] = make_uint4(sub2(A[ks].x, mb0), sub2(A[ks].y, mb1), sub2(A[ks].z, mb0), sub2(A[ks].w, mb1));
    };
    uint32_t sdw, mw;
    float4 c0, c1;
    auto stats = [&] {
      const float d0 = m0 - bf_lo(mb0), d1 = m1 - bf_lo(mb1);
      const float q0 = fmaxf(rs0 * (1.f / DM) - d0 * d0, 0.f) + 1e-5f;
      const float q1 = fmaxf(rs1 * (1.f / DM) - d1 * d1, 0.f) + 1e-5f;
      rs0 = rsqf(q0);
      rs1 = rsqf(q1);
      const float sd = (tq & 2 ? q1 * rs1 : q0 * rs0);
      sdw = pack2(sd, sd - bf_lo(pack2(sd, 0.f)));
      mw = pack2(tq ? m1 : m0, tq ? d1 : d0);
      c0 = make_float4(rs0 * 1.4426950408889634f, lg2f(rs0), rs0 * rs0, 1e-6f * rs0);
      c1 = make_float4(rs1 * 1.4426950408889634f, lg2f(rs1), rs1 * rs1, 1e-6f * rs1);
      asm volatile("" : "+r"(sdw), "+r"(mw), "+f"(c0.x), "+f"(c0.y), "+f"(c0.z), "+f"(c0.w), "+f"(c1.x), "+f"(c1.y), "+f"(c1.z), "+f"(c1.w));
    };
    auto alu = [&](auto S) {
      sfor<4>([&](auto Q) { if (SUBM >> 4 * S + Q & 1) sub(Q); });
      sfor<4>([&](auto Q) { if (SQS >> 4 * S + Q & 1) sqs(Q); });
      if (S == STP) stats();
    };
    alu(IC<0>{});
    sfor<4>([&](auto J) {
      constexpr int j = J;
      WAIT(BAR(B_K + j), 0);
      STAMP(26 + j);
      if (j == 0 && g) bar_sync<7, 256>();
      wg_fence();
      sfor<7>([&](auto I) { wgmma_rs_n56<2 * STG + (7 * j + I) * 2048>(acc0, A[7 * j + I], dk, j + I != 0); });
      if (j == 0 && !g) bar_arrive<7, 256>();
      if (j == 3) wg_commit();
      alu(IC<j + 1>{});
    });
    STAMP(3);
    WAIT(BAR(B_V), 0);
    STAMP(10);
    wg_fence();
    sfor<7>([&](auto I) { wgmma_rs_n56<I * 2048>(acc1, A[I], dk, I != 0); });
    wg_commit();
    alu(IC<5>{});
    WAIT(BAR(B_XFREE), 0);
    wg_wait<1>();
    acc_fence(acc0);
    STAMP(4);
    if (lane == 0) mbar_arrive(BAR(B_KFREE));
    sfor<7>([&](auto J) {
      constexpr int j = J;
      sfor<3>([&](auto I) {
        constexpr int ks = 7 + 3 * j + I;
        if (ks % 7 == 0) { WAIT(BAR(B_V + ks / 7), 0); STAMP(49 + ks / 7); wg_fence(); }
        wgmma_rs_n56<ks * 2048>(acc1, A[ks], dk, 1);
      });
      sts1(pa[j], pack2(phi(acc0[4 * j], c0), phi(acc0[4 * j + 1], c0)));
      sts1(pa[j] + 1024, pack2(phi(acc0[4 * j + 2], c1), phi(acc0[4 * j + 3], c1)));
    });
    wg_commit();
    sts1(((pa[0] & ~15u) ^ (48 + 64 * (tq & 1))) + 2048 + 8 + ((tq >> 1) << 10), sdw);
    if (tq < 2) sts4(sb + OFF_XS + 112 + warp * 2048 + tq * 1024 + gq * 112, mw, 0, 0, 0);
    wg_wait<0>();
    acc_fence(acc1);
    STAMP(5);
    STAMP(54);
#pragma unroll
    for (int j = 0; j < 7; j++) {
      sts1(pa[j] + 2048, pack2(acc1[4 * j], acc1[4 * j + 1]));
      sts1(pa[j] + 3072, pack2(acc1[4 * j + 2], acc1[4 * j + 3]));
    }
    fence_async_smem();
    if (lane == 0) mbar_arrive(BAR(B_VFREE));
    if (g == 0) {
      bar_arrive<1, 256>();
      bar_sync<3, 256>();
    } else {
      bar_sync<1, 256>();
      STAMP(55);
      float kv[32];
      wg_fence();
      sfor<8>([&](auto I) {
        constexpr int o = OFF_PK + I * 4096;
        wgmma_ss_n64<o, o + 2048>(kv, d128, d128, I != 0);
      });
      wg_commit();
      bar_arrive<3, 256>();
      WAIT(BAR(B_INIT), 0);
      char* da = buf + (A_KVR + p * KVR_B + (warp & 3) * 2176) + (uint32_t)(gq * 64 + (tq & 1) * 32 + (tq & 2) * 8);
      char *db = da + (uint32_t)(1152 + gq * 64), *dz = da + (uint32_t)(1008 - gq * 48);
      asm volatile("" : "+l"(da), "+l"(db), "+l"(dz));
      wg_wait<0>();
      acc_fence(kv);
      STAMP(56);
      auto put = [&](const float* v, int n) {
        const int b = n & 2;
        if (!b || (tid & 48) != 48) {
          if (n & 1) red_add4(b ? db + 64 : da + 512, v[b + 8], v[b + 9], tq & 2 ? v[b + 5] : v[b + 12], tq & 2 ? 1.f : v[b + 13]);
          else red_add4(b ? db : da, v[b], v[b + 1], v[b + 4], tq & 2 ? 1.f : v[b + 5]);
        }
      };
#pragma unroll
      for (int i = 0; i < 16; i++) kv[i] = warp & 2 ? kv[16 + i] : kv[i];
#pragma unroll
      for (int n = 0; n < 4; n++) put(kv, n);
      if (tq == 2) red_add4(dz, kv[12] + kv[13], kv[14] + kv[15], 0.f, 1.f);
      STAMP(53);
    }
    STAMP(6);
    const uint32_t par = ~ld_rlx1(&g_cnt[C_ROW + r * 32 + (tid >> 7)]) >> 5;
    WAIT(BAR(B_Q), 0);
    wg_fence();
    sfor<28>([&](auto I) { wgmma_rs_n56<I * 2048>(acc0, A[I], dq + kh, I != 0); });
    wg_commit();
    const uint32_t wb = BAR(B_WB) + 32 * g;
    const int wq4 = warp & 3;
    char* const oblk = buf + (A_O + (r * 2 + g) * 2 * STG);
    const uint32_t gsub = sb + OFF_G + g * 2 * STG + wq4 * 3584 + lane * 16, gsub8 = gsub - lane * 8;
    const char* const olane = oblk + (uint32_t)(wq4 * 3584 + lane * 16);
    char* const ob = oblk + (uint32_t)((p >> 1) * TILE + wq4 * 3584 + kh * 896 + gq * 16);
    char *ob16 = ob + tq * 128, *ob8 = ob + 512 + (tq >> 1) * 128 + (tq & 1) * 8, *ob4 = ob + 768 + tq * 4;
    unsigned* cnt = &g_cnt[C_ROW + r * 32];
    asm volatile("" : "+l"(ob16), "+l"(ob8), "+l"(ob4), "+l"(cnt));
    wg_wait<0>();
    acc_fence(acc0);
    STAMP(7);
    if (lane == 0) mbar_arrive(BAR(B_QFREE));
    uint32_t R[14];
    {
      uint4 Q[4];
#pragma unroll
      for (int j = 0; j < 7; j++) {
        const uint32_t lo = pack2(phi(acc0[4 * j], c0), phi(acc0[4 * j + 1], c0));
        const uint32_t hi = pack2(phi(acc0[4 * j + 2], c1), phi(acc0[4 * j + 3], c1));
        if (j & 1) { Q[j >> 1].z = lo; Q[j >> 1].w = hi; } else { Q[j >> 1].x = lo; Q[j >> 1].y = hi; }
      }
      Q[3].z = 0; Q[3].w = 0;
      STAMP(8);
      WAIT(BAR(B_KVB), 0);
      STAMP(9);
      float o[32];
      wg_fence();
      sfor<4>([&](auto I) { wgmma_rs_n64<OFF_KVB + I * 2048>(o, Q[I], d128, I != 0); });
      wg_commit();
            wg_wait<0>();
      if (ORED == 2) red_inc(cnt, tid & 159);
      acc_fence(o);
      const float da0 = rcpf(o[28] + c0.w), db0 = rcpf(o[29] + c0.w), da1 = rcpf(o[30] + c1.w), db1 = rcpf(o[31] + c1.w);
      uint32_t P[14];
#pragma unroll
      for (int j = 0; j < 7; j++) {
        const bool first = j < 2 || (j < 4 && tq < 3);
        const float s0 = first ? da0 : db0, s1 = first ? da1 : db1;
        P[2 * j] = pack2(o[4 * j] * s0, o[4 * j + 1] * s0);
        P[2 * j + 1] = pack2(o[4 * j + 2] * s1, o[4 * j + 3] * s1);
        if (0x53 >> j & 1) { P[2 * j] = tag(P[2 * j], par); P[2 * j + 1] = tag(P[2 * j + 1], par); }
      }
      auto publish = [&] {
#pragma unroll
        for (int h = 0; h < 2; h++) {
          st_rlx4(ob16 + 1792 * h, P[h], P[2 + h], P[4 + h], P[6 + h]);
          st_rlx2(ob8 + 1792 * h, P[8 + h], P[10 + h]);
          st_rlx1(ob4 + 1792 * h, P[12 + h]);
        }
      };
      if (!g) {
        if (ORED == 4) red_inc(cnt, lane);
        publish();
        if (ORED == 6) red_inc(cnt, lane);
        STAMP(11);
        if (lane == 0) mbar_arrive(BAR(B_OFREE));
        const int sec = min(lane, 27);
        uint32_t ta = sb + OFF_WO + wq4 * 3584 + sec * 32 + (0x3625410 >> (sec & 28) & 7) * 4;
        uint32_t gs = gsub - 2 * STG;
        const char* ol = olane + (A_WOC - A_O + (p - 2 * r) * 2 * STG);
        asm volatile("" : "+r"(ta), "+l"(ol));
#pragma unroll 1
        for (int n = 0; n < 12; n++) {
          WAIT(n < 4 ? BAR(B_WO) : BAR(B_WB - 4) + 8 * n, 0);
          STAMPD(max(n - 3, 1));
          RETRY(n < 4 ? 30 : n - 4, fixq(ta, gs, ol, par, budget));
          bar_arrive_id(4 + n);
          ol = n == 3 ? olane : ol + TILE;
          ta += TILE;
          gs += TILE;
        }
        bar_sync<3, 256>();
      } else {
        const uint32_t wa = sb + (lane >> 4) * 1024 + (lane & 7) * 128 + ((((2 * wq4 + (lane >> 3 & 1)) ^ lane) & 7) << 4);
        float hacc[64];
        {
          const uint32_t one = 0x3F80u << (lane * 4 & 16), m = tq == 0 ? 0xBF80BF80u : 0, id = (tid >> 3 ^ tq) & 15;
          uint4 E[4];
#pragma unroll
          for (int i = 0; i < 4; i++) {
            const uint32_t e = id == 4 * i ? one : 0;
            E[i] = make_uint4(e, 0, i < 3 ? 0 : m, i < 3 ? e : m);
            asm volatile("" : "+r"(E[i].x), "+r"(E[i].y), "+r"(E[i].z), "+r"(E[i].w));
          }
          wg_fence();
          sfor<8>([&](auto I) { wgmma_rk_n64<OFF_XS + I / 4 * 8192 + I % 4 * 32, I / 4 * 32>(hacc, E[I % 4], d128, I % 4 != 0); });
          wg_commit();
        }
        WAIT(BAR(B_WO), 0);
        sfor<28>([&](auto KS) {
          constexpr int ks = KS;
          if (ks == XW) {
            wg_wait<0>();
            acc_fence(hacc);
            if (lane == 0) mbar_arrive(BAR(B_OFREE));
          }
          if (ks == ORED1) red_inc(cnt + 1, lane);
          if (ks == OPUB) {
            WAIT(BAR(B_WO), 0);
            publish();
            STAMP(11);
            WAIT(BAR(B_WO), 0);
          }
          if (ks % 7 == 0) bar_sync<4 + ks / 7, 256>();
          A[ks] = ldsm4t(wa + OFF_WO + ks * 2048);
        });
        if (lane < 2) mbar_arrive(BAR(B_WOFREE) + (A[27].x & zero));
        if (OPUB >= 28) {
          if (OPUB == 29) WAIT(BAR(B_WOFREE), 0);
          if (OPUB == 30) WAIT(BAR(B_WB), 0);
          if (OPUB > 30) { const uint32_t t0 = clock(); while (clock() - t0 < OPUB); }
          if (ORED1 == 28) red_inc(cnt + 1, lane);
          publish();
          STAMP(11);
        }
        STAMP(10);
        uint32_t ma = sb + OFF_M + tq * 8;
        char* hb = oblk + (uint32_t)(FRAG_B - 2 * STG + (p >> 1) * TILE + (wq4 < 3 ? kh * 2048 + wq4 * 512 + lane * 16 : 1536 + kh * 256 + lane * 8));
        asm volatile("" : "+l"(hb));
        STAMP(16);
#pragma unroll 1
        for (int h = 0; h < 2; h++) {
          const uint64_t dh = dko + h * (2 * STG >> 4);
          sfor<4>([&](auto Q) {
            constexpr int q = Q;
            bar_sync_id(8 + 4 * h + q);
            STAMPD(1 + 4 * h + q);
            wg_fence();
            sfor<7>([&](auto I) { wgmma_rk_n64<OFF_G + q * TILE + I * 256>(hacc, A[7 * q + I], dh, 1); });
          });
          wg_commit();
          if (h) bar_sync<6, 160>();
          if (HRED == 4) red_inc(cnt + 2, lane);
          wg_wait<0>();
          if (HRED == 5) red_inc(cnt + 2, lane);
          acc_fence(hacc);
          STAMPD(12 + 2 * h);
          if (lane < 2) mbar_arrive(BAR(B_ORD) + 8 * h);
#pragma unroll
          for (int i = 0; i < 4; i++) {
            const float* a = hacc + 8 * i;
            st_rlx42(hb + 3584 * i, tag(transp(pack2(a[0], a[1])), par), transp(pack2(a[4], a[5])), transp(pack2(a[2], a[3])), transp(pack2(a[6], a[7])), wq4 - 3);
          }
          if (HRED == 6) red_inc(cnt + 2, lane);
          if (tid >= 224 && gq == 0) {
#pragma unroll
            for (int j = 0; j < 8; j++) sts2(ma + 32 * j, __float_as_uint(hacc[4 * j + 2]), __float_as_uint(hacc[4 * j + 3]));
          }
          STAMPD(13 + 2 * h);
          if (h) break;
          bar_arrive<3, 256>();
#pragma unroll
          for (int i = 0; i < 32; i++) hacc[i] = hacc[32 + i];
          acc_fence(hacc);
          hb += 2 * STG;
          ma += 256;
          cnt++;
        }
        bar_sync<5, 128>();
      }
      const char* const rb = olane + (FRAG_B + (p >> 1) * TILE);
#pragma unroll
      for (int i = 0; i < 3; i++) {
        const uint4 v = ld_rlx4(rb + kh * 2048 + 512 * i);
        R[4 * i] = v.x; R[4 * i + 1] = v.y; R[4 * i + 2] = v.z; R[4 * i + 3] = v.w;
      }
      const uint2 v = ld_rlx2(rb + 1536 + kh * 256 - lane * 8);
      R[12] = v.x; R[13] = v.y;
    }
    char* hdst = buf + (A_HH + cta * 2 * STG + warp * 3584) + (uint32_t)(lane * 16);
    {
#define GLU(gt, up, e) fmaf((up) * (e), tanhf_((gt) * (e)), (up) * (e))
      float acc[64];
      uint4 own[5];
#pragma unroll
      for (int i = 0; i < 5; i++) asm volatile("" : "=r"(own[i].x), "=r"(own[i].y), "=r"(own[i].z), "=r"(own[i].w));
      sfor<2>([&](auto Q) {
        WAIT(wb + 8 * Q, 1);
        STAMP(58);
        load7s<Q * TILE>(&A[7 * Q], gsub, gsub8);
      });
#pragma unroll 1
      for (int c = 0; c < 3; c++) {
        const uint32_t half = (c & 1) * 4;
        const uint64_t dc = d128 + half * (STG >> 4);
        if (GGATE && c == 1) WAIT(BAR(B_HFREE + 1 + GGATE), 0);
        sfor<4>([&](auto KQ) {
          constexpr int kq = KQ;
          if (c == 0) {
            if (kq < 2 && LDP == 0) WAIT(wb + 8 * (kq + 2), 1);
            RETRY(8 + kq + 4 * g, fix7t<A_H + kq * TILE>(&A[7 * kq], buf + r * 4 * STG, gsub, gsub8, par, budget));
            if (lane == 0) mbar_arrive(BAR(B_HFREE + kq / 2) + 16 * g);
            if (kq < 2 && LDP == 1) WAIT(wb + 8 * (kq + 2), 1);
            if (kq < 2 && LDP < 2) load7s<(kq + 2) % 4 * TILE>(&A[7 * ((kq + 2) % 4)], gsub, gsub8);
          }
          WAIT(BAR(B_FULL + kq) + 8 * half, c >> 1);
          STAMPD(30 + 4 * c + kq);
          wg_fence();
          sfor<7>([&](auto I) { wgmma_rs_n128<kq * STG + koff(I, 1024)>(acc, A[7 * kq + I], dc, kq + I != 0); });
          wg_commit();
          if (LDP == 2 && c == 0 && kq < 2) {
            WAIT(wb + 8 * (kq + 2), 1);
            load7s<(kq + 2) % 4 * TILE>(&A[7 * ((kq + 2) % 4)], gsub, gsub8);
          }
          if (c == 0 && (SQM >> 4 * kq & 15)) {
            sfor<4>([&](auto Q) { if (SQM >> 4 * kq + Q & 1) sqs(Q); });
            if (kq == 3) {
              rs0 = 0.5f * rsqf(rs0 * (1.f / DM) + 1e-5f);
              rs1 = 0.5f * rsqf(rs1 * (1.f / DM) + 1e-5f);
              asm volatile("" : "+f"(rs0), "+f"(rs1));
            }
          }
          if (kq > 0) {
            wg_wait<1>();
            if (lane == 0) mbar_arrive(BAR(B_EMPTY + kq - 1) + 8 * half);
          }
        });
        wg_wait<0>();
        acc_fence(acc);
        if (lane == 0) mbar_arrive(BAR(B_EMPTY + 3) + 8 * half);
        STAMPD(17 + c);
        constexpr int GO = SWAP ? 32 : 0, UO = SWAP ? 0 : 32;
        own[0] = own[4];
#pragma unroll
        for (int i = 0; i < 4; i++) {
          uint32_t w[4];
#pragma unroll
          for (int t = 0; t < 2; t++) {
            const int b = 8 * i + 4 * t;
            w[2 * t] = pack2(GLU(acc[GO + b], acc[UO + b], rs0), GLU(acc[GO + b + 1], acc[UO + b + 1], rs0));
            w[2 * t + 1] = pack2(GLU(acc[GO + b + 2], acc[UO + b + 2], rs1), GLU(acc[GO + b + 3], acc[UO + b + 3], rs1));
          }
          if (i == 3 && c == 1) hdst += STG - 3584;
          own[i + 1] = make_uint4(tag(w[0], par), w[1], w[2], w[3]);
          st_rlx4(hdst + i * 512, own[i + 1].x, w[1], w[2], w[3]);
        }
        hdst += 2048;
        red_inc(&g_cnt[C_ROW + r * 32 + 4 + 2 * (p & 6) + g], lane | c ^ 1);
      }
      float acct[32];
      sfor<2>([&](auto H) {
        constexpr int h = H;
        WAIT(BAR(B_FULL + 4 + h), 1);
        wg_fence();
        sfor<14>([&](auto I) { wgmma_rs_n64<(4 + h) * STG + I / 7 * (TILE / 2) + koff(I % 7, 512)>(acct, A[14 * h + I], d64, h + I != 0); });
        wg_commit();
      });
      auto ldh = [&](int k) {
        WAIT(wb + 8 * k, 0);
#pragma unroll
        for (int i = 0; i < 7; i++) A[7 * k + 7 + i] = lds4(gsub - g * STG + 2 * STG + k * TILE + i * 512);
      };
      wg_wait<1>();
      if (lane == 0) mbar_arrive(BAR(B_EMPTY + 4));
      if (HLD >= 1) ldh(0);
      wg_wait<0>();
      acc_fence(acct);
      if (lane == 0) mbar_arrive(BAR(B_EMPTY + 5));
      if (HLD == 2) ldh(1);
      STAMP(20);
      constexpr int GO = SWAP ? 16 : 0, UO = SWAP ? 0 : 16;
#pragma unroll
      for (int i = 0; i < 2; i++) {
        uint32_t w[4];
#pragma unroll
        for (int t = 0; t < 2; t++) {
          const int b = 8 * i + 4 * t;
          w[2 * t] = pack2(GLU(acct[GO + b], acct[UO + b], rs0), GLU(acct[GO + b + 1], acct[UO + b + 1], rs0));
          w[2 * t + 1] = pack2(GLU(acct[GO + b + 2], acct[UO + b + 2], rs1), GLU(acct[GO + b + 3], acct[UO + b + 3], rs1));
        }
        st_rlx4(hdst + i * 512, tag(w[0], par), w[1], w[2], w[3]);
        A[5 + i] = make_uint4(w[0], w[1], w[2], w[3]);
      }
#pragma unroll
      for (int i = 0; i < 5; i++) A[i] = own[i];
    }
    STAMP(21);
    {
      const char* const hnb = hdst + (1 - 2 * kh) * 2 * STG;
      uint32_t eye = tq == gq >> 1 ? 0x3F80u << (16 * (gq & 1)) : 0;
      auto add = [&](float (&a)[28], const uint32_t (&v)[14]) {
#pragma unroll
        for (int j = 0; j < 7; j++)
          asm("mma.sync.aligned.m16n8k8.row.col.f32.bf16.bf16.f32 {%0,%1,%2,%3}, {%4,%5}, {%6}, {%0,%1,%2,%3};"
              : "+f"(a[4 * j]), "+f"(a[4 * j + 1]), "+f"(a[4 * j + 2]), "+f"(a[4 * j + 3]) : "r"(v[2 * j]), "r"(v[2 * j + 1]), "r"(eye));
      };
      auto send = [&](float (&acc)[28], int x) {
        acc_fence(acc);
        char* const pd = buf + (A_PS + ((cta ^ 2 * x) * 6 + 3 * g + x - 1) * 7168 + (warp & 3) * 1792);
        uint32_t P[14];
#pragma unroll
        for (int j = 0; j < 14; j++) P[j] = pack2(acc[2 * j], acc[2 * j + 1]);
        publish7(pd + (uint32_t)(lane * 16), pd + 1536 + (uint32_t)(lane * 8), P, par);
        if (x < 3) red_inc(&g_cnt[C_PS + (cta ^ 2 * x) * 8 + g], lane);
      };
      sfor<4>([&](auto K) {
        constexpr int k = K;
        if (k > 1) {
          wg_wait<1>();
          if (lane == 0) mbar_arrive(BAR(B_EMPTY + k - 2));
        }
        if (k) RETRY(16 + k + 4 * g, fix7<-2560 - (k < 3) * STG>(&A[7 * k], k > 1 ? hnb : hdst, par, budget));
        if (k == 2 && lane < 2) mbar_arrive(BAR(B_HFREE + 1) + 16 * g);
        if (HLD == 0 ? k < 2 : HLD == 1 ? k == 1 : HLD == 3 ? k == 0 : false) {
          constexpr int kk = HLD ? 1 : k;
          WAIT(wb + 8 * kk, 0);
#pragma unroll
          for (int i = 0; i < 7; i++) A[7 * kk + 7 + i] = lds4(gsub - g * STG + 2 * STG + kk * TILE + i * 512);
        }
        if (k == 2) {
#pragma unroll
          for (int i = 0; i < 7; i++) A[21 + i] = ld_rlx4(hnb - 2560 + 512 * i);
        }
        WAIT(BAR(B_FULL + k), 0);
        STAMP(42 + k);
        wg_fence();
        sfor<7>([&](auto I) { wgmma_rs_n56<k * STG + I * 3584>(acc0, A[7 * k + I], d0, k + I != 0); });
        if (k == 3) wg_commit();
        sfor<7>([&](auto I) { wgmma_rs_n56<k * STG + I * 3584 + 896>(acc1, A[7 * k + I], d0, k + I != 0); });
        wg_commit();
      });
      wg_wait<1>();
      send(acc0, 1);
      sfor<4>([&](auto K) {
        constexpr int k = K, s = (k + 4) % 6;
        WAIT(BAR(B_FULL + s), k >= 2);
        STAMP(46 + k);
        wg_fence();
        sfor<7>([&](auto I) { wgmma_rs_n56<s * STG + I * 3584>(acc0, A[7 * k + I], d1, k + I != 0); });
        wg_commit();
        if (k == 0) {
          wg_wait<1>();
          send(acc1, 2);
          const float m0 = __uint_as_float(lds1(sb + OFF_M + warp * 64 + gq * 4)), m1 = __uint_as_float(lds1(sb + OFF_M + warp * 64 + gq * 4 + 32));
#pragma unroll
          for (int i = 0; i < 28; i++) acc1[i] = i & 2 ? -m1 : -m0;
          acc_fence(acc1);
        }
      });
      if (g) bar_arrive<7, 256>();
      wg_wait<0>();
      STAMP(22);
      send(acc0, 3);
      if (!g) bar_sync<7, 256>();
      uint32_t P[3][14];
      const char* const ps = buf + (A_PS + (cta * 6 + 3 * g) * 7168 + (warp & 3) * 1792) + (uint32_t)(lane * 16);
      const char* const ps8 = ps - lane * 8;
      auto fetch = [&](int x) {
#pragma unroll
        for (int i = 0; i < 3; i++) {
          const uint4 v = ld_rlx4(ps + 7168 * x + 512 * i);
          P[x][4 * i] = v.x; P[x][4 * i + 1] = v.y; P[x][4 * i + 2] = v.z; P[x][4 * i + 3] = v.w;
        }
        const uint2 v = ld_rlx2(ps8 + 7168 * x + 1536);
        P[x][12] = v.x; P[x][13] = v.y;
      };
      const uint32_t pss = sb + (6 + g) * STG + (warp & 3) * 1792;
      auto fetchs = [&] {
        WAIT(wb + 24, 0);
#pragma unroll
        for (int x = 0; x < 2; x++) {
          const uint32_t a = pss + TILE + 7168 * x;
#pragma unroll
          for (int i = 0; i < 3; i++) {
            const uint4 v = lds4(a + 512 * i + lane * 16);
            P[x][4 * i] = v.x; P[x][4 * i + 1] = v.y; P[x][4 * i + 2] = v.z; P[x][4 * i + 3] = v.w;
          }
          const uint2 v = lds2(a + 1536 + lane * 8);
          P[x][12] = v.x; P[x][13] = v.y;
        }
      };
      WAIT(BAR(B_FULL + 5), 0);
      wg_fence();
      sfor<28>([&](auto I) {
        if (I == FPOS) {
          fetchs();
          fetch(2);
          wg_fence();
        }
        wgmma_rs_n56<(I / 7 + 4) % 6 * STG + I % 7 * 3584 + 896>(acc1, A[I], d1, 1);
      });
      wg_commit();
      STAMP(23);
      WAIT(BAR(B_FULL + 5), 0);
      uint32_t ob = pss + 7168 + (lane & 15) * 112 + (lane & 16);
      char* op = out + (uint32_t)((128 * r + (tid >> 5) * 16 + (lane >> 3)) * 896 + 112 * p + (lane & 7) * 16);
      uint32_t ia = pss + 7168 + (lane >> 3) * 112 + (lane & 7) * 16;
      asm volatile("" : "+r"(ob), "+l"(op), "+r"(ia));
      auto check = [&](int x) {
#pragma unroll 1
        while (stale(xor2(P[x][0], P[x][4], par) | xor2(P[x][8], P[x][12], par), budget)) fetch(x);
      };
      check(0);
      check(1);
      uint32_t o[14];
      {
        wg_wait<0>();
        acc_fence(acc1);
        STAMP(24);
        add(acc1, R);
        add(acc1, P[0]);
        add(acc1, P[1]);
        acc_fence(acc1);
        WAIT(BAR(B_FULL + 5), 0);
        check(2);
        STAMP(57);
        add(acc1, P[2]);
#pragma unroll
        for (int j = 0; j < 14; j++) o[j] = pack2(acc1[2 * j], acc1[2 * j + 1]);
      }
#pragma unroll
      for (int i = 0; i < 3; i++)
        asm volatile("stmatrix.sync.aligned.m8n8.x4.shared.b16 [%0], {%1,%2,%3,%4};" ::"r"(ob + 32 * i), "r"(o[4 * i]), "r"(o[4 * i + 1]), "r"(o[4 * i + 2]), "r"(o[4 * i + 3]) : "memory");
      asm volatile("stmatrix.sync.aligned.m8n8.x2.shared.b16 [%0], {%1,%2};" ::"r"(ob + 96), "r"(o[12]), "r"(o[13]) : "memory");
      __syncwarp();
      {
        uint4 v[4];
#pragma unroll
        for (int i = 0; i < 4; i++) v[i] = lds4(ia + 448 * i);
        if ((lane & 7) < 7) {
#pragma unroll
          for (int i = 0; i < 4; i++) *(uint4*)(op + 3584 * i) = v[i];
        }
      }
      STAMP(25);
      SPINS(24 + g);
      GTIME(1);
    }
  }
}

typedef CUresult (*EncodeFn)(CUtensorMap*, CUtensorMapDataType, cuuint32_t, void*, const cuuint64_t*, const cuuint64_t*,
                             const cuuint32_t*, const cuuint32_t*, CUtensorMapInterleave, CUtensorMapSwizzle,
                             CUtensorMapL2promotion, CUtensorMapFloatOOBfill);

void make_map(EncodeFn enc, CUtensorMap* m, const void* p, int rank, const cuuint64_t* gd, const cuuint64_t* gs,
              const cuuint32_t* bd, CUtensorMapSwizzle sw) {
  const cuuint32_t es[5] = {1, 1, 1, 1, 1};
  ENC_CHECK(enc(m, CU_TENSOR_MAP_DATA_TYPE_BFLOAT16, rank, (void*)p, gd, gs, bd, es, CU_TENSOR_MAP_INTERLEAVE_NONE, sw,
                CU_TENSOR_MAP_L2_PROMOTION_NONE, CU_TENSOR_MAP_FLOAT_OOB_FILL_NONE));
}

}

extern "C" void kernel_launch(void* const* d_in, const int* in_sizes, int n_in, void* d_out, int out_size) {
  (void)in_sizes; (void)n_in; (void)out_size;
  static EncodeFn enc = nullptr;
  static char* buf = nullptr;
  if (!enc) {
    void* fn = nullptr;
    cudaDriverEntryPointQueryResult qr;
    cudaGetDriverEntryPoint("cuTensorMapEncodeTiled", &fn, cudaEnableDefault, &qr);
    enc = (EncodeFn)fn;
    cudaGetSymbolAddress((void**)&buf, g_buf);
    cudaFuncSetAttribute(fused_block_kernel<false>, cudaFuncAttributeMaxDynamicSharedMemorySize, SMEM_TOTAL);
    cudaFuncSetAttribute(fused_block_kernel<true>, cudaFuncAttributeMaxDynamicSharedMemorySize, SMEM_TOTAL);
  }
  const CUtensorMapSwizzle S128 = CU_TENSOR_MAP_SWIZZLE_128B;
  CUtensorMap mx, mqkv, mgu, mgu32;
  {
    cuuint64_t gd[3] = {64, SEQ, 7}, gs[2] = {DM * 2, 128};
    cuuint32_t bd[3] = {64, 16, 7};
    make_map(enc, &mx, d_in[0], 3, gd, gs, bd, S128);
  }
  {
    cuuint64_t gd[2] = {3 * DM, DM}, gs[1] = {3 * DM * 2};
    cuuint32_t bd[2] = {64, 112};
    make_map(enc, &mqkv, d_in[1], 2, gd, gs, bd, S128);
  }
  Pos pos = {};
  for (int i = 0; i < 32; i++) {
    const int c = 28 * (i >> 4) + 2 * (i >> 2 & 3) + 8 * (i & 3);
    pos.v[i >> 2] |= (uint32_t)(2 * (c < 32 ? (c & 6) * 4 + (c >> 3) * 2 : c < 48 ? 32 + (c & 2) * 4 + (c >> 1 & 6) : c)) << 8 * (i & 3);
  }
  const char *wg = (const char*)d_in[4], *wu = (const char*)d_in[5];
  const bool swap = wu < wg;
  const char* gub = swap ? wu : wg;
  const cuuint64_t gud = swap ? (cuuint64_t)(wg - wu) : (cuuint64_t)(wu - wg);
  {
    cuuint64_t gd[3] = {FF, DM, 2}, gs[2] = {FF * 2, gud};
    cuuint32_t bd[3] = {64, 112, 2};
    make_map(enc, &mgu, gub, 3, gd, gs, bd, S128);
  }
  {
    cuuint64_t gd[3] = {FF, DM, 2}, gs[2] = {FF * 2, gud};
    cuuint32_t bd[3] = {32, 224, 2};
    make_map(enc, &mgu32, gub, 3, gd, gs, bd, CU_TENSOR_MAP_SWIZZLE_64B);
  }
  (swap ? fused_block_kernel<true> : fused_block_kernel<false>)<<<128, 384, SMEM_TOTAL>>>(
      buf, (const char*)d_in[2], mn_desc(sb), mn_desc64(sb), mn_desc0(sb), mn_desc(sb + OFF_Q), mn_desc0(sb), k_desc0(sb), wg, wu, (const char*)d_in[6], (const char*)d_in[1], (char*)d_out, mx, mqkv, pos, mgu, mgu32);
}
```

```cpp
#include <cuda_runtime.h>
#include <cuda_bf16.h>
#include <cuda.h>
#include <stdint.h>
#include <stdio.h>
#include <utility>

#define SPIN_LIMIT (1 << 18)

namespace {

constexpr uint32_t sb = 1024;
constexpr int SEQ = 2048, DM = 448, FF = 1792;
constexpr int TILE = 14336;
constexpr int STG = 2 * TILE;
constexpr int SMEM_BAR = 8 * STG;
constexpr int SMEM_TOTAL = SMEM_BAR + 3072;
constexpr int OFF_X = 4 * STG, OFF_Q = 4 * STG, OFF_WO = 2 * STG, OFF_G = 4 * STG, OFF_PK = 6 * STG, OFF_KVB = OFF_PK + 32768, OFF_XS = OFF_KVB + 8192,
              OFF_M = SMEM_BAR + 512;
constexpr int B_XB = 0  , B_K = 8  , B_V = 12  , B_Q = 16, B_WO = 17, B_FULL = 18  , B_WB = 26  ,
              B_KVB = 34, B_WDOK = 35, B_INIT = 36,
              B_KFREE = 37, B_QFREE = 38, B_WOFREE = 39, B_OFREE = 40, B_HFREE = 41  , B_EMPTY = 45  , B_XFREE = 53, B_VFREE = 54,
              B_ORD = 55  ;

constexpr int KVR_B = 8704;
constexpr int FRAG_B = 16 * 4 * STG;
constexpr int A_CNT = 0, A_KVR = 24576, A_O = A_KVR + 8 * KVR_B + 2048, A_H = A_O + FRAG_B,
              A_HH = A_H + FRAG_B;
constexpr int HH_B = 128 * 2 * STG;
constexpr int A_PS = A_HH + HH_B;
constexpr int WDS = 25088;
constexpr int A_WD = A_PS + 128 * 3 * TILE;
constexpr int A_WOC = A_WD + 64 * WDS;

__device__ uint4 g_buf[(A_WOC + 16 * STG) / 16];
constexpr int C_ROW = 0, C_WD = 512, C_PS = 1024;
#define g_cnt ((unsigned*)buf + A_CNT / 4)
#define ENC_CHECK(x) (void)(x)
#define STAMP(i)
#define STAMPX(i)
#define GTIME(i)
#define STAMPP(i)
#define STAMPD(i)
#define DUMP(row)

__device__ __forceinline__ uint32_t smem_u32(const void* p) { return (uint32_t)__cvta_generic_to_shared(p); }
__device__ __forceinline__ void mbar_expect_tx(uint32_t bar, uint32_t bytes) {
  asm volatile("mbarrier.arrive.expect_tx.shared::cta.b64 _, [%0], %1;" ::"r"(bar), "r"(bytes) : "memory");
}
__device__ __forceinline__ void mbar_arrive(uint32_t bar) {
  asm volatile("mbarrier.arrive.shared::cta.b64 _, [%0];" ::"r"(bar) : "memory");
}
__device__ __forceinline__ void mbar_wait(uint32_t bar, uint32_t parity, int& budget) {
  asm volatile("{\n.reg .pred p;\nW:\nmbarrier.try_wait.parity.shared::cta.b64 p, [%1], %2;\n"
               "add.s32 %0, %0, -1;\nsetp.gt.and.s32 p, %0, 0, !p;\n@p bra W;\n}"
               : "+r"(budget) : "r"(bar), "r"(parity) : "memory");
}
__device__ __forceinline__ bool elect() {
  uint32_t v;
  asm volatile("{\n.reg .pred p;\nelect.sync _|p, 0xffffffff;\nselp.u32 %0, 1, 0, p;\n}" : "=r"(v));
  return v;
}
__device__ __forceinline__ void tma2d(uint32_t dst, const CUtensorMap* m, int c0, int c1, uint32_t bar) {
  asm volatile("cp.async.bulk.tensor.2d.shared::cluster.global.mbarrier::complete_tx::bytes [%0], [%1, {%3, %4}], [%2];"
               ::"r"(dst), "l"(m), "r"(bar), "r"(c0), "r"(c1) : "memory");
}
__device__ __forceinline__ void tma3d(uint32_t dst, const CUtensorMap* m, int c0, int c1, int c2, uint32_t bar) {
  asm volatile("cp.async.bulk.tensor.3d.shared::cluster.global.mbarrier::complete_tx::bytes [%0], [%1, {%3, %4, %5}], [%2];"
               ::"r"(dst), "l"(m), "r"(bar), "r"(c0), "r"(c1), "r"(c2) : "memory");
}
__device__ __forceinline__ void bulk_g2s(uint32_t dst, const void* src, uint32_t bytes, uint32_t bar) {
  asm volatile("cp.async.bulk.shared::cluster.global.mbarrier::complete_tx::bytes [%0], [%1], %2, [%3];"
               ::"r"(dst), "l"(src), "r"(bytes), "r"(bar) : "memory");
}
__device__ __forceinline__ void l2_prefetch(const void* p, uint32_t bytes) {
  asm volatile("cp.async.bulk.prefetch.L2.global [%0], %1;" ::"l"(p), "r"(bytes) : "memory");
}
__device__ __forceinline__ void prefetch_map(const CUtensorMap* m) {
  asm volatile("prefetch.tensormap [%0];" ::"l"(m) : "memory");
}
__device__ __forceinline__ void fence_async_smem() { asm volatile("fence.proxy.async.shared::cta;" ::: "memory"); }
template <int ID, int N> __device__ __forceinline__ void bar_arrive() { asm volatile("bar.arrive %0, %1;" ::"n"(ID), "n"(N) : "memory"); }
__device__ __forceinline__ void bar_arrive_id(int id) { asm volatile("bar.arrive %0, 256;" ::"r"(id) : "memory"); }
__device__ __forceinline__ void bar_sync_id(int id) { asm volatile("bar.sync %0, 256;" ::"r"(id) : "memory"); }
__device__ __forceinline__ void bar_sync_wg(int id) { asm volatile("bar.sync %0, 128;" ::"r"(id) : "memory"); }
template <int ID, int N> __device__ __forceinline__ void bar_sync() { asm volatile("bar.sync %0, %1;" ::"n"(ID), "n"(N) : "memory"); }
__device__ __forceinline__ void wg_fence() { asm volatile("wgmma.fence.sync.aligned;" ::: "memory"); }
__device__ __forceinline__ void wg_commit() { asm volatile("wgmma.commit_group.sync.aligned;" ::: "memory"); }
template <int N> __device__ __forceinline__ void wg_wait() { asm volatile("wgmma.wait_group.sync.aligned %0;" ::"n"(N) : "memory"); }
template <int N> __device__ __forceinline__ void acc_fence(float (&d)[N]) {
#pragma unroll
  for (int i = 0; i < N; i++) asm volatile("" : "+f"(d[i])::"memory");
}
constexpr uint64_t mn_desc(uint32_t addr) {
  return (uint64_t)((addr & 0x3FFFF) >> 4) | ((uint64_t)(TILE >> 4) << 16) | ((uint64_t)64 << 32) | ((uint64_t)1 << 62);
}
constexpr uint64_t mn_desc64(uint32_t addr) {
  return (uint64_t)((addr & 0x3FFFF) >> 4) | ((uint64_t)(TILE >> 4) << 16) | ((uint64_t)32 << 32) | ((uint64_t)2 << 62);
}
constexpr uint64_t mn_desc0(uint32_t addr) {
  return (uint64_t)((addr & 0x3FFFF) >> 4) | ((uint64_t)(1792 >> 4) << 16) | ((uint64_t)8 << 32);
}
constexpr uint64_t k_desc0(uint32_t addr) {
  return (uint64_t)((addr & 0x3FFFF) >> 4) | ((uint64_t)8 << 16) | ((uint64_t)(1792 >> 4) << 32);
}
__device__ __forceinline__ uint4 ld_rlx4(const void* p) {
  uint4 v;
  asm volatile("ld.relaxed.gpu.global.v4.u32 {%0,%1,%2,%3}, [%4];" : "=r"(v.x), "=r"(v.y), "=r"(v.z), "=r"(v.w) : "l"(p) : "memory");
  return v;
}
__device__ __forceinline__ uint2 ld_rlx2(const void* p) {
  uint2 v;
  asm volatile("ld.relaxed.gpu.global.v2.u32 {%0,%1}, [%2];" : "=r"(v.x), "=r"(v.y) : "l"(p) : "memory");
  return v;
}
__device__ __forceinline__ uint32_t ld_rlx1(const void* p) {
  uint32_t v;
  asm volatile("ld.relaxed.gpu.global.u32 %0, [%1];" : "=r"(v) : "l"(p) : "memory");
  return v;
}
__device__ __forceinline__ void st_rlx4(void* p, uint32_t a, uint32_t b, uint32_t c, uint32_t d) {
  asm volatile("st.relaxed.gpu.global.v4.u32 [%0], {%1,%2,%3,%4};" ::"l"(p), "r"(a), "r"(b), "r"(c), "r"(d) : "memory");
}
__device__ __forceinline__ void st_rlx2(void* p, uint32_t a, uint32_t b) {
  asm volatile("st.relaxed.gpu.global.v2.u32 [%0], {%1,%2};" ::"l"(p), "r"(a), "r"(b) : "memory");
}
__device__ __forceinline__ void st_rlx1(void* p, uint32_t a) {
  asm volatile("st.relaxed.gpu.global.u32 [%0], %1;" ::"l"(p), "r"(a) : "memory");
}
__device__ __forceinline__ void red_inc(unsigned* p, uint32_t skip) {
  asm volatile("{\n.reg .pred p;\nsetp.eq.u32 p, %1, 0;\n@p red.relaxed.gpu.global.inc.u32 [%0], 0xfffffffe;\n}" ::"l"(p), "r"(skip) : "memory");
}
__device__ __forceinline__ void red_release(unsigned* p) {
  asm volatile("red.release.gpu.global.inc.u32 [%0], 0xfffffffe;" ::"l"(p) : "memory");
}
__device__ __forceinline__ void st_rlx42(void* p, uint32_t a, uint32_t b, uint32_t c, uint32_t d, uint32_t all) {
  asm volatile("{\n.reg .pred p;\nsetp.ne.u32 p, %5, 0;\n@p st.relaxed.gpu.global.v4.u32 [%0], {%1,%2,%3,%4};\n"
               "@!p st.relaxed.gpu.global.v2.u32 [%0], {%1,%2};\n}" ::"l"(p), "r"(a), "r"(b), "r"(c), "r"(d), "r"(all) : "memory");
}
__device__ __forceinline__ void red_add4(void* p, float a, float b, float c, float d) {
  asm volatile("red.relaxed.gpu.global.add.v4.f32 [%0], {%1,%2,%3,%4};" ::"l"(p), "f"(a), "f"(b), "f"(c), "f"(d) : "memory");
}
__device__ __forceinline__ void eq_wait(const void* p, uint32_t target, int& budget) {
  asm volatile("{\n.reg .pred p;\n.reg .b32 v;\nW:\nld.relaxed.gpu.global.b32 v, [%1];\nadd.s32 %0, %0, -1;\n"
               "setp.gt.s32 p, %0, 0;\nsetp.gt.and.u32 p, v, %2, p;\n@p bra W;\n}"
               : "+r"(budget) : "l"(p), "r"(target) : "memory");
}
template <bool ACQ = false>
__device__ __forceinline__ void cnt_wait(const unsigned* p, uint32_t target, int& budget) {
  if (ACQ)
    asm volatile("{\n.reg .pred p;\n.reg .s32 v;\nW:\nld.acquire.gpu.global.s32 v, [%1];\nadd.s32 %0, %0, -1;\n"
                 "setp.gt.s32 p, %0, 0;\nsub.s32 v, v, %2;\nsetp.lt.and.s32 p, v, 0, p;\n@p bra W;\n}"
                 : "+r"(budget) : "l"(p), "r"(target) : "memory");
  else
  asm volatile("{\n.reg .pred p;\n.reg .s32 v;\nW:\nld.relaxed.gpu.global.s32 v, [%1];\nadd.s32 %0, %0, -1;\n"
               "setp.gt.s32 p, %0, 0;\nsub.s32 v, v, %2;\nsetp.lt.and.s32 p, v, 0, p;\n@p bra W;\n}"
               : "+r"(budget) : "l"(p), "r"(target) : "memory");
}
__device__ __forceinline__ uint32_t or3(uint32_t a, uint32_t b, uint32_t c) {
  uint32_t r;
  asm("lop3.b32 %0, %1, %2, %3, 0xfe;" : "=r"(r) : "r"(a), "r"(b), "r"(c));
  return r;
}
__device__ __forceinline__ uint32_t xor2(uint32_t a, uint32_t b, uint32_t f) {
  uint32_t r;
  asm("lop3.b32 %0, %1, %2, %3, 0x7e;" : "=r"(r) : "r"(a), "r"(b), "r"(f));
  return r;
}
__device__ __forceinline__ bool stale(uint32_t bad, int& budget, uint32_t mask = 1) {
  uint32_t v;
  asm volatile("{\n.reg .pred p;\n.reg .b32 t;\nand.b32 t, %2, %3;\nsetp.ne.u32 p, t, 0;\nadd.s32 %1, %1, -1;\n"
               "setp.gt.and.s32 p, %1, 0, p;\nvote.sync.any.pred p, p, 0xffffffff;\nselp.u32 %0, 1, 0, p;\n}"
               : "=r"(v), "+r"(budget) : "r"(bad), "r"(mask));
  return v;
}
__device__ __forceinline__ uint32_t tag(uint32_t w, uint32_t par) {
  uint32_t r;
  asm("lop3.b32 %0, %1, %2, 1, 0xd8;" : "=r"(r) : "r"(w), "r"(par));
  return r;
}
__device__ __forceinline__ void sts1(uint32_t a, uint32_t v) { asm volatile("st.shared.u32 [%0], %1;" ::"r"(a), "r"(v) : "memory"); }
__device__ __forceinline__ void sts2(uint32_t a, uint32_t x, uint32_t y) {
  asm volatile("st.shared.v2.u32 [%0], {%1,%2};" ::"r"(a), "r"(x), "r"(y) : "memory");
}
__device__ __forceinline__ void sts4(uint32_t a, uint32_t x, uint32_t y, uint32_t z, uint32_t w) {
  asm volatile("st.shared.v4.u32 [%0], {%1,%2,%3,%4};" ::"r"(a), "r"(x), "r"(y), "r"(z), "r"(w) : "memory");
}
__device__ __forceinline__ uint32_t lds1(uint32_t a) {
  uint32_t v;
  asm volatile("ld.shared.u32 %0, [%1];" : "=r"(v) : "r"(a) : "memory");
  return v;
}
__device__ __forceinline__ uint2 lds2(uint32_t a) {
  uint2 v;
  asm volatile("ld.shared.v2.u32 {%0,%1}, [%2];" : "=r"(v.x), "=r"(v.y) : "r"(a) : "memory");
  return v;
}
__device__ __forceinline__ uint4 lds4(uint32_t a) {
  uint4 v;
  asm volatile("ld.shared.v4.u32 {%0,%1,%2,%3}, [%4];" : "=r"(v.x), "=r"(v.y), "=r"(v.z), "=r"(v.w) : "r"(a) : "memory");
  return v;
}
__device__ __forceinline__ uint4 ldsm4(uint32_t a) {
  uint4 v;
  asm volatile("ldmatrix.sync.aligned.m8n8.x4.shared.b16 {%0,%1,%2,%3}, [%4];" : "=r"(v.x), "=r"(v.y), "=r"(v.z), "=r"(v.w) : "r"(a) : "memory");
  return v;
}
__device__ __forceinline__ uint4 ldsm4t(uint32_t a) {
  uint4 v;
  asm volatile("ldmatrix.sync.aligned.m8n8.x4.trans.shared.b16 {%0,%1,%2,%3}, [%4];" : "=r"(v.x), "=r"(v.y), "=r"(v.z), "=r"(v.w) : "r"(a) : "memory");
  return v;
}
__device__ __forceinline__ uint32_t pack2(float lo, float hi) {
  uint32_t r;
  asm("cvt.rn.bf16x2.f32 %0, %1, %2;" : "=r"(r) : "f"(hi), "f"(lo));
  return r;
}
__device__ __forceinline__ float bf_lo(uint32_t w) { return __uint_as_float(w << 16); }
__device__ __forceinline__ float bf_hi(uint32_t w) { return __uint_as_float(w & 0xFFFF0000u); }
__device__ __forceinline__ uint32_t sub2(uint32_t a, uint32_t b) {
  uint32_t r;
  asm volatile("sub.rn.bf16x2 %0, %1, %2;" : "=r"(r) : "r"(a), "r"(b));
  return r;
}
__device__ __forceinline__ uint32_t add2(uint32_t a, uint32_t b) {
  uint32_t r;
  asm("add.rn.bf16x2 %0, %1, %2;" : "=r"(r) : "r"(a), "r"(b));
  return r;
}
__device__ __forceinline__ uint32_t transp(uint32_t a) {
  uint32_t r;
  asm volatile("movmatrix.sync.aligned.m8n8.trans.b16 %0, %1;" : "=r"(r) : "r"(a));
  return r;
}
__device__ __forceinline__ uint32_t sq2(uint32_t a) {
  uint32_t r;
  asm volatile("mul.rn.bf16x2 %0, %1, %1;" : "=r"(r) : "r"(a));
  return r;
}
__device__ __forceinline__ uint32_t sq2(uint32_t a, uint32_t c) {
  uint32_t r;
  asm volatile("fma.rn.bf16x2 %0, %1, %1, %2;" : "=r"(r) : "r"(a), "r"(c));
  return r;
}
__device__ __forceinline__ uint4 ldg4(const void* p) {
  uint4 v;
  asm volatile("ld.global.nc.v4.u32 {%0,%1,%2,%3}, [%4];" : "=r"(v.x), "=r"(v.y), "=r"(v.z), "=r"(v.w) : "l"(p));
  return v;
}
__device__ __forceinline__ void mma16816(float (&c)[4], uint32_t a0, uint32_t a1, uint32_t a2, uint32_t a3, uint32_t b0, uint32_t b1) {
  asm("mma.sync.aligned.m16n8k16.row.col.f32.bf16.bf16.f32 {%0,%1,%2,%3}, {%4,%5,%6,%7}, {%8,%9}, {%0,%1,%2,%3};"
      : "+f"(c[0]), "+f"(c[1]), "+f"(c[2]), "+f"(c[3]) : "r"(a0), "r"(a1), "r"(a2), "r"(a3), "r"(b0), "r"(b1));
}
__device__ __forceinline__ void mma16816z(float (&c)[4], const uint4& a, uint32_t b0, uint32_t b1) {
  asm("mma.sync.aligned.m16n8k16.row.col.f32.bf16.bf16.f32 {%0,%1,%2,%3}, {%4,%5,%6,%7}, {%8,%9}, {%10,%10,%10,%10};"
      : "=f"(c[0]), "=f"(c[1]), "=f"(c[2]), "=f"(c[3]) : "r"(a.x), "r"(a.y), "r"(a.z), "r"(a.w), "r"(b0), "r"(b1), "f"(0.f));
}
__device__ __forceinline__ float ex2f(float x) { float r; asm("ex2.approx.ftz.f32 %0, %1;" : "=f"(r) : "f"(x)); return r; }
__device__ __forceinline__ float tanhf_(float x) { float r; asm("tanh.approx.f32 %0, %1;" : "=f"(r) : "f"(x)); return r; }
__device__ __forceinline__ float rsqf(float x) { float r; asm("rsqrt.approx.ftz.f32 %0, %1;" : "=f"(r) : "f"(x)); return r; }
__device__ __forceinline__ float lg2f(float x) { float r; asm("lg2.approx.ftz.f32 %0, %1;" : "=f"(r) : "f"(x)); return r; }
__device__ __forceinline__ float rcpf(float x) { float r; asm("rcp.approx.ftz.f32 %0, %1;" : "=f"(r) : "f"(x)); return r; }
struct PhiC { float x, y; uint32_t z, s, w; };
__device__ __forceinline__ uint32_t phi2(float a, float b, const PhiC& c) {
  uint32_t r;
  asm("{\n.reg .b32 e, u;\ncvt.rn.bf16x2.f32 e, %2, %1;\ncvt.rn.relu.bf16x2.f32 u, %4, %3;\nfma.rn.bf16x2 u, u, %5, %6;\n"
      "min.bf16x2 u, u, e;\nadd.rn.bf16x2 %0, u, %7;\n}"
      : "=r"(r) : "f"(ex2f(fmaf(a, c.x, c.y))), "f"(ex2f(fmaf(b, c.x, c.y))), "f"(a), "f"(b), "r"(c.z), "r"(c.s), "r"(c.w));
  return r;
}
__host__ __device__ constexpr long long koff(int i, int u) { return i < 3 ? 2 * i * u : i == 3 ? 6 * u + ((6ll * u) << 32) : (2 * i - 1) * u; }
__device__ __forceinline__ float shx(float v, int m) { return __shfl_xor_sync(0xffffffffu, v, m); }
template <int V> struct IC { __host__ __device__ constexpr operator int() const { return V; } };
template <class F, int... I> __device__ __forceinline__ void sfor_impl(F&& f, std::integer_sequence<int, I...>) {
  (f(IC<I>{}), ...);
}
template <int N, class F> __device__ __forceinline__ void sfor(F&& f) { sfor_impl(f, std::make_integer_sequence<int, N>{}); }

template <long long OFF, int RO = 0, int N>
__device__ __forceinline__ void wgmma_rs_n56(float (&d)[N], const uint4& a, uint64_t base, int scale_d) {
  asm volatile("{\n.reg .pred p;\n.reg .b64 t;\nsetp.ne.b32 p, %33, 0;\nadd.s64 t, %32, %34;\n"
    "wgmma.mma_async.sync.aligned.m64n56k16.f32.bf16.bf16 {%0, %1, %2, %3, %4, %5, %6, %7, %8, %9, %10, %11, %12, %13, %14, %15, %16, %17, %18, %19, %20, %21, %22, %23, %24, %25, %26, %27}, {%28, %29, %30, %31}, t, p, 1, 1, 1;\n}\n"
    : "+f"(d[RO + 0]), "+f"(d[RO + 1]), "+f"(d[RO + 2]), "+f"(d[RO + 3]), "+f"(d[RO + 4]), "+f"(d[RO + 5]), "+f"(d[RO + 6]), "+f"(d[RO + 7]), "+f"(d[RO + 8]), "+f"(d[RO + 9]), "+f"(d[RO + 10]), "+f"(d[RO + 11]), "+f"(d[RO + 12]), "+f"(d[RO + 13]), "+f"(d[RO + 14]), "+f"(d[RO + 15]), "+f"(d[RO + 16]), "+f"(d[RO + 17]), "+f"(d[RO + 18]), "+f"(d[RO + 19]), "+f"(d[RO + 20]), "+f"(d[RO + 21]), "+f"(d[RO + 22]), "+f"(d[RO + 23]), "+f"(d[RO + 24]), "+f"(d[RO + 25]), "+f"(d[RO + 26]), "+f"(d[RO + 27])
    : "r"(a.x), "r"(a.y), "r"(a.z), "r"(a.w), "l"(base), "r"(scale_d), "n"(OFF >> 4));
}
template <long long OFF, int RO = 0, int N>
__device__ __forceinline__ void wgmma_rs_n64(float (&d)[N], const uint4& a, uint64_t base, int scale_d) {
  asm volatile("{\n.reg .pred p;\n.reg .b64 t;\nsetp.ne.b32 p, %37, 0;\nadd.s64 t, %36, %38;\n"
    "wgmma.mma_async.sync.aligned.m64n64k16.f32.bf16.bf16 {%0, %1, %2, %3, %4, %5, %6, %7, %8, %9, %10, %11, %12, %13, %14, %15, %16, %17, %18, %19, %20, %21, %22, %23, %24, %25, %26, %27, %28, %29, %30, %31}, {%32, %33, %34, %35}, t, p, 1, 1, 1;\n}\n"
    : "+f"(d[RO + 0]), "+f"(d[RO + 1]), "+f"(d[RO + 2]), "+f"(d[RO + 3]), "+f"(d[RO + 4]), "+f"(d[RO + 5]), "+f"(d[RO + 6]), "+f"(d[RO + 7]), "+f"(d[RO + 8]), "+f"(d[RO + 9]), "+f"(d[RO + 10]), "+f"(d[RO + 11]), "+f"(d[RO + 12]), "+f"(d[RO + 13]), "+f"(d[RO + 14]), "+f"(d[RO + 15]), "+f"(d[RO + 16]), "+f"(d[RO + 17]), "+f"(d[RO + 18]), "+f"(d[RO + 19]), "+f"(d[RO + 20]), "+f"(d[RO + 21]), "+f"(d[RO + 22]), "+f"(d[RO + 23]), "+f"(d[RO + 24]), "+f"(d[RO + 25]), "+f"(d[RO + 26]), "+f"(d[RO + 27]), "+f"(d[RO + 28]), "+f"(d[RO + 29]), "+f"(d[RO + 30]), "+f"(d[RO + 31])
    : "r"(a.x), "r"(a.y), "r"(a.z), "r"(a.w), "l"(base), "r"(scale_d), "n"(OFF >> 4));
}
template <long long OFF, int RO = 0, int N>
__device__ __forceinline__ void wgmma_rk_n64(float (&d)[N], const uint4& a, uint64_t base, int scale_d) {
  asm volatile("{\n.reg .pred p;\n.reg .b64 t;\nsetp.ne.b32 p, %37, 0;\nadd.s64 t, %36, %38;\n"
    "wgmma.mma_async.sync.aligned.m64n64k16.f32.bf16.bf16 {%0, %1, %2, %3, %4, %5, %6, %7, %8, %9, %10, %11, %12, %13, %14, %15, %16, %17, %18, %19, %20, %21, %22, %23, %24, %25, %26, %27, %28, %29, %30, %31}, {%32, %33, %34, %35}, t, p, 1, 1, 0;\n}\n"
    : "+f"(d[RO + 0]), "+f"(d[RO + 1]), "+f"(d[RO + 2]), "+f"(d[RO + 3]), "+f"(d[RO + 4]), "+f"(d[RO + 5]), "+f"(d[RO + 6]), "+f"(d[RO + 7]), "+f"(d[RO + 8]), "+f"(d[RO + 9]), "+f"(d[RO + 10]), "+f"(d[RO + 11]), "+f"(d[RO + 12]), "+f"(d[RO + 13]), "+f"(d[RO + 14]), "+f"(d[RO + 15]), "+f"(d[RO + 16]), "+f"(d[RO + 17]), "+f"(d[RO + 18]), "+f"(d[RO + 19]), "+f"(d[RO + 20]), "+f"(d[RO + 21]), "+f"(d[RO + 22]), "+f"(d[RO + 23]), "+f"(d[RO + 24]), "+f"(d[RO + 25]), "+f"(d[RO + 26]), "+f"(d[RO + 27]), "+f"(d[RO + 28]), "+f"(d[RO + 29]), "+f"(d[RO + 30]), "+f"(d[RO + 31])
    : "r"(a.x), "r"(a.y), "r"(a.z), "r"(a.w), "l"(base), "r"(scale_d), "n"(OFF >> 4));
}
template <long long OFF, int RO = 0, int N>
__device__ __forceinline__ void wgmma_rs_n128(float (&d)[N], const uint4& a, uint64_t base, int scale_d) {
  asm volatile("{\n.reg .pred p;\n.reg .b64 t;\nsetp.ne.b32 p, %69, 0;\nadd.s64 t, %68, %70;\n"
    "wgmma.mma_async.sync.aligned.m64n128k16.f32.bf16.bf16 {%0, %1, %2, %3, %4, %5, %6, %7, %8, %9, %10, %11, %12, %13, %14, %15, %16, %17, %18, %19, %20, %21, %22, %23, %24, %25, %26, %27, %28, %29, %30, %31, %32, %33, %34, %35, %36, %37, %38, %39, %40, %41, %42, %43, %44, %45, %46, %47, %48, %49, %50, %51, %52, %53, %54, %55, %56, %57, %58, %59, %60, %61, %62, %63}, {%64, %65, %66, %67}, t, p, 1, 1, 1;\n}\n"
    : "+f"(d[RO + 0]), "+f"(d[RO + 1]), "+f"(d[RO + 2]), "+f"(d[RO + 3]), "+f"(d[RO + 4]), "+f"(d[RO + 5]), "+f"(d[RO + 6]), "+f"(d[RO + 7]), "+f"(d[RO + 8]), "+f"(d[RO + 9]), "+f"(d[RO + 10]), "+f"(d[RO + 11]), "+f"(d[RO + 12]), "+f"(d[RO + 13]), "+f"(d[RO + 14]), "+f"(d[RO + 15]), "+f"(d[RO + 16]), "+f"(d[RO + 17]), "+f"(d[RO + 18]), "+f"(d[RO + 19]), "+f"(d[RO + 20]), "+f"(d[RO + 21]), "+f"(d[RO + 22]), "+f"(d[RO + 23]), "+f"(d[RO + 24]), "+f"(d[RO + 25]), "+f"(d[RO + 26]), "+f"(d[RO + 27]), "+f"(d[RO + 28]), "+f"(d[RO + 29]), "+f"(d[RO + 30]), "+f"(d[RO + 31]), "+f"(d[RO + 32]), "+f"(d[RO + 33]), "+f"(d[RO + 34]), "+f"(d[RO + 35]), "+f"(d[RO + 36]), "+f"(d[RO + 37]), "+f"(d[RO + 38]), "+f"(d[RO + 39]), "+f"(d[RO + 40]), "+f"(d[RO + 41]), "+f"(d[RO + 42]), "+f"(d[RO + 43]), "+f"(d[RO + 44]), "+f"(d[RO + 45]), "+f"(d[RO + 46]), "+f"(d[RO + 47]), "+f"(d[RO + 48]), "+f"(d[RO + 49]), "+f"(d[RO + 50]), "+f"(d[RO + 51]), "+f"(d[RO + 52]), "+f"(d[RO + 53]), "+f"(d[RO + 54]), "+f"(d[RO + 55]), "+f"(d[RO + 56]), "+f"(d[RO + 57]), "+f"(d[RO + 58]), "+f"(d[RO + 59]), "+f"(d[RO + 60]), "+f"(d[RO + 61]), "+f"(d[RO + 62]), "+f"(d[RO + 63])
    : "r"(a.x), "r"(a.y), "r"(a.z), "r"(a.w), "l"(base), "r"(scale_d), "n"(OFF >> 4));
}
template <int OFFA, int OFFB>
__device__ __forceinline__ void wgmma_ss_n64(float (&d)[32], uint64_t basea, uint64_t baseb, int scale_d) {
  asm volatile("{\n.reg .pred p;\n.reg .b64 t, u;\nsetp.ne.b32 p, %34, 0;\nadd.s64 t, %32, %35;\nadd.s64 u, %33, %36;\n"
    "wgmma.mma_async.sync.aligned.m64n64k16.f32.bf16.bf16 {%0, %1, %2, %3, %4, %5, %6, %7, %8, %9, %10, %11, %12, %13, %14, %15, %16, %17, %18, %19, %20, %21, %22, %23, %24, %25, %26, %27, %28, %29, %30, %31}, t, u, p, 1, 1, 1, 1;\n}\n"
    : "+f"(d[0]), "+f"(d[1]), "+f"(d[2]), "+f"(d[3]), "+f"(d[4]), "+f"(d[5]), "+f"(d[6]), "+f"(d[7]), "+f"(d[8]), "+f"(d[9]), "+f"(d[10]), "+f"(d[11]), "+f"(d[12]), "+f"(d[13]), "+f"(d[14]), "+f"(d[15]), "+f"(d[16]), "+f"(d[17]), "+f"(d[18]), "+f"(d[19]), "+f"(d[20]), "+f"(d[21]), "+f"(d[22]), "+f"(d[23]), "+f"(d[24]), "+f"(d[25]), "+f"(d[26]), "+f"(d[27]), "+f"(d[28]), "+f"(d[29]), "+f"(d[30]), "+f"(d[31])
    : "l"(basea), "l"(baseb), "r"(scale_d), "n"(OFFA >> 4), "n"(OFFB >> 4));
}

__device__ __forceinline__ void publish7(char* b16, char* b8, const uint32_t (&P)[14], uint32_t par) {
  st_rlx4(b16, tag(P[0], par), P[1], P[2], P[3]);
  st_rlx4(b16 + 512, tag(P[4], par), P[5], P[6], P[7]);
  st_rlx4(b16 + 1024, tag(P[8], par), P[9], P[10], P[11]);
  st_rlx2(b8, tag(P[12], par), P[13]);
}
template <int GOFF>
__device__ __forceinline__ void fix7(uint4* v, const char* g, uint32_t par, int& budget) {
  asm volatile("{\n.reg .pred p;\n.reg .b32 t, w<4>;\nsetp.eq.s32 p, %28, 0;\nC:\n@!p bra.uni L;\nadd.s32 %28, %28, -1;\n"
               "ld.relaxed.gpu.global.v4.u32 {%0,%1,%2,%3}, [%29+%31+0];\n"
               "ld.relaxed.gpu.global.v4.u32 {%4,%5,%6,%7}, [%29+%31+512];\n"
               "ld.relaxed.gpu.global.v4.u32 {%8,%9,%10,%11}, [%29+%31+1024];\n"
               "ld.relaxed.gpu.global.v4.u32 {%12,%13,%14,%15}, [%29+%31+1536];\n"
               "ld.relaxed.gpu.global.v4.u32 {%16,%17,%18,%19}, [%29+%31+2048];\n"
               "ld.relaxed.gpu.global.v4.u32 {%20,%21,%22,%23}, [%29+%31+2560];\n"
               "ld.relaxed.gpu.global.v4.u32 {%24,%25,%26,%27}, [%29+%31+3072];\n"
               "L:\nlop3.b32 w0, %0, %4, %30, 0x7e;\nlop3.b32 w1, %8, %12, %30, 0x7e;\nlop3.b32 w2, %16, %20, %30, 0x7e;\nxor.b32 w3, %24, %30;\n"
               "lop3.b32 t, w0, w1, w2, 0xfe;\nlop3.b32 t, t, w3, 1, 0xa8;\n"
               "setp.ne.u32 p, t, 0;\nsetp.gt.and.s32 p, %28, 0, p;\nvote.sync.any.pred p, p, 0xffffffff;\n@p bra.uni C;\n}"
               : "+r"(v[0].x), "+r"(v[0].y), "+r"(v[0].z), "+r"(v[0].w), "+r"(v[1].x), "+r"(v[1].y), "+r"(v[1].z), "+r"(v[1].w), "+r"(v[2].x), "+r"(v[2].y), "+r"(v[2].z), "+r"(v[2].w), "+r"(v[3].x), "+r"(v[3].y), "+r"(v[3].z), "+r"(v[3].w), "+r"(v[4].x), "+r"(v[4].y), "+r"(v[4].z), "+r"(v[4].w), "+r"(v[5].x), "+r"(v[5].y), "+r"(v[5].z), "+r"(v[5].w), "+r"(v[6].x), "+r"(v[6].y), "+r"(v[6].z), "+r"(v[6].w), "+r"(budget)
               : "l"(g), "r"(par), "n"(GOFF) : "memory");
}
template <int SOFF>
__device__ __forceinline__ void load7s(uint4* v, uint32_t s, uint32_t s8) {
  asm volatile("ld.shared.v4.u32 {%0,%1,%2,%3}, [%28+%30+0];\n"
               "ld.shared.v4.u32 {%4,%5,%6,%7}, [%28+%30+512];\n"
               "ld.shared.v4.u32 {%8,%9,%10,%11}, [%28+%30+1024];\n"
               "ld.shared.v2.u32 {%12,%13}, [%29+%30+1536];\nld.shared.v2.u32 {%14,%15}, [%29+%30+1792];\n"
               "ld.shared.v4.u32 {%16,%17,%18,%19}, [%28+%30+2048];\n"
               "ld.shared.v4.u32 {%20,%21,%22,%23}, [%28+%30+2560];\n"
               "ld.shared.v4.u32 {%24,%25,%26,%27}, [%28+%30+3072];\n"
               : "=r"(v[0].x), "=r"(v[0].y), "=r"(v[0].z), "=r"(v[0].w), "=r"(v[1].x), "=r"(v[1].y), "=r"(v[1].z), "=r"(v[1].w), "=r"(v[2].x), "=r"(v[2].y), "=r"(v[2].z), "=r"(v[2].w), "=r"(v[3].x), "=r"(v[3].y), "=r"(v[3].z), "=r"(v[3].w), "=r"(v[4].x), "=r"(v[4].y), "=r"(v[4].z), "=r"(v[4].w), "=r"(v[5].x), "=r"(v[5].y), "=r"(v[5].z), "=r"(v[5].w), "=r"(v[6].x), "=r"(v[6].y), "=r"(v[6].z), "=r"(v[6].w)
               : "r"(s), "r"(s8), "n"(SOFF) : "memory");
}
template <int GOFF>
__device__ __forceinline__ void fix7t(uint4* v, const char* base, uint32_t s, uint32_t s8, uint32_t par, int& budget) {
  asm volatile("{\n.reg .pred p;\n.reg .b32 t, w<4>;\n.reg .b64 g, h;\nsetp.eq.s32 p, %28, 0;\nC:\n@!p bra.uni L;\nadd.s32 %28, %28, -1;\n"
               "mad.wide.u32 g, %32, 1, %29;\nmad.wide.u32 h, %33, 1, %29;\n"
               "ld.relaxed.gpu.global.v4.u32 {%0,%1,%2,%3}, [g+%31+0];\n"
               "ld.relaxed.gpu.global.v4.u32 {%4,%5,%6,%7}, [g+%31+512];\n"
               "ld.relaxed.gpu.global.v4.u32 {%8,%9,%10,%11}, [g+%31+1024];\n"
               "ld.relaxed.gpu.global.v2.u32 {%12,%13}, [h+%31+1536];\nld.relaxed.gpu.global.v2.u32 {%14,%15}, [h+%31+1792];\n"
               "ld.relaxed.gpu.global.v4.u32 {%16,%17,%18,%19}, [g+%31+2048];\n"
               "ld.relaxed.gpu.global.v4.u32 {%20,%21,%22,%23}, [g+%31+2560];\n"
               "ld.relaxed.gpu.global.v4.u32 {%24,%25,%26,%27}, [g+%31+3072];\nL:\n"
               "lop3.b32 w0, %0, %4, %30, 0x7e;\nlop3.b32 w1, %8, %12, %30, 0x7e;\nlop3.b32 w2, %14, %16, %30, 0x7e;\nlop3.b32 w3, %20, %24, %30, 0x7e;\n"
               "lop3.b32 t, w0, w1, w2, 0xfe;\nlop3.b32 t, t, w3, 1, 0xa8;\n"
               "setp.ne.u32 p, t, 0;\nsetp.gt.and.s32 p, %28, 0, p;\nvote.sync.any.pred p, p, 0xffffffff;\n@p bra.uni C;\n}"
               : "+r"(v[0].x), "+r"(v[0].y), "+r"(v[0].z), "+r"(v[0].w), "+r"(v[1].x), "+r"(v[1].y), "+r"(v[1].z), "+r"(v[1].w), "+r"(v[2].x), "+r"(v[2].y), "+r"(v[2].z), "+r"(v[2].w), "+r"(v[3].x), "+r"(v[3].y), "+r"(v[3].z), "+r"(v[3].w), "+r"(v[4].x), "+r"(v[4].y), "+r"(v[4].z), "+r"(v[4].w), "+r"(v[5].x), "+r"(v[5].y), "+r"(v[5].z), "+r"(v[5].w), "+r"(v[6].x), "+r"(v[6].y), "+r"(v[6].z), "+r"(v[6].w), "+r"(budget)
               : "l"(base), "r"(par), "n"(GOFF - (int)sb - OFF_G), "r"(s), "r"(s8) : "memory");
}
__device__ __forceinline__ void fixq(uint32_t a, uint32_t s, const char* g, uint32_t par, int& budget) {
  asm volatile("{\n.reg .pred p;\n.reg .b32 t, u, w<28>;\nsetp.eq.s32 p, %0, 0;\n"
               "ld.shared.u32 w0, [%1];\nld.shared.u32 w1, [%1+896];\nld.shared.u32 w2, [%1+1792];\nld.shared.u32 w3, [%1+2688];\n"
               "C:\n@!p bra.uni L;\nadd.s32 %0, %0, -1;\n"
               "ld.relaxed.gpu.global.v4.u32 {w0,w1,w2,w3}, [%3+0];\n"
               "ld.relaxed.gpu.global.v4.u32 {w4,w5,w6,w7}, [%3+512];\n"
               "ld.relaxed.gpu.global.v4.u32 {w8,w9,w10,w11}, [%3+1024];\n"
               "ld.relaxed.gpu.global.v4.u32 {w12,w13,w14,w15}, [%3+1536];\n"
               "ld.relaxed.gpu.global.v4.u32 {w16,w17,w18,w19}, [%3+2048];\n"
               "ld.relaxed.gpu.global.v4.u32 {w20,w21,w22,w23}, [%3+2560];\n"
               "ld.relaxed.gpu.global.v4.u32 {w24,w25,w26,w27}, [%3+3072];\n"
               "st.shared.v4.u32 [%2+0], {w0,w1,w2,w3};\n"
               "st.shared.v4.u32 [%2+512], {w4,w5,w6,w7};\n"
               "st.shared.v4.u32 [%2+1024], {w8,w9,w10,w11};\n"
               "st.shared.v4.u32 [%2+1536], {w12,w13,w14,w15};\n"
               "st.shared.v4.u32 [%2+2048], {w16,w17,w18,w19};\n"
               "st.shared.v4.u32 [%2+2560], {w20,w21,w22,w23};\n"
               "st.shared.v4.u32 [%2+3072], {w24,w25,w26,w27};\n"
               "fence.proxy.async.shared::cta;\nbar.warp.sync 0xffffffff;\n"
               "ld.shared.u32 w0, [%1];\nld.shared.u32 w1, [%1+896];\nld.shared.u32 w2, [%1+1792];\nld.shared.u32 w3, [%1+2688];\n"
               "L:\n"
               "lop3.b32 t, w0, w1, %4, 0x7e;\nlop3.b32 u, w2, w3, %4, 0x7e;\nlop3.b32 t, t, u, 1, 0xa8;\n"
               "setp.ne.u32 p, t, 0;\nsetp.gt.and.s32 p, %0, 0, p;\nvote.sync.any.pred p, p, 0xffffffff;\n@p bra.uni C;\n}"
               : "+r"(budget)
               : "r"(a), "r"(s), "l"(g), "r"(par) : "memory");
}
#define SPINS(i)
#define RETRY(i, ...) __VA_ARGS__
#define BAR(i) (sb + SMEM_BAR + 8 * (i))
#define WAIT(b, ph) mbar_wait(b, ph, budget)

struct Pos { uint32_t v[8]; };
template <bool SWAP>
__global__ void __launch_bounds__(384, 1)
fused_block_kernel(char* const buf, const char* __restrict__ wo, const uint64_t d128, const uint64_t d64, const uint64_t d0,
                   const uint64_t dq, const uint64_t d1, const uint64_t dko,
                   const char* __restrict__ wg, const char* __restrict__ wu, const char* __restrict__ wd, const char* __restrict__ wq, char* __restrict__ out,
                   const __grid_constant__ CUtensorMap map_x, const __grid_constant__ CUtensorMap map_qkv,
                   const __grid_constant__ Pos pos, const __grid_constant__ CUtensorMap map_gu,
                   const __grid_constant__ CUtensorMap map_gu32) {
  extern __shared__ __align__(1024) uint8_t smem[];
  const int tid = threadIdx.x, lane = tid & 31;
  const int warp = __shfl_sync(0xffffffffu, tid >> 5, 0);
  const int cta = (blockIdx.x & 56) * 2 + (blockIdx.x & 1) * 8 + (blockIdx.x & 6) + (blockIdx.x >> 6), r = cta >> 3, p = cta & 7;
  const int kh = p & 1;
  const int wcol = 56 * p - 8 * kh;
  int budget = SPIN_LIMIT;
  const uint32_t zero = d0 >> 48;
  STAMP(0);
  if (warp >= 8) {
    {
      const uint32_t c = 0x100000 - (tid < 256 + B_KVB ? 1 : tid < 256 + B_KFREE ? 4 : tid == 256 + B_XFREE ? 12 : 8);
      if (tid < 320) sts2(BAR(tid - 256), c << 1, c << 11);
      fence_async_smem();
      bar_arrive<0, 384>();
      bar_sync<2, 128>();
#pragma unroll
      for (int i = warp - 8; i < warp; i += 4) {
        if (elect()) {
          mbar_expect_tx(BAR(B_XB + i), TILE);
          tma3d(sb + OFF_X + i * TILE, &map_x, 0, 128 * r + 16 * i, 0, BAR(B_XB + i));
        }
      }
      prefetch_map(&map_qkv);
    }
    STAMPP(60);
    asm volatile("setmaxnreg.dec.sync.aligned.u32 56;");
    STAMPP(63);
    if (warp == 11) {
#pragma unroll 1
      for (int j = 0; j < 8; j++) {
        if (elect()) {
          mbar_expect_tx(BAR(B_K + j), TILE);
          tma2d(sb + (j ^ 4) * TILE, &map_qkv, wcol + DM + DM * (j >> 2), 112 * (j & 3), BAR(B_K + j));
        }
      }
    }
  }
  int role = warp;
  asm volatile("" : "+r"(role));
  if (role >= 8) {
    STAMPP(59);
    const int w = warp - 8, t = tid - 256;
    STAMPP(61);
    char* const kvr = buf + (A_KVR + p * KVR_B);
    if (t < 34) st_rlx4(kvr + (uint32_t)((r * 34 + t) * 16), 0, 0, 0, (t & 1) || ((r & 3) * 34 + t >> 3) == 8 ? 0xC1800000u : 0u);
    const uint32_t e1 = (ld_rlx1(&g_cnt[C_ROW + r * 32]) >> 5) + 1;
    const int krow = min(cta, 111) * 4 + w;
    const char* wrow = wo + (uint32_t)(krow * (DM * 2) + (lane - (lane >> 3)) * 16);
    uint4 u0 = make_uint4(0, 0, 0, 0), u1 = u0;
    if ((lane & 7) < 7) {
      u0 = ldg4(wrow);
      u1 = ldg4(wrow + 448);
    }
    if (lane < 7) asm volatile("prefetch.global.L2 [%0];" ::"l"(wq + (uint32_t)(krow * (DM * 6) + lane * 128)));
    GTIME(0);
    STAMPP(62);
    {
      float c[4];
      mma16816z(c, u0, 0x3F803F80u, 0x3F803F80u);
      mma16816(c, u1.x, u1.y, u1.z, u1.w, 0x3F803F80u, 0x3F803F80u);
      float s = c[0] + c[2];
      s += shx(s, 4); s += shx(s, 8); s += shx(s, 16);
      const uint32_t nw = pack2(s * (1.f / DM), s * (1.f / DM));
      char* const wc = buf + (A_WOC + krow * 128) + (uint32_t)((lane >> 3) * 2 * STG + (((lane ^ krow) & 7) << 4));
      st_rlx4(wc, tag(sub2(u0.x, nw), e1), tag(sub2(u0.y, nw), e1), tag(sub2(u0.z, nw), e1), tag(sub2(u0.w, nw), e1));
      st_rlx4(wc + 8 * STG, tag(sub2(u1.x, nw), e1), tag(sub2(u1.y, nw), e1), tag(sub2(u1.z, nw), e1), tag(sub2(u1.w, nw), e1));
    }
    if (smem_u32(smem) != sb) __trap();
    STAMPP(19);
    uint4 xs[8];
    {
      const uint32_t G = 7 * p + (lane & 7), a = sb + OFF_X + w * TILE + (G >> 3) * 2048 + (lane >> 3) * 128 + (((G ^ lane >> 3) & 7) << 4), b = a ^ 64;
#pragma unroll
      for (int i = 0; i < 8; i++) {
        if (i % 4 == 0) WAIT(BAR(B_XB + w + (i & 4)), 0);
        xs[i] = lds4((i & 1 ? b : a) + (i & 4) * TILE + (i & 3) * 512);
      }
    }
    if (lane == 0) mbar_arrive(BAR(B_XFREE) + (xs[7].x & zero));
    WAIT(BAR(B_XFREE), 0);
    if (w == 0 && elect()) {
      mbar_expect_tx(BAR(B_Q), 2 * STG);
#pragma unroll 1
      for (int j = 0; j < 4; j++) tma2d(sb + OFF_Q + j * TILE, &map_qkv, wcol, 112 * j, BAR(B_Q));
    }
#pragma unroll
    for (int i = 0; i < 4; i++) sts4(sb + OFF_KVB + 2048 * i + t * 16, 0, 0, 0, 0);
    if ((lane & 7) < 7) {
      const uint32_t a = sb + OFF_XS + w * 2048 + (lane >> 3) * 128 + (((lane ^ lane >> 3) & 7) << 4), b = a ^ 64;
#pragma unroll
      for (int i = 0; i < 8; i++) sts4((i & 1 ? b : a) + (i & 4) * 2048 + (i & 3) * 512, xs[i].x, xs[i].y, xs[i].z, xs[i].w);
    }
    const char* const kvt = kvr + (uint32_t)(w * 2176 + (lane & 28) * 16 + (t & 1) * 32 + (t & 2) * 8);
    const char* const kvz = kvr + (uint32_t)(w * 2176 + 1024 + (lane & 28) * 4);
    const char* const kvh = kvt + (uint32_t)(1152 + (lane & 28) * 16);
    {
      uint32_t c[3];
      bool first = w == 0;
#pragma unroll 1
      do {
#pragma unroll
        for (int i = 0; i < 2; i++) c[i] = ld_rlx1(kvr + (uint32_t)(t * 32) + 4096 * i + 28);
        c[2] = ld_rlx1(kvr + (uint32_t)((t & 15) * 32) + 8192 + 28);
        if (first) {
          WAIT(BAR(B_KFREE), 0);
          STAMPX(6);
          if (elect()) {
            mbar_expect_tx(BAR(B_WO), 2 * STG);
            bulk_g2s(sb + OFF_WO, buf + (A_WOC + p * 2 * STG), 2 * STG, BAR(B_WO));
          }
        }
        first = false;
      } while (stale(~(c[0] & c[1] & c[2]), budget, 0x80000000u));
    }
    if (lane == 0) mbar_arrive(BAR(B_INIT));
    STAMPP(1);
    if (w == 2 && elect()) {
      prefetch_map(&map_gu);
      l2_prefetch(wg + cta * 12544, 12544);
      l2_prefetch(wu + cta * 12544, 12544);
      l2_prefetch(wd + cta * 12544, 12544);
      prefetch_map(&map_gu32);
    }
    WAIT(BAR(B_VFREE), 0);
    bar_sync<2, 128>();
    const int gq = lane >> 2, tq = lane & 3, k = 28 * (w >> 1) + 16 * (w & 1) + gq;
    const uint32_t row = sb + OFF_KVB + k * 128, sw = (k & 7) << 4;
    uint32_t ad[4];
    {
      const uint32_t t4 = pos.v[(w & 2) * 2 + tq] ^ (sw | row & 128) * 0x01010101u;
#pragma unroll
      for (int q = 0; q < 4; q++) {
        ad[q] = __byte_perm(row, t4, 0x3214 + q);
        asm volatile("" : "+r"(ad[q]));
      }
    }
    const bool lo = !(w & 1) || gq < 4;
    uint32_t m1 = tq & 2 ? ~0u : 0, m2 = lo ? m1 : 0;
    asm volatile("" : "+r"(m1), "+r"(m2));
    eq_wait(kvr + w * 2176 + 1152 + 28, 0xC0800000, budget);
    STAMPX(2);
    {
      uint4 v[5];
#pragma unroll 1
      do {
#pragma unroll
        for (int i = 0; i < 4; i++) v[i] = ld_rlx4(i < 2 ? kvt + 512 * i : kvh + 64 * i - 128);
        v[4] = ld_rlx4(kvz);
      } while (stale(or3((v[0].w | v[1].w) & m1, (v[2].w | v[3].w) & m2, v[4].w), budget, ~0u));
      STAMPX(3);
#define F(x) __uint_as_float(x)
      const uint32_t a[4] = {pack2(F(v[0].x), F(v[0].y)), pack2(F(v[0].z), F(m1 ? v[1].z : v[0].w)), pack2(F(v[1].x), F(v[1].y)), pack2(F(v[1].z), F(v[1].w))};
      const uint32_t b[4] = {pack2(F(v[2].x), F(v[2].y)), pack2(F(v[2].z), F(m1 ? v[3].z : v[2].w)), pack2(F(v[3].x), F(v[3].y)), pack2(F(v[3].z), F(v[3].w))};
#pragma unroll
      for (int q = 0; q < 4; q++) {
        if (q < 3 || tq < 2) {
          sts1(ad[q], a[q]);
          if (lo) sts1(ad[q] + 1024, b[q]);
        }
      }
      if (tq == 2) {
        const uint32_t z = pack2(F(v[4].x), F(v[4].y));
        const uint32_t za = __byte_perm(z, 0, w & 2 ? 0x1044 : 0x4410), zb = __byte_perm(z, 0, w & 2 ? 0x3244 : 0x4432);
        sts4(row + (112 ^ sw), za, za, za, za);
        if (lo) sts4(row + 1024 + (112 ^ sw), zb, zb, zb, zb);
      }
      fence_async_smem();
      __syncwarp();
      if (lane == 0) mbar_arrive(BAR(B_KVB));
      STAMPP(4);
    }
    if (w == 0) {
#pragma unroll 1
      for (int u = 0; u < 22; u++) {
        const int s = u < 14 ? u & 7 : u < 20 ? u - 14 : u - 20;
        if (u == 2 || u == 14) WAIT(BAR(u == 2 ? B_WB + 3 : B_WDOK), 0);
        WAIT(BAR(B_KFREE + s) + (u >= 8 ? 64 : 0), u >= 14 && u < 20);
        STAMPP(20 + u);
        if (elect()) {
          mbar_expect_tx(BAR(B_FULL + s), u < 14 ? STG : WDS);
          if (u < 12) tma3d(sb + s * STG, &map_gu, 224 * p + 32 * kh + 64 * (u >> 2), 112 * (u & 3), 0, BAR(B_FULL + s));
          else if (u < 14) tma3d(sb + s * STG, &map_gu32, 224 * p + 192 - 192 * kh, 224 * (u - 12), 0, BAR(B_FULL + s));
          else bulk_g2s(sb + s * STG, buf + (A_WD + (p * 8 + u - 14) * WDS), WDS, BAR(B_FULL + s));
        }
      }
      SPINS(26);
    } else {
#pragma unroll 1
      for (int j = 0; j < (w == 1 ? 4 : 0); j++) {
        WAIT(BAR(j < 2 ? B_QFREE + 2 * j : B_ORD - 2 + j), 0);
        const char* src = buf + (uint32_t)(A_O + (j >> 1) * FRAG_B + (r * 2 + (j & 1)) * 2 * STG);
        uint32_t dst = sb + OFF_G + (j & 1) * 2 * STG, full = BAR(B_WB + 4 * (j & 1));
        if (lane < 4) mbar_expect_tx(full + 8 * lane, TILE);
        asm volatile("" : "+l"(src), "+r"(dst), "+r"(full));
        cnt_wait(&g_cnt[C_ROW + r * 32 + j], e1 * 32, budget);
        STAMPX(50 + 2 * j);
#pragma unroll 1
        do {
          if (elect()) bulk_g2s(dst, src, TILE, full);
          dst += TILE;
          src += TILE;
          full += 8;
        } while ((full - BAR(B_WB)) & 24);
        if (j == 2) bar_arrive<6, 160>();
        STAMPP(51 + 2 * j);
      }
      if (w == 1) { SPINS(27); return; }
      const int g = w - 2;
      WAIT(BAR(B_HFREE), 0);
      {
        const int t = tid < 376 ? tid - 256 : tid - 264;
        const int src = p ^ (r >> 2 & 1), part = (r & 1) + (~(r ^ r >> 1) & 2);
        char* zp = buf + (uint32_t)(A_WD + (p * 16 + r) * (WDS / 2) + t * 16 - 1024);
#pragma unroll 1
        for (int x = 1 + (r >> 2 & 2);; x++, zp += 896) {
          const char* wp = wd + (uint32_t)((224 * src + 32 * (src & 1) + 56 * part + (t & 7)) * 896 + (p ^ 2 * x & 7) * 112 + (t & 56) * 2);
          uint4 z[7];
#pragma unroll
          for (int i = 0; i < 7; i++) {
            if (i == 3 && part + (src & 1) == 4) wp -= 224 * 896;
            z[i] = ldg4(wp + i * 8 * 896);
          }
#pragma unroll
          for (int i = 0; i < 7; i++) st_rlx4(zp + i * 1792, z[i].x, z[i].y, z[i].z, z[i].w);
          if (!(x & 1)) break;
        }
      }
      STAMPP(5);
      asm volatile("fence.proxy.async.global;" ::: "memory");
      __syncwarp();
      if (lane == 0) red_release(&g_cnt[C_WD + p * 32]);
      STAMPP(7);
      cnt_wait<true>(&g_cnt[C_WD + p * 32], e1 * 32, budget);
      STAMPP(18);
      asm volatile("fence.proxy.async.global;" ::: "memory");
      if (lane < 2) mbar_arrive(BAR(B_WDOK));
#pragma unroll 1
      for (int j = 0; j < 4; j += j + 1) {
        const uint32_t bar = BAR(B_WB + 4 * g + j);
        const char* src = buf + (j < 3 ? A_HH + (cta ^ j) * 2 * STG + g * TILE : A_PS + (cta * 6 + 3 * g) * 7168);
        if (j != 1) cnt_wait(&g_cnt[(j < 3 ? C_ROW + r * 32 + 4 + 2 * (p & 6) : C_PS + cta * 8) + g], e1 * 8, budget);
        WAIT(j >= 2 ? BAR(B_HFREE + 2 * g + 1) : BAR(B_EMPTY + 6 + g), j >> 1);
        if (elect()) {
          mbar_expect_tx(bar, TILE);
          bulk_g2s(sb + (6 + g) * STG + (j & 1) * TILE, src, TILE, bar);
        }
      }
      SPINS(28 + g);
      if (g && lane == 0) DUMP(2);
    }
  } else {
    STAMP(60);
    bar_sync<0, 384>();
    STAMP(63);
    asm volatile("setmaxnreg.inc.sync.aligned.u32 224;");
    STAMP(61);
    const int g = warp >> 2, gq = lane >> 2, tq = lane & 3;
    const uint64_t dk = d128 + kh;
    uint4 A[28];
    float rs0, rs1, m0, m1;
    float acc0[28], acc1[28];
    uint32_t mb0, mb1;
    {
      uint32_t la[4];
#pragma unroll
      for (int i = 0; i < 4; i++) {
        la[i] = sb + OFF_X + warp * TILE + (lane & 15) * 128 + (((2 * i + (lane >> 4)) ^ (lane & 7)) << 4);
        asm volatile("" : "+r"(la[i]));
      }
      STAMP(62);
      WAIT(BAR(B_XB + warp), 0);
      STAMP(1);
#pragma unroll
      for (int ks = 0; ks < 28; ks++) A[ks] = ldsm4(la[ks & 3] + (ks >> 2) * 2048);
      float cs[4][4] = {};
#pragma unroll
      for (int ks = 0; ks < 28; ks++) mma16816(cs[ks & 3], A[ks].x, A[ks].y, A[ks].z, A[ks].w, 0x3F803F80u, 0x3F803F80u);
      m0 = ((cs[0][0] + cs[1][0]) + (cs[2][0] + cs[3][0])) * (1.f / DM);
      m1 = ((cs[0][2] + cs[1][2]) + (cs[2][2] + cs[3][2])) * (1.f / DM);
      mb0 = pack2(m0, m0); mb1 = pack2(m1, m1);
      if (lane == 0) mbar_arrive(BAR(B_XFREE) + (mb0 & zero));
    }
    STAMP(2);
    uint32_t pa[7];
    {
      const uint32_t prow = sb + OFF_PK + warp * 4096 + gq * 128 + (gq << 4), t = tq >> 1;
      const uint32_t b2 = (prow + ((4 * tq + 8) & 15)) ^ (t << 4);
      pa[0] = prow + 4 * tq; pa[1] = pa[0] ^ 16; pa[2] = pa[0] ^ 32;
      pa[3] = (prow + 4 * (tq & 1)) ^ (48 + 16 * t);
      pa[4] = b2 ^ 64; pa[5] = b2 ^ 80 ^ (t << 5); pa[6] = b2 ^ 96;
#pragma unroll
      for (int j = 0; j < 7; j++) asm volatile("" : "+r"(pa[j]));
    }
    auto sqs = [&](int q) {
      uint4 s;
#pragma unroll
      for (int ks = 7 * q; ks < 7 * q + 7; ks++) {
        if (ks % 7 == 0) s = make_uint4(sq2(A[ks].x), sq2(A[ks].y), sq2(A[ks].z), sq2(A[ks].w));
        else s = make_uint4(sq2(A[ks].x, s.x), sq2(A[ks].y, s.y), sq2(A[ks].z, s.z), sq2(A[ks].w, s.w));
      }
      s.x = add2(s.x, s.z);
      s.y = add2(s.y, s.w);
      rs0 = (q ? rs0 : 0.f) + (bf_lo(s.x) + bf_hi(s.x));
      rs1 = (q ? rs1 : 0.f) + (bf_lo(s.y) + bf_hi(s.y));
      if (q == 3) {
        rs0 += shx(rs0, 1); rs1 += shx(rs1, 1);
        rs0 += shx(rs0, 2); rs1 += shx(rs1, 2);
      }
      asm volatile("" : "+f"(rs0), "+f"(rs1));
    };
    auto sub = [&](int q) {
#pragma unroll
      for (int ks = 7 * q; ks < 7 * q + 7; ks++)
        A[ks] = make_uint4(sub2(A[ks].x, mb0), sub2(A[ks].y, mb1), sub2(A[ks].z, mb0), sub2(A[ks].w, mb1));
    };
    uint32_t sdw, mw;
    PhiC c0, c1;
    auto stats = [&] {
      const float d0 = m0 - bf_lo(mb0), d1 = m1 - bf_lo(mb1);
      const float q0 = fmaxf(rs0 * (1.f / DM) - d0 * d0, 0.f) + 1e-5f;
      const float q1 = fmaxf(rs1 * (1.f / DM) - d1 * d1, 0.f) + 1e-5f;
      rs0 = rsqf(q0);
      rs1 = rsqf(q1);
      const float sd = (tq & 2 ? q1 * rs1 : q0 * rs0);
      sdw = pack2(sd, sd - bf_lo(pack2(sd, 0.f)));
      mw = pack2(tq ? m1 : m0, tq ? d1 : d0);
      c0 = {rs0 * 1.4426950408889634f, lg2f(rs0), pack2(rs0 * rs0, rs0 * rs0), pack2(rs0, rs0), pack2(1e-6f * rs0, 1e-6f * rs0)};
      c1 = {rs1 * 1.4426950408889634f, lg2f(rs1), pack2(rs1 * rs1, rs1 * rs1), pack2(rs1, rs1), pack2(1e-6f * rs1, 1e-6f * rs1)};
      asm volatile("" : "+r"(sdw), "+r"(mw), "+f"(c0.x), "+f"(c0.y), "+r"(c0.z), "+r"(c0.s), "+r"(c0.w), "+f"(c1.x), "+f"(c1.y), "+r"(c1.z), "+r"(c1.s), "+r"(c1.w));
    };
    auto alu = [&](auto S) {
      sfor<4>([&](auto Q) { if (0x843 >> 4 * S + Q & 1) sub(Q); });
      if (S < 4) sqs(S);
      if (S == 3) stats();
    };
    alu(IC<0>{});
    sfor<4>([&](auto J) {
      constexpr int j = J;
      WAIT(BAR(B_K + j), 0);
      STAMP(26 + j);
      if (j == 0 && g) bar_sync<7, 256>();
      wg_fence();
      sfor<7>([&](auto I) { wgmma_rs_n56<2 * STG + (7 * j + I) * 2048>(acc0, A[7 * j + I], dk, j + I != 0); });
      if (j == 0 && !g) bar_arrive<7, 256>();
      if (j == 3) wg_commit();
      alu(IC<j + 1>{});
    });
    STAMP(3);
    WAIT(BAR(B_V), 0);
    STAMP(10);
    wg_fence();
    sfor<7>([&](auto I) { wgmma_rs_n56<I * 2048>(acc1, A[I], dk, I != 0); });
    wg_commit();
    WAIT(BAR(B_XFREE), 0);
    wg_wait<1>();
    acc_fence(acc0);
    STAMP(4);
    if (lane == 0) mbar_arrive(BAR(B_KFREE));
    sfor<7>([&](auto J) {
      constexpr int j = J;
      sfor<3>([&](auto I) {
        constexpr int ks = 7 + 3 * j + I;
        if (ks % 7 == 0) { WAIT(BAR(B_V + ks / 7), 0); wg_fence(); }
        wgmma_rs_n56<ks * 2048>(acc1, A[ks], dk, 1);
      });
      sts1(pa[j], phi2(acc0[4 * j], acc0[4 * j + 1], c0));
      sts1(pa[j] + 1024, phi2(acc0[4 * j + 2], acc0[4 * j + 3], c1));
    });
    wg_commit();
    sts1(((pa[0] & ~15u) ^ (48 + 64 * (tq & 1))) + 2048 + 8 + ((tq >> 1) << 10), sdw);
    if (tq < 2) sts4(sb + OFF_XS + 112 + warp * 2048 + tq * 1024 + gq * 112, mw, 0, 0, 0);
    wg_wait<0>();
    acc_fence(acc1);
    STAMP(5);
    STAMP(54);
#pragma unroll
    for (int j = 0; j < 7; j++) {
      sts1(pa[j] + 2048, pack2(acc1[4 * j], acc1[4 * j + 1]));
      sts1(pa[j] + 3072, pack2(acc1[4 * j + 2], acc1[4 * j + 3]));
    }
    fence_async_smem();
    if (lane == 0) mbar_arrive(BAR(B_VFREE));
    if (g == 0) {
      bar_arrive<1, 256>();
      bar_sync<3, 256>();
    } else {
      bar_sync<1, 256>();
      STAMP(55);
      float kv[32];
      wg_fence();
      sfor<8>([&](auto I) {
        constexpr int o = OFF_PK + I * 4096;
        wgmma_ss_n64<o, o + 2048>(kv, d128, d128, I != 0);
      });
      wg_commit();
      bar_arrive<3, 256>();
      WAIT(BAR(B_INIT), 0);
      char* da = buf + (A_KVR + p * KVR_B + (warp & 3) * 2176) + (uint32_t)(gq * 64 + (tq & 1) * 32 + (tq & 2) * 8);
      char *db = da + (uint32_t)(1152 + gq * 64), *dz = da + (uint32_t)(1008 - gq * 48);
      asm volatile("" : "+l"(da), "+l"(db), "+l"(dz));
      wg_wait<0>();
      acc_fence(kv);
      STAMP(56);
      auto put = [&](const float* v, int n) {
        const int b = n & 2;
        if (!b || (tid & 48) != 48) {
          if (n & 1) red_add4(b ? db + 64 : da + 512, v[b + 8], v[b + 9], tq & 2 ? v[b + 5] : v[b + 12], tq & 2 ? 1.f : v[b + 13]);
          else red_add4(b ? db : da, v[b], v[b + 1], v[b + 4], tq & 2 ? 1.f : v[b + 5]);
        }
      };
#pragma unroll
      for (int i = 0; i < 16; i++) kv[i] = warp & 2 ? kv[16 + i] : kv[i];
#pragma unroll
      for (int n = 0; n < 4; n++) put(kv, n);
      if (tq == 2) red_add4(dz, kv[12] + kv[13], kv[14] + kv[15], 0.f, 1.f);
    }
    STAMP(6);
    const uint32_t par = ~ld_rlx1(&g_cnt[C_ROW + r * 32 + (tid >> 7)]) >> 5;
    WAIT(BAR(B_Q), 0);
    wg_fence();
    sfor<28>([&](auto I) { wgmma_rs_n56<I * 2048>(acc0, A[I], dq + kh, I != 0); });
    wg_commit();
    const uint32_t wb = BAR(B_WB) + 32 * g;
    const int wq4 = warp & 3;
    char* const oblk = buf + (A_O + (r * 2 + g) * 2 * STG);
    const uint32_t gsub = sb + OFF_G + g * 2 * STG + wq4 * 3584 + lane * 16, gsub8 = gsub - lane * 8;
    const char* const olane = oblk + (uint32_t)(wq4 * 3584 + lane * 16);
    char* const ob = oblk + (uint32_t)((p >> 1) * TILE + wq4 * 3584 + kh * 896 + gq * 16);
    char *ob16 = ob + tq * 128, *ob8 = ob + 512 + (tq >> 1) * 128 + (tq & 1) * 8, *ob4 = ob + 768 + tq * 4;
    unsigned* cnt = &g_cnt[C_ROW + r * 32];
    asm volatile("" : "+l"(ob16), "+l"(ob8), "+l"(ob4), "+l"(cnt));
    wg_wait<0>();
    acc_fence(acc0);
    STAMP(7);
    if (lane == 0) mbar_arrive(BAR(B_QFREE));
    uint32_t R[14];
    {
      uint4 Q[4];
#pragma unroll
      for (int j = 0; j < 7; j++) {
        const uint32_t lo = phi2(acc0[4 * j], acc0[4 * j + 1], c0);
        const uint32_t hi = phi2(acc0[4 * j + 2], acc0[4 * j + 3], c1);
        if (j & 1) { Q[j >> 1].z = lo; Q[j >> 1].w = hi; } else { Q[j >> 1].x = lo; Q[j >> 1].y = hi; }
      }
      Q[3].z = 0; Q[3].w = 0;
      STAMP(8);
      WAIT(BAR(B_KVB), 0);
      STAMP(9);
      float o[32];
      wg_fence();
      sfor<4>([&](auto I) { wgmma_rs_n64<OFF_KVB + I * 2048>(o, Q[I], d128, I != 0); });
      wg_commit();
      wg_wait<0>();
      red_inc(cnt, tid & 159);
      acc_fence(o);
      const float da0 = rcpf(o[28] + bf_lo(c0.w)), db0 = rcpf(o[29] + bf_lo(c0.w)), da1 = rcpf(o[30] + bf_lo(c1.w)), db1 = rcpf(o[31] + bf_lo(c1.w));
      uint32_t P[14];
#pragma unroll
      for (int j = 0; j < 7; j++) {
        const bool first = j < 2 || (j < 4 && tq < 3);
        const float s0 = first ? da0 : db0, s1 = first ? da1 : db1;
        P[2 * j] = pack2(o[4 * j] * s0, o[4 * j + 1] * s0);
        P[2 * j + 1] = pack2(o[4 * j + 2] * s1, o[4 * j + 3] * s1);
        if (0x53 >> j & 1) { P[2 * j] = tag(P[2 * j], par); P[2 * j + 1] = tag(P[2 * j + 1], par); }
      }
      auto publish = [&] {
#pragma unroll
        for (int h = 0; h < 2; h++) {
          st_rlx4(ob16 + 1792 * h, P[h], P[2 + h], P[4 + h], P[6 + h]);
          st_rlx2(ob8 + 1792 * h, P[8 + h], P[10 + h]);
          st_rlx1(ob4 + 1792 * h, P[12 + h]);
        }
      };
      if (!g) {
        publish();
        STAMP(11);
        if (lane == 0) mbar_arrive(BAR(B_OFREE));
        const int sec = min(lane, 27);
        uint32_t ta = sb + OFF_WO + wq4 * 3584 + sec * 32 + (0x3625410 >> (sec & 28) & 7) * 4;
        uint32_t gs = gsub - 2 * STG;
        const char* ol = olane + (A_WOC - A_O + (p - 2 * r) * 2 * STG);
        asm volatile("" : "+r"(ta), "+l"(ol));
#pragma unroll 1
        for (int n = 0; n < 12; n++) {
          WAIT(n < 4 ? BAR(B_WO) : BAR(B_WB - 4) + 8 * n, 0);
          STAMPD(max(n - 3, 1));
          RETRY(n < 4 ? 30 : n - 4, fixq(ta, gs, ol, par, budget));
          bar_arrive_id(4 + n);
          ol = n == 3 ? olane : ol + TILE;
          ta += TILE;
          gs += TILE;
        }
        bar_sync<3, 256>();
      } else {
        const uint32_t wa = sb + (lane >> 4) * 1024 + (lane & 7) * 128 + ((((2 * wq4 + (lane >> 3 & 1)) ^ lane) & 7) << 4);
        float hacc[64];
        {
          const uint32_t one = 0x3F80u << (lane * 4 & 16), m = tq == 0 ? 0xBF80BF80u : 0, id = (tid >> 3 ^ tq) & 15;
          uint4 E[4];
#pragma unroll
          for (int i = 0; i < 4; i++) {
            const uint32_t e = id == 4 * i ? one : 0;
            E[i] = make_uint4(e, 0, i < 3 ? 0 : m, i < 3 ? e : m);
            asm volatile("" : "+r"(E[i].x), "+r"(E[i].y), "+r"(E[i].z), "+r"(E[i].w));
          }
          wg_fence();
          sfor<8>([&](auto I) { wgmma_rk_n64<OFF_XS + I / 4 * 8192 + I % 4 * 32, I / 4 * 32>(hacc, E[I % 4], d128, I % 4 != 0); });
          wg_commit();
        }
        WAIT(BAR(B_WO), 0);
        sfor<28>([&](auto KS) {
          constexpr int ks = KS;
          if (ks == 1) {
            wg_wait<0>();
            acc_fence(hacc);
            if (lane == 0) mbar_arrive(BAR(B_OFREE));
          }
          if (ks == 24) red_inc(cnt + 1, lane);
          if (ks == 27) {
            WAIT(BAR(B_WO), 0);
            publish();
            STAMP(11);
            WAIT(BAR(B_WO), 0);
          }
          if (ks % 7 == 0) bar_sync<4 + ks / 7, 256>();
          A[ks] = ldsm4t(wa + OFF_WO + ks * 2048);
        });
        if (lane < 2) mbar_arrive(BAR(B_WOFREE) + (A[27].x & zero));
        STAMP(10);
        uint32_t ma = sb + OFF_M + tq * 8;
        char* hb = oblk + (uint32_t)(FRAG_B - 2 * STG + (p >> 1) * TILE + (wq4 < 3 ? kh * 2048 + wq4 * 512 + lane * 16 : 1536 + kh * 256 + lane * 8));
        asm volatile("" : "+l"(hb));
        STAMP(16);
#pragma unroll 1
        for (int h = 0; h < 2; h++) {
          const uint64_t dh = dko + h * (2 * STG >> 4);
          sfor<4>([&](auto Q) {
            constexpr int q = Q;
            bar_sync_id(8 + 4 * h + q);
            STAMPD(1 + 4 * h + q);
            wg_fence();
            sfor<7>([&](auto I) { wgmma_rk_n64<OFF_G + q * TILE + I * 256>(hacc, A[7 * q + I], dh, 1); });
          });
          wg_commit();
          if (h) bar_sync<6, 160>();
          wg_wait<0>();
          red_inc(cnt + 2, lane);
          acc_fence(hacc);
          STAMPD(12 + 2 * h);
          if (lane < 2) mbar_arrive(BAR(B_ORD) + 8 * h);
#pragma unroll
          for (int i = 0; i < 4; i++) {
            const float* a = hacc + 8 * i;
            st_rlx42(hb + 3584 * i, tag(transp(pack2(a[0], a[1])), par), transp(pack2(a[4], a[5])), transp(pack2(a[2], a[3])), transp(pack2(a[6], a[7])), wq4 - 3);
          }
          if (tid >= 224 && gq == 0) {
#pragma unroll
            for (int j = 0; j < 8; j++) sts2(ma + 32 * j, __float_as_uint(hacc[4 * j + 2]), __float_as_uint(hacc[4 * j + 3]));
          }
          STAMPD(13 + 2 * h);
          if (h) break;
          bar_arrive<3, 256>();
#pragma unroll
          for (int i = 0; i < 32; i++) hacc[i] = hacc[32 + i];
          acc_fence(hacc);
          hb += 2 * STG;
          ma += 256;
          cnt++;
        }
        bar_sync<5, 128>();
      }
      const char* const rb = olane + (FRAG_B + (p >> 1) * TILE);
#pragma unroll
      for (int i = 0; i < 3; i++) {
        const uint4 v = ld_rlx4(rb + kh * 2048 + 512 * i);
        R[4 * i] = v.x; R[4 * i + 1] = v.y; R[4 * i + 2] = v.z; R[4 * i + 3] = v.w;
      }
      const uint2 v = ld_rlx2(rb + 1536 + kh * 256 - lane * 8);
      R[12] = v.x; R[13] = v.y;
    }
    char* hdst = buf + (A_HH + cta * 2 * STG + warp * 3584) + (uint32_t)(lane * 16);
    {
#define GLU(gt, up, e) fmaf((up) * (e), tanhf_((gt) * (e)), (up) * (e))
      float acc[64];
      uint4 own[5];
#pragma unroll
      for (int i = 0; i < 5; i++) asm volatile("" : "=r"(own[i].x), "=r"(own[i].y), "=r"(own[i].z), "=r"(own[i].w));
      sfor<2>([&](auto Q) {
        WAIT(wb + 8 * Q, 1);
        STAMP(57 + Q);
        load7s<Q * TILE>(&A[7 * Q], gsub, gsub8);
      });
#pragma unroll 1
      for (int c = 0; c < 3; c++) {
        const uint32_t half = (c & 1) * 4;
        const uint64_t dc = d128 + half * (STG >> 4);
        if (c == 1) WAIT(BAR(B_HFREE + 3), 0);
        sfor<4>([&](auto KQ) {
          constexpr int kq = KQ;
          WAIT(BAR(B_FULL + kq) + 8 * half, c >> 1);
          if (c == 0) {
            RETRY(8 + kq + 4 * g, fix7t<A_H + kq * TILE>(&A[7 * kq], buf + r * 4 * STG, gsub, gsub8, par, budget));
            STAMP(42 + kq);
            if (lane == 0) mbar_arrive(BAR(B_HFREE + kq / 2) + 16 * g);
            if (kq < 2) WAIT(wb + 8 * (kq + 2), 1);
            STAMP(46 + kq);
            if (kq < 2) load7s<(kq + 2) % 4 * TILE>(&A[7 * ((kq + 2) % 4)], gsub, gsub8);
          }
          STAMPD(30 + 4 * c + kq);
          wg_fence();
          sfor<7>([&](auto I) { wgmma_rs_n128<kq * STG + koff(I, 1024)>(acc, A[7 * kq + I], dc, kq + I != 0); });
          wg_commit();
          if (c == 0) STAMP(50 + kq);
          if (c == 0) {
            sqs(kq);
            if (kq == 3) {
              rs0 = 0.5f * rsqf(rs0 * (1.f / DM) + 1e-5f);
              rs1 = 0.5f * rsqf(rs1 * (1.f / DM) + 1e-5f);
              asm volatile("" : "+f"(rs0), "+f"(rs1));
            }
          }
          if (kq > 0) {
            wg_wait<1>();
            if (lane == 0) mbar_arrive(BAR(B_EMPTY + kq - 1) + 8 * half);
          }
        });
        wg_wait<0>();
        acc_fence(acc);
        if (lane == 0) mbar_arrive(BAR(B_EMPTY + 3) + 8 * half);
        STAMPD(17 + c);
        constexpr int GO = SWAP ? 32 : 0, UO = SWAP ? 0 : 32;
        own[0] = own[4];
#pragma unroll
        for (int i = 0; i < 4; i++) {
          uint32_t w[4];
#pragma unroll
          for (int t = 0; t < 2; t++) {
            const int b = 8 * i + 4 * t;
            w[2 * t] = pack2(GLU(acc[GO + b], acc[UO + b], rs0), GLU(acc[GO + b + 1], acc[UO + b + 1], rs0));
            w[2 * t + 1] = pack2(GLU(acc[GO + b + 2], acc[UO + b + 2], rs1), GLU(acc[GO + b + 3], acc[UO + b + 3], rs1));
          }
          if (i == 3 && c == 1) hdst += STG - 3584;
          own[i + 1] = make_uint4(tag(w[0], par), w[1], w[2], w[3]);
          st_rlx4(hdst + i * 512, own[i + 1].x, w[1], w[2], w[3]);
        }
        hdst += 2048;
        red_inc(&g_cnt[C_ROW + r * 32 + 4 + 2 * (p & 6) + g], lane | c ^ 1);
      }
      float acct[32];
      sfor<2>([&](auto H) {
        constexpr int h = H;
        WAIT(BAR(B_FULL + 4 + h), 1);
        wg_fence();
        sfor<14>([&](auto I) { wgmma_rs_n64<(4 + h) * STG + I / 7 * (TILE / 2) + koff(I % 7, 512)>(acct, A[14 * h + I], d64, h + I != 0); });
        wg_commit();
      });
      auto ldh = [&](int k) {
        WAIT(wb + 8 * k, 0);
#pragma unroll
        for (int i = 0; i < 7; i++) A[7 * k + 7 + i] = lds4(gsub - g * STG + 2 * STG + k * TILE + i * 512);
      };
      wg_wait<1>();
      if (lane == 0) mbar_arrive(BAR(B_EMPTY + 4));
      ldh(0);
      wg_wait<0>();
      acc_fence(acct);
      if (lane == 0) mbar_arrive(BAR(B_EMPTY + 5));
      STAMP(20);
      constexpr int GO = SWAP ? 16 : 0, UO = SWAP ? 0 : 16;
#pragma unroll
      for (int i = 0; i < 2; i++) {
        uint32_t w[4];
#pragma unroll
        for (int t = 0; t < 2; t++) {
          const int b = 8 * i + 4 * t;
          w[2 * t] = pack2(GLU(acct[GO + b], acct[UO + b], rs0), GLU(acct[GO + b + 1], acct[UO + b + 1], rs0));
          w[2 * t + 1] = pack2(GLU(acct[GO + b + 2], acct[UO + b + 2], rs1), GLU(acct[GO + b + 3], acct[UO + b + 3], rs1));
        }
        st_rlx4(hdst + i * 512, tag(w[0], par), w[1], w[2], w[3]);
        A[5 + i] = make_uint4(w[0], w[1], w[2], w[3]);
      }
#pragma unroll
      for (int i = 0; i < 5; i++) A[i] = own[i];
    }
    STAMP(21);
    {
      const char* const hnb = hdst + (1 - 2 * kh) * 2 * STG;
      uint32_t eye = tq == gq >> 1 ? 0x3F80u << (16 * (gq & 1)) : 0;
      auto add = [&](float (&a)[28], const uint32_t (&v)[14]) {
#pragma unroll
        for (int j = 0; j < 7; j++)
          asm("mma.sync.aligned.m16n8k8.row.col.f32.bf16.bf16.f32 {%0,%1,%2,%3}, {%4,%5}, {%6}, {%0,%1,%2,%3};"
              : "+f"(a[4 * j]), "+f"(a[4 * j + 1]), "+f"(a[4 * j + 2]), "+f"(a[4 * j + 3]) : "r"(v[2 * j]), "r"(v[2 * j + 1]), "r"(eye));
      };
      auto send = [&](float (&acc)[28], int x) {
        acc_fence(acc);
        char* const pd = buf + (A_PS + ((cta ^ 2 * x) * 6 + 3 * g + x - 1) * 7168 + (warp & 3) * 1792);
        uint32_t P[14];
#pragma unroll
        for (int j = 0; j < 14; j++) P[j] = pack2(acc[2 * j], acc[2 * j + 1]);
        publish7(pd + (uint32_t)(lane * 16), pd + 1536 + (uint32_t)(lane * 8), P, par);
        if (x < 3) red_inc(&g_cnt[C_PS + (cta ^ 2 * x) * 8 + g], lane);
      };
      sfor<4>([&](auto K) {
        constexpr int k = K;
        if (k > 1) {
          wg_wait<1>();
          if (lane == 0) mbar_arrive(BAR(B_EMPTY + k - 2));
        }
        if (k) RETRY(16 + k + 4 * g, fix7<-2560 - (k < 3) * STG>(&A[7 * k], k > 1 ? hnb : hdst, par, budget));
        if (k == 2 && lane < 2) mbar_arrive(BAR(B_HFREE + 1) + 16 * g);
        if (k == 1) {
          WAIT(wb + 8, 0);
#pragma unroll
          for (int i = 0; i < 7; i++) A[14 + i] = lds4(gsub - g * STG + 2 * STG + TILE + i * 512);
        }
        if (k == 2) {
#pragma unroll
          for (int i = 0; i < 7; i++) A[21 + i] = ld_rlx4(hnb - 2560 + 512 * i);
        }
        WAIT(BAR(B_FULL + k), 0);
        wg_fence();
        sfor<7>([&](auto I) { wgmma_rs_n56<k * STG + I * 3584>(acc0, A[7 * k + I], d0, k + I != 0); });
        if (k == 3) wg_commit();
        sfor<7>([&](auto I) { wgmma_rs_n56<k * STG + I * 3584 + 896>(acc1, A[7 * k + I], d0, k + I != 0); });
        wg_commit();
      });
      wg_wait<1>();
      send(acc0, 1);
      sfor<4>([&](auto K) {
        constexpr int k = K, s = (k + 4) % 6;
        WAIT(BAR(B_FULL + s), k >= 2);
        wg_fence();
        sfor<7>([&](auto I) { wgmma_rs_n56<s * STG + I * 3584>(acc0, A[7 * k + I], d1, k + I != 0); });
        wg_commit();
        if (k == 0) {
          wg_wait<1>();
          send(acc1, 2);
          const float m0 = __uint_as_float(lds1(sb + OFF_M + warp * 64 + gq * 4)), m1 = __uint_as_float(lds1(sb + OFF_M + warp * 64 + gq * 4 + 32));
#pragma unroll
          for (int i = 0; i < 28; i++) acc1[i] = i & 2 ? -m1 : -m0;
          acc_fence(acc1);
        }
      });
      if (g) bar_arrive<7, 256>();
      wg_wait<0>();
      STAMP(22);
      send(acc0, 3);
      if (!g) bar_sync<7, 256>();
      uint32_t P[3][14];
      const char* const ps = buf + (A_PS + (cta * 6 + 3 * g) * 7168 + (warp & 3) * 1792) + (uint32_t)(lane * 16);
      const char* const ps8 = ps - lane * 8;
      auto fetch = [&](int x) {
#pragma unroll
        for (int i = 0; i < 3; i++) {
          const uint4 v = ld_rlx4(ps + 7168 * x + 512 * i);
          P[x][4 * i] = v.x; P[x][4 * i + 1] = v.y; P[x][4 * i + 2] = v.z; P[x][4 * i + 3] = v.w;
        }
        const uint2 v = ld_rlx2(ps8 + 7168 * x + 1536);
        P[x][12] = v.x; P[x][13] = v.y;
      };
      const uint32_t pss = sb + (6 + g) * STG + (warp & 3) * 1792;
      auto fetchs = [&] {
        WAIT(wb + 24, 0);
#pragma unroll
        for (int x = 0; x < 2; x++) {
          const uint32_t a = pss + TILE + 7168 * x;
#pragma unroll
          for (int i = 0; i < 3; i++) {
            const uint4 v = lds4(a + 512 * i + lane * 16);
            P[x][4 * i] = v.x; P[x][4 * i + 1] = v.y; P[x][4 * i + 2] = v.z; P[x][4 * i + 3] = v.w;
          }
          const uint2 v = lds2(a + 1536 + lane * 8);
          P[x][12] = v.x; P[x][13] = v.y;
        }
      };
      WAIT(BAR(B_FULL + 5), 0);
      wg_fence();
      sfor<28>([&](auto I) {
        if (I == 21) {
          fetchs();
          fetch(2);
          wg_fence();
        }
        wgmma_rs_n56<(I / 7 + 4) % 6 * STG + I % 7 * 3584 + 896>(acc1, A[I], d1, 1);
      });
      wg_commit();
      STAMP(23);
      WAIT(BAR(B_FULL + 5), 0);
      uint32_t ob = pss + 7168 + (lane & 15) * 112 + (lane & 16);
      char* op = out + (uint32_t)((128 * r + (tid >> 5) * 16 + (lane >> 3)) * 896 + 112 * p + (lane & 7) * 16);
      uint32_t ia = pss + 7168 + (lane >> 3) * 112 + (lane & 7) * 16;
      asm volatile("" : "+r"(ob), "+l"(op), "+r"(ia));
      auto check = [&](int x) {
#pragma unroll 1
        while (stale(xor2(P[x][0], P[x][4], par) | xor2(P[x][8], P[x][12], par), budget)) fetch(x);
      };
      check(0);
      check(1);
      uint32_t o[14];
      {
        wg_wait<0>();
        acc_fence(acc1);
        STAMP(24);
        add(acc1, R);
        add(acc1, P[0]);
        add(acc1, P[1]);
        acc_fence(acc1);
        WAIT(BAR(B_FULL + 5), 0);
        check(2);
        add(acc1, P[2]);
#pragma unroll
        for (int j = 0; j < 14; j++) o[j] = pack2(acc1[2 * j], acc1[2 * j + 1]);
      }
#pragma unroll
      for (int i = 0; i < 3; i++)
        asm volatile("stmatrix.sync.aligned.m8n8.x4.shared.b16 [%0], {%1,%2,%3,%4};" ::"r"(ob + 32 * i), "r"(o[4 * i]), "r"(o[4 * i + 1]), "r"(o[4 * i + 2]), "r"(o[4 * i + 3]) : "memory");
      asm volatile("stmatrix.sync.aligned.m8n8.x2.shared.b16 [%0], {%1,%2};" ::"r"(ob + 96), "r"(o[12]), "r"(o[13]) : "memory");
      __syncwarp();
      {
        uint4 v[4];
#pragma unroll
        for (int i = 0; i < 4; i++) v[i] = lds4(ia + 448 * i);
        if ((lane & 7) < 7) {
#pragma unroll
          for (int i = 0; i < 4; i++) *(uint4*)(op + 3584 * i) = v[i];
        }
      }
      STAMP(25);
      SPINS(24 + g);
      GTIME(1);
    }
  }
}

typedef CUresult (*EncodeFn)(CUtensorMap*, CUtensorMapDataType, cuuint32_t, void*, const cuuint64_t*, const cuuint64_t*,
                             const cuuint32_t*, const cuuint32_t*, CUtensorMapInterleave, CUtensorMapSwizzle,
                             CUtensorMapL2promotion, CUtensorMapFloatOOBfill);

void make_map(EncodeFn enc, CUtensorMap* m, const void* p, int rank, const cuuint64_t* gd, const cuuint64_t* gs,
              const cuuint32_t* bd, CUtensorMapSwizzle sw) {
  const cuuint32_t es[5] = {1, 1, 1, 1, 1};
  ENC_CHECK(enc(m, CU_TENSOR_MAP_DATA_TYPE_BFLOAT16, rank, (void*)p, gd, gs, bd, es, CU_TENSOR_MAP_INTERLEAVE_NONE, sw,
                CU_TENSOR_MAP_L2_PROMOTION_NONE, CU_TENSOR_MAP_FLOAT_OOB_FILL_NONE));
}

}

extern "C" void kernel_launch(void* const* d_in, const int* in_sizes, int n_in, void* d_out, int out_size) {
  (void)in_sizes; (void)n_in; (void)out_size;
  static EncodeFn enc = nullptr;
  static char* buf = nullptr;
  if (!enc) {
    void* fn = nullptr;
    cudaDriverEntryPointQueryResult qr;
    cudaGetDriverEntryPoint("cuTensorMapEncodeTiled", &fn, cudaEnableDefault, &qr);
    enc = (EncodeFn)fn;
    cudaGetSymbolAddress((void**)&buf, g_buf);
    cudaFuncSetAttribute(fused_block_kernel<false>, cudaFuncAttributeMaxDynamicSharedMemorySize, SMEM_TOTAL);
    cudaFuncSetAttribute(fused_block_kernel<true>, cudaFuncAttributeMaxDynamicSharedMemorySize, SMEM_TOTAL);
  }
  const CUtensorMapSwizzle S128 = CU_TENSOR_MAP_SWIZZLE_128B;
  CUtensorMap mx, mqkv, mgu, mgu32;
  {
    cuuint64_t gd[3] = {64, SEQ, 7}, gs[2] = {DM * 2, 128};
    cuuint32_t bd[3] = {64, 16, 7};
    make_map(enc, &mx, d_in[0], 3, gd, gs, bd, S128);
  }
  {
    cuuint64_t gd[2] = {3 * DM, DM}, gs[1] = {3 * DM * 2};
    cuuint32_t bd[2] = {64, 112};
    make_map(enc, &mqkv, d_in[1], 2, gd, gs, bd, S128);
  }
  Pos pos = {};
  for (int i = 0; i < 32; i++) {
    const int c = 28 * (i >> 4) + 2 * (i >> 2 & 3) + 8 * (i & 3);
    pos.v[i >> 2] |= (uint32_t)(2 * (c < 32 ? (c & 6) * 4 + (c >> 3) * 2 : c < 48 ? 32 + (c & 2) * 4 + (c >> 1 & 6) : c)) << 8 * (i & 3);
  }
  const char *wg = (const char*)d_in[4], *wu = (const char*)d_in[5];
  const bool swap = wu < wg;
  const char* gub = swap ? wu : wg;
  const cuuint64_t gud = swap ? (cuuint64_t)(wg - wu) : (cuuint64_t)(wu - wg);
  {
    cuuint64_t gd[3] = {FF, DM, 2}, gs[2] = {FF * 2, gud};
    cuuint32_t bd[3] = {64, 112, 2};
    make_map(enc, &mgu, gub, 3, gd, gs, bd, S128);
  }
  {
    cuuint64_t gd[3] = {FF, DM, 2}, gs[2] = {FF * 2, gud};
    cuuint32_t bd[3] = {32, 224, 2};
    make_map(enc, &mgu32, gub, 3, gd, gs, bd, CU_TENSOR_MAP_SWIZZLE_64B);
  }
  (swap ? fused_block_kernel<true> : fused_block_kernel<false>)<<<128, 384, SMEM_TOTAL>>>(
      buf, (const char*)d_in[2], mn_desc(sb), mn_desc64(sb), mn_desc0(sb), mn_desc(sb + OFF_Q), mn_desc0(sb), k_desc0(sb), wg, wu, (const char*)d_in[6], (const char*)d_in[1], (char*)d_out, mx, mqkv, pos, mgu, mgu32);
}
```

```cpp
#include <cuda_runtime.h>
#include <cuda_bf16.h>
#include <cuda.h>
#include <stdint.h>
#include <stdio.h>
#include <utility>

#define SPIN_LIMIT (1 << 18)

namespace {

constexpr uint32_t sb = 1024;
constexpr int SEQ = 2048, DM = 448, FF = 1792;
constexpr int TILE = 14336;
constexpr int STG = 2 * TILE;
constexpr int SMEM_BAR = 8 * STG;
constexpr int SMEM_TOTAL = SMEM_BAR + 3072;
constexpr int OFF_X = 4 * STG, OFF_Q = 4 * STG, OFF_WO = 2 * STG, OFF_G = 4 * STG, OFF_PK = 6 * STG, OFF_KVB = OFF_PK + 32768, OFF_XS = OFF_KVB + 8192,
              OFF_M = SMEM_BAR + 512;
constexpr int B_XB = 0  , B_K = 8  , B_V = 12  , B_Q = 16, B_WO = 17, B_FULL = 18  , B_WB = 26  ,
              B_KVB = 34, B_WDOK = 35, B_INIT = 36,
              B_KFREE = 37, B_QFREE = 38, B_WOFREE = 39, B_OFREE = 40, B_HFREE = 41  , B_EMPTY = 45  , B_XFREE = 53, B_VFREE = 54,
              B_ORD = 55  ;

constexpr int KVR_B = 8704;
constexpr int FRAG_B = 16 * 4 * STG;
constexpr int A_CNT = 0, A_EPOCH = 8192, A_KVR = A_EPOCH + 16384, A_O = A_KVR + 8 * KVR_B + 2048, A_H = A_O + FRAG_B,
              A_HH = A_H + FRAG_B;
constexpr int HH_B = 128 * 2 * STG;
constexpr int A_PS = A_HH + HH_B;
constexpr int WDS = 25088;
constexpr int A_WD = A_PS + 128 * 3 * TILE;
constexpr int A_WOC = A_WD + 64 * WDS;

__device__ uint4 g_buf[(A_WOC + 16 * STG) / 16];
constexpr int C_ROW = 0, C_WD = 512, C_PS = 1024;
#define g_cnt ((unsigned*)buf + A_CNT / 4)
#define ENC_CHECK(x) (void)(x)
#define STAMP(i)
#define STAMPX(i)
#define GTIME(i)
#define STAMPP(i)
#define STAMPD(i)
#define DUMP(row)

__device__ __forceinline__ uint32_t smem_u32(const void* p) { return (uint32_t)__cvta_generic_to_shared(p); }
__device__ __forceinline__ void mbar_init(uint32_t bar, uint32_t cnt) {
  asm volatile("mbarrier.init.shared::cta.b64 [%0], %1;" ::"r"(bar), "r"(cnt) : "memory");
}
__device__ __forceinline__ void mbar_expect_tx(uint32_t bar, uint32_t bytes) {
  asm volatile("mbarrier.arrive.expect_tx.shared::cta.b64 _, [%0], %1;" ::"r"(bar), "r"(bytes) : "memory");
}
__device__ __forceinline__ void mbar_arrive(uint32_t bar) {
  asm volatile("mbarrier.arrive.shared::cta.b64 _, [%0];" ::"r"(bar) : "memory");
}
__device__ __forceinline__ void mbar_wait(uint32_t bar, uint32_t parity, int& budget) {
  asm volatile("{\n.reg .pred p;\nW:\nmbarrier.try_wait.parity.shared::cta.b64 p, [%1], %2;\n"
               "add.s32 %0, %0, -1;\nsetp.gt.and.s32 p, %0, 0, !p;\n@p bra W;\n}"
               : "+r"(budget) : "r"(bar), "r"(parity) : "memory");
}
__device__ __forceinline__ bool elect() {
  uint32_t v;
  asm volatile("{\n.reg .pred p;\nelect.sync _|p, 0xffffffff;\nselp.u32 %0, 1, 0, p;\n}" : "=r"(v));
  return v;
}
__device__ __forceinline__ void tma2d(uint32_t dst, const CUtensorMap* m, int c0, int c1, uint32_t bar) {
  asm volatile("cp.async.bulk.tensor.2d.shared::cluster.global.mbarrier::complete_tx::bytes [%0], [%1, {%3, %4}], [%2];"
               ::"r"(dst), "l"(m), "r"(bar), "r"(c0), "r"(c1) : "memory");
}
__device__ __forceinline__ void tma3d(uint32_t dst, const CUtensorMap* m, int c0, int c1, int c2, uint32_t bar) {
  asm volatile("cp.async.bulk.tensor.3d.shared::cluster.global.mbarrier::complete_tx::bytes [%0], [%1, {%3, %4, %5}], [%2];"
               ::"r"(dst), "l"(m), "r"(bar), "r"(c0), "r"(c1), "r"(c2) : "memory");
}
__device__ __forceinline__ void bulk_g2s(uint32_t dst, const void* src, uint32_t bytes, uint32_t bar) {
  asm volatile("cp.async.bulk.shared::cluster.global.mbarrier::complete_tx::bytes [%0], [%1], %2, [%3];"
               ::"r"(dst), "l"(src), "r"(bytes), "r"(bar) : "memory");
}
__device__ __forceinline__ void l2_prefetch(const void* p, uint32_t bytes) {
  asm volatile("cp.async.bulk.prefetch.L2.global [%0], %1;" ::"l"(p), "r"(bytes) : "memory");
}
__device__ __forceinline__ void prefetch_map(const CUtensorMap* m) {
  asm volatile("prefetch.tensormap [%0];" ::"l"(m) : "memory");
}
__device__ __forceinline__ void fence_async_smem() { asm volatile("fence.proxy.async.shared::cta;" ::: "memory"); }
template <int ID, int N> __device__ __forceinline__ void bar_arrive() { asm volatile("bar.arrive %0, %1;" ::"n"(ID), "n"(N) : "memory"); }
__device__ __forceinline__ void bar_arrive_id(int id) { asm volatile("bar.arrive %0, 256;" ::"r"(id) : "memory"); }
__device__ __forceinline__ void bar_sync_id(int id) { asm volatile("bar.sync %0, 256;" ::"r"(id) : "memory"); }
__device__ __forceinline__ void bar_sync_wg(int id) { asm volatile("bar.sync %0, 128;" ::"r"(id) : "memory"); }
template <int ID, int N> __device__ __forceinline__ void bar_sync() { asm volatile("bar.sync %0, %1;" ::"n"(ID), "n"(N) : "memory"); }
__device__ __forceinline__ void wg_fence() { asm volatile("wgmma.fence.sync.aligned;" ::: "memory"); }
__device__ __forceinline__ void wg_commit() { asm volatile("wgmma.commit_group.sync.aligned;" ::: "memory"); }
template <int N> __device__ __forceinline__ void wg_wait() { asm volatile("wgmma.wait_group.sync.aligned %0;" ::"n"(N) : "memory"); }
template <int N> __device__ __forceinline__ void acc_fence(float (&d)[N]) {
#pragma unroll
  for (int i = 0; i < N; i++) asm volatile("" : "+f"(d[i])::"memory");
}
constexpr uint64_t mn_desc(uint32_t addr) {
  return (uint64_t)((addr & 0x3FFFF) >> 4) | ((uint64_t)(TILE >> 4) << 16) | ((uint64_t)64 << 32) | ((uint64_t)1 << 62);
}
constexpr uint64_t mn_desc64(uint32_t addr) {
  return (uint64_t)((addr & 0x3FFFF) >> 4) | ((uint64_t)(TILE >> 4) << 16) | ((uint64_t)32 << 32) | ((uint64_t)2 << 62);
}
constexpr uint64_t mn_desc0(uint32_t addr) {
  return (uint64_t)((addr & 0x3FFFF) >> 4) | ((uint64_t)(1792 >> 4) << 16) | ((uint64_t)8 << 32);
}
constexpr uint64_t k_desc0(uint32_t addr) {
  return (uint64_t)((addr & 0x3FFFF) >> 4) | ((uint64_t)8 << 16) | ((uint64_t)(1792 >> 4) << 32);
}
__device__ __forceinline__ uint4 ld_rlx4(const void* p) {
  uint4 v;
  asm volatile("ld.relaxed.gpu.global.v4.u32 {%0,%1,%2,%3}, [%4];" : "=r"(v.x), "=r"(v.y), "=r"(v.z), "=r"(v.w) : "l"(p) : "memory");
  return v;
}
__device__ __forceinline__ uint2 ld_rlx2(const void* p) {
  uint2 v;
  asm volatile("ld.relaxed.gpu.global.v2.u32 {%0,%1}, [%2];" : "=r"(v.x), "=r"(v.y) : "l"(p) : "memory");
  return v;
}
__device__ __forceinline__ uint32_t ld_rlx1(const void* p) {
  uint32_t v;
  asm volatile("ld.relaxed.gpu.global.u32 %0, [%1];" : "=r"(v) : "l"(p) : "memory");
  return v;
}
__device__ __forceinline__ void st_rlx4(void* p, uint32_t a, uint32_t b, uint32_t c, uint32_t d) {
  asm volatile("st.relaxed.gpu.global.v4.u32 [%0], {%1,%2,%3,%4};" ::"l"(p), "r"(a), "r"(b), "r"(c), "r"(d) : "memory");
}
__device__ __forceinline__ void st_rlx2(void* p, uint32_t a, uint32_t b) {
  asm volatile("st.relaxed.gpu.global.v2.u32 [%0], {%1,%2};" ::"l"(p), "r"(a), "r"(b) : "memory");
}
__device__ __forceinline__ void st_rlx1(void* p, uint32_t a) {
  asm volatile("st.relaxed.gpu.global.u32 [%0], %1;" ::"l"(p), "r"(a) : "memory");
}
__device__ __forceinline__ void red_inc(unsigned* p, uint32_t skip) {
  asm volatile("{\n.reg .pred p;\nsetp.eq.u32 p, %1, 0;\n@p red.relaxed.gpu.global.inc.u32 [%0], 0xfffffffe;\n}" ::"l"(p), "r"(skip) : "memory");
}
__device__ __forceinline__ void red_release(unsigned* p) {
  asm volatile("red.release.gpu.global.inc.u32 [%0], 0xfffffffe;" ::"l"(p) : "memory");
}
__device__ __forceinline__ void st_rlx42(void* p, uint32_t a, uint32_t b, uint32_t c, uint32_t d, uint32_t all) {
  asm volatile("{\n.reg .pred p;\nsetp.ne.u32 p, %5, 0;\n@p st.relaxed.gpu.global.v4.u32 [%0], {%1,%2,%3,%4};\n"
               "@!p st.relaxed.gpu.global.v2.u32 [%0], {%1,%2};\n}" ::"l"(p), "r"(a), "r"(b), "r"(c), "r"(d), "r"(all) : "memory");
}
__device__ __forceinline__ void red_add4(void* p, float a, float b, float c, float d) {
  asm volatile("red.relaxed.gpu.global.add.v4.f32 [%0], {%1,%2,%3,%4};" ::"l"(p), "f"(a), "f"(b), "f"(c), "f"(d) : "memory");
}
__device__ __forceinline__ void eq_wait(const void* p, uint32_t target, int& budget) {
  asm volatile("{\n.reg .pred p;\n.reg .b32 v;\nW:\nld.relaxed.gpu.global.b32 v, [%1];\nadd.s32 %0, %0, -1;\n"
               "setp.gt.s32 p, %0, 0;\nsetp.gt.and.u32 p, v, %2, p;\n@p bra W;\n}"
               : "+r"(budget) : "l"(p), "r"(target) : "memory");
}
template <bool ACQ = false>
__device__ __forceinline__ void cnt_wait(const unsigned* p, uint32_t target, int& budget) {
  if (ACQ)
    asm volatile("{\n.reg .pred p;\n.reg .s32 v;\nW:\nld.acquire.gpu.global.s32 v, [%1];\nadd.s32 %0, %0, -1;\n"
                 "setp.gt.s32 p, %0, 0;\nsub.s32 v, v, %2;\nsetp.lt.and.s32 p, v, 0, p;\n@p bra W;\n}"
                 : "+r"(budget) : "l"(p), "r"(target) : "memory");
  else
  asm volatile("{\n.reg .pred p;\n.reg .s32 v;\nW:\nld.relaxed.gpu.global.s32 v, [%1];\nadd.s32 %0, %0, -1;\n"
               "setp.gt.s32 p, %0, 0;\nsub.s32 v, v, %2;\nsetp.lt.and.s32 p, v, 0, p;\n@p bra W;\n}"
               : "+r"(budget) : "l"(p), "r"(target) : "memory");
}
__device__ __forceinline__ uint32_t or3(uint32_t a, uint32_t b, uint32_t c) {
  uint32_t r;
  asm("lop3.b32 %0, %1, %2, %3, 0xfe;" : "=r"(r) : "r"(a), "r"(b), "r"(c));
  return r;
}
__device__ __forceinline__ uint32_t xor2(uint32_t a, uint32_t b, uint32_t f) {
  uint32_t r;
  asm("lop3.b32 %0, %1, %2, %3, 0x7e;" : "=r"(r) : "r"(a), "r"(b), "r"(f));
  return r;
}
__device__ __forceinline__ bool stale(uint32_t bad, int& budget, uint32_t mask = 1) {
  uint32_t v;
  asm volatile("{\n.reg .pred p;\n.reg .b32 t;\nand.b32 t, %2, %3;\nsetp.ne.u32 p, t, 0;\nadd.s32 %1, %1, -1;\n"
               "setp.gt.and.s32 p, %1, 0, p;\nvote.sync.any.pred p, p, 0xffffffff;\nselp.u32 %0, 1, 0, p;\n}"
               : "=r"(v), "+r"(budget) : "r"(bad), "r"(mask));
  return v;
}
__device__ __forceinline__ uint32_t tag(uint32_t w, uint32_t par) {
  uint32_t r;
  asm("lop3.b32 %0, %1, %2, 1, 0xd8;" : "=r"(r) : "r"(w), "r"(par));
  return r;
}
__device__ __forceinline__ void sts1(uint32_t a, uint32_t v) { asm volatile("st.shared.u32 [%0], %1;" ::"r"(a), "r"(v) : "memory"); }
__device__ __forceinline__ void sts2(uint32_t a, uint32_t x, uint32_t y) {
  asm volatile("st.shared.v2.u32 [%0], {%1,%2};" ::"r"(a), "r"(x), "r"(y) : "memory");
}
__device__ __forceinline__ void sts4(uint32_t a, uint32_t x, uint32_t y, uint32_t z, uint32_t w) {
  asm volatile("st.shared.v4.u32 [%0], {%1,%2,%3,%4};" ::"r"(a), "r"(x), "r"(y), "r"(z), "r"(w) : "memory");
}
__device__ __forceinline__ uint32_t lds1(uint32_t a) {
  uint32_t v;
  asm volatile("ld.shared.u32 %0, [%1];" : "=r"(v) : "r"(a) : "memory");
  return v;
}
__device__ __forceinline__ uint2 lds2(uint32_t a) {
  uint2 v;
  asm volatile("ld.shared.v2.u32 {%0,%1}, [%2];" : "=r"(v.x), "=r"(v.y) : "r"(a) : "memory");
  return v;
}
__device__ __forceinline__ uint4 lds4(uint32_t a) {
  uint4 v;
  asm volatile("ld.shared.v4.u32 {%0,%1,%2,%3}, [%4];" : "=r"(v.x), "=r"(v.y), "=r"(v.z), "=r"(v.w) : "r"(a) : "memory");
  return v;
}
__device__ __forceinline__ uint4 ldsm4(uint32_t a) {
  uint4 v;
  asm volatile("ldmatrix.sync.aligned.m8n8.x4.shared.b16 {%0,%1,%2,%3}, [%4];" : "=r"(v.x), "=r"(v.y), "=r"(v.z), "=r"(v.w) : "r"(a) : "memory");
  return v;
}
__device__ __forceinline__ uint4 ldsm4t(uint32_t a) {
  uint4 v;
  asm volatile("ldmatrix.sync.aligned.m8n8.x4.trans.shared.b16 {%0,%1,%2,%3}, [%4];" : "=r"(v.x), "=r"(v.y), "=r"(v.z), "=r"(v.w) : "r"(a) : "memory");
  return v;
}
__device__ __forceinline__ uint32_t pack2(float lo, float hi) {
  uint32_t r;
  asm("cvt.rn.bf16x2.f32 %0, %1, %2;" : "=r"(r) : "f"(hi), "f"(lo));
  return r;
}
__device__ __forceinline__ float bf_lo(uint32_t w) { return __uint_as_float(w << 16); }
__device__ __forceinline__ float bf_hi(uint32_t w) { return __uint_as_float(w & 0xFFFF0000u); }
__device__ __forceinline__ uint32_t sub2(uint32_t a, uint32_t b) {
  uint32_t r;
  asm volatile("sub.rn.bf16x2 %0, %1, %2;" : "=r"(r) : "r"(a), "r"(b));
  return r;
}
__device__ __forceinline__ uint32_t add2(uint32_t a, uint32_t b) {
  uint32_t r;
  asm("add.rn.bf16x2 %0, %1, %2;" : "=r"(r) : "r"(a), "r"(b));
  return r;
}
__device__ __forceinline__ uint32_t fma2(uint32_t a, uint32_t b, uint32_t c) {
  uint32_t r;
  asm("fma.rn.bf16x2 %0, %1, %2, %3;" : "=r"(r) : "r"(a), "r"(b), "r"(c));
  return r;
}
__device__ __forceinline__ uint32_t transp(uint32_t a) {
  uint32_t r;
  asm volatile("movmatrix.sync.aligned.m8n8.trans.b16 %0, %1;" : "=r"(r) : "r"(a));
  return r;
}
__device__ __forceinline__ uint32_t sq2(uint32_t a) {
  uint32_t r;
  asm volatile("mul.rn.bf16x2 %0, %1, %1;" : "=r"(r) : "r"(a));
  return r;
}
__device__ __forceinline__ uint32_t sq2(uint32_t a, uint32_t c) {
  uint32_t r;
  asm volatile("fma.rn.bf16x2 %0, %1, %1, %2;" : "=r"(r) : "r"(a), "r"(c));
  return r;
}
__device__ __forceinline__ uint4 ldg4(const void* p) {
  uint4 v;
  asm volatile("ld.global.nc.v4.u32 {%0,%1,%2,%3}, [%4];" : "=r"(v.x), "=r"(v.y), "=r"(v.z), "=r"(v.w) : "l"(p));
  return v;
}
__device__ __forceinline__ void mma16816(float (&c)[4], uint32_t a0, uint32_t a1, uint32_t a2, uint32_t a3, uint32_t b0, uint32_t b1) {
  asm("mma.sync.aligned.m16n8k16.row.col.f32.bf16.bf16.f32 {%0,%1,%2,%3}, {%4,%5,%6,%7}, {%8,%9}, {%0,%1,%2,%3};"
      : "+f"(c[0]), "+f"(c[1]), "+f"(c[2]), "+f"(c[3]) : "r"(a0), "r"(a1), "r"(a2), "r"(a3), "r"(b0), "r"(b1));
}
__device__ __forceinline__ void mma16816z(float (&c)[4], const uint4& a, uint32_t b0, uint32_t b1) {
  asm("mma.sync.aligned.m16n8k16.row.col.f32.bf16.bf16.f32 {%0,%1,%2,%3}, {%4,%5,%6,%7}, {%8,%9}, {%10,%10,%10,%10};"
      : "=f"(c[0]), "=f"(c[1]), "=f"(c[2]), "=f"(c[3]) : "r"(a.x), "r"(a.y), "r"(a.z), "r"(a.w), "r"(b0), "r"(b1), "f"(0.f));
}
__device__ __forceinline__ float ex2f(float x) { float r; asm("ex2.approx.ftz.f32 %0, %1;" : "=f"(r) : "f"(x)); return r; }
__device__ __forceinline__ float tanhf_(float x) { float r; asm("tanh.approx.f32 %0, %1;" : "=f"(r) : "f"(x)); return r; }
__device__ __forceinline__ float rsqf(float x) { float r; asm("rsqrt.approx.ftz.f32 %0, %1;" : "=f"(r) : "f"(x)); return r; }
__device__ __forceinline__ float lg2f(float x) { float r; asm("lg2.approx.ftz.f32 %0, %1;" : "=f"(r) : "f"(x)); return r; }
__device__ __forceinline__ float rcpf(float x) { float r; asm("rcp.approx.ftz.f32 %0, %1;" : "=f"(r) : "f"(x)); return r; }
__device__ __forceinline__ float phi(float a, const float4& c) {
  return ex2f(fmaf(fminf(a, 0.f), c.x, c.y)) + fmaf(fmaxf(a, 0.f), c.z, c.w);
}
struct PhiC { float x, y; uint32_t z, s, w; };
__device__ __forceinline__ uint32_t phi2(float a, float b, const PhiC& c) {
  uint32_t r;
  asm("{\n.reg .b32 e, u;\ncvt.rn.bf16x2.f32 e, %2, %1;\ncvt.rn.relu.bf16x2.f32 u, %4, %3;\nfma.rn.bf16x2 u, u, %5, %6;\n"
      "min.bf16x2 u, u, e;\nadd.rn.bf16x2 %0, u, %7;\n}"
      : "=r"(r) : "f"(ex2f(fmaf(a, c.x, c.y))), "f"(ex2f(fmaf(b, c.x, c.y))), "f"(a), "f"(b), "r"(c.z), "r"(c.s), "r"(c.w));
  return r;
}
__host__ __device__ constexpr long long koff(int i, int u) { return i < 3 ? 2 * i * u : i == 3 ? 6 * u + ((6ll * u) << 32) : (2 * i - 1) * u; }
__device__ __forceinline__ float shx(float v, int m) { return __shfl_xor_sync(0xffffffffu, v, m); }
template <int V> struct IC { __host__ __device__ constexpr operator int() const { return V; } };
template <class F, int... I> __device__ __forceinline__ void sfor_impl(F&& f, std::integer_sequence<int, I...>) {
  (f(IC<I>{}), ...);
}
template <int N, class F> __device__ __forceinline__ void sfor(F&& f) { sfor_impl(f, std::make_integer_sequence<int, N>{}); }

template <long long OFF, int RO = 0, int N>
__device__ __forceinline__ void wgmma_rs_n56(float (&d)[N], const uint4& a, uint64_t base, int scale_d) {
  asm volatile("{\n.reg .pred p;\n.reg .b64 t;\nsetp.ne.b32 p, %33, 0;\nadd.s64 t, %32, %34;\n"
    "wgmma.mma_async.sync.aligned.m64n56k16.f32.bf16.bf16 {%0, %1, %2, %3, %4, %5, %6, %7, %8, %9, %10, %11, %12, %13, %14, %15, %16, %17, %18, %19, %20, %21, %22, %23, %24, %25, %26, %27}, {%28, %29, %30, %31}, t, p, 1, 1, 1;\n}\n"
    : "+f"(d[RO + 0]), "+f"(d[RO + 1]), "+f"(d[RO + 2]), "+f"(d[RO + 3]), "+f"(d[RO + 4]), "+f"(d[RO + 5]), "+f"(d[RO + 6]), "+f"(d[RO + 7]), "+f"(d[RO + 8]), "+f"(d[RO + 9]), "+f"(d[RO + 10]), "+f"(d[RO + 11]), "+f"(d[RO + 12]), "+f"(d[RO + 13]), "+f"(d[RO + 14]), "+f"(d[RO + 15]), "+f"(d[RO + 16]), "+f"(d[RO + 17]), "+f"(d[RO + 18]), "+f"(d[RO + 19]), "+f"(d[RO + 20]), "+f"(d[RO + 21]), "+f"(d[RO + 22]), "+f"(d[RO + 23]), "+f"(d[RO + 24]), "+f"(d[RO + 25]), "+f"(d[RO + 26]), "+f"(d[RO + 27])
    : "r"(a.x), "r"(a.y), "r"(a.z), "r"(a.w), "l"(base), "r"(scale_d), "n"(OFF >> 4));
}
template <long long OFF, int RO = 0, int N>
__device__ __forceinline__ void wgmma_rs_n64(float (&d)[N], const uint4& a, uint64_t base, int scale_d) {
  asm volatile("{\n.reg .pred p;\n.reg .b64 t;\nsetp.ne.b32 p, %37, 0;\nadd.s64 t, %36, %38;\n"
    "wgmma.mma_async.sync.aligned.m64n64k16.f32.bf16.bf16 {%0, %1, %2, %3, %4, %5, %6, %7, %8, %9, %10, %11, %12, %13, %14, %15, %16, %17, %18, %19, %20, %21, %22, %23, %24, %25, %26, %27, %28, %29, %30, %31}, {%32, %33, %34, %35}, t, p, 1, 1, 1;\n}\n"
    : "+f"(d[RO + 0]), "+f"(d[RO + 1]), "+f"(d[RO + 2]), "+f"(d[RO + 3]), "+f"(d[RO + 4]), "+f"(d[RO + 5]), "+f"(d[RO + 6]), "+f"(d[RO + 7]), "+f"(d[RO + 8]), "+f"(d[RO + 9]), "+f"(d[RO + 10]), "+f"(d[RO + 11]), "+f"(d[RO + 12]), "+f"(d[RO + 13]), "+f"(d[RO + 14]), "+f"(d[RO + 15]), "+f"(d[RO + 16]), "+f"(d[RO + 17]), "+f"(d[RO + 18]), "+f"(d[RO + 19]), "+f"(d[RO + 20]), "+f"(d[RO + 21]), "+f"(d[RO + 22]), "+f"(d[RO + 23]), "+f"(d[RO + 24]), "+f"(d[RO + 25]), "+f"(d[RO + 26]), "+f"(d[RO + 27]), "+f"(d[RO + 28]), "+f"(d[RO + 29]), "+f"(d[RO + 30]), "+f"(d[RO + 31])
    : "r"(a.x), "r"(a.y), "r"(a.z), "r"(a.w), "l"(base), "r"(scale_d), "n"(OFF >> 4));
}
template <long long OFF, int RO = 0, int N>
__device__ __forceinline__ void wgmma_rk_n64(float (&d)[N], const uint4& a, uint64_t base, int scale_d) {
  asm volatile("{\n.reg .pred p;\n.reg .b64 t;\nsetp.ne.b32 p, %37, 0;\nadd.s64 t, %36, %38;\n"
    "wgmma.mma_async.sync.aligned.m64n64k16.f32.bf16.bf16 {%0, %1, %2, %3, %4, %5, %6, %7, %8, %9, %10, %11, %12, %13, %14, %15, %16, %17, %18, %19, %20, %21, %22, %23, %24, %25, %26, %27, %28, %29, %30, %31}, {%32, %33, %34, %35}, t, p, 1, 1, 0;\n}\n"
    : "+f"(d[RO + 0]), "+f"(d[RO + 1]), "+f"(d[RO + 2]), "+f"(d[RO + 3]), "+f"(d[RO + 4]), "+f"(d[RO + 5]), "+f"(d[RO + 6]), "+f"(d[RO + 7]), "+f"(d[RO + 8]), "+f"(d[RO + 9]), "+f"(d[RO + 10]), "+f"(d[RO + 11]), "+f"(d[RO + 12]), "+f"(d[RO + 13]), "+f"(d[RO + 14]), "+f"(d[RO + 15]), "+f"(d[RO + 16]), "+f"(d[RO + 17]), "+f"(d[RO + 18]), "+f"(d[RO + 19]), "+f"(d[RO + 20]), "+f"(d[RO + 21]), "+f"(d[RO + 22]), "+f"(d[RO + 23]), "+f"(d[RO + 24]), "+f"(d[RO + 25]), "+f"(d[RO + 26]), "+f"(d[RO + 27]), "+f"(d[RO + 28]), "+f"(d[RO + 29]), "+f"(d[RO + 30]), "+f"(d[RO + 31])
    : "r"(a.x), "r"(a.y), "r"(a.z), "r"(a.w), "l"(base), "r"(scale_d), "n"(OFF >> 4));
}
template <long long OFF, int RO = 0, int N>
__device__ __forceinline__ void wgmma_rs_n128(float (&d)[N], const uint4& a, uint64_t base, int scale_d) {
  asm volatile("{\n.reg .pred p;\n.reg .b64 t;\nsetp.ne.b32 p, %69, 0;\nadd.s64 t, %68, %70;\n"
    "wgmma.mma_async.sync.aligned.m64n128k16.f32.bf16.bf16 {%0, %1, %2, %3, %4, %5, %6, %7, %8, %9, %10, %11, %12, %13, %14, %15, %16, %17, %18, %19, %20, %21, %22, %23, %24, %25, %26, %27, %28, %29, %30, %31, %32, %33, %34, %35, %36, %37, %38, %39, %40, %41, %42, %43, %44, %45, %46, %47, %48, %49, %50, %51, %52, %53, %54, %55, %56, %57, %58, %59, %60, %61, %62, %63}, {%64, %65, %66, %67}, t, p, 1, 1, 1;\n}\n"
    : "+f"(d[RO + 0]), "+f"(d[RO + 1]), "+f"(d[RO + 2]), "+f"(d[RO + 3]), "+f"(d[RO + 4]), "+f"(d[RO + 5]), "+f"(d[RO + 6]), "+f"(d[RO + 7]), "+f"(d[RO + 8]), "+f"(d[RO + 9]), "+f"(d[RO + 10]), "+f"(d[RO + 11]), "+f"(d[RO + 12]), "+f"(d[RO + 13]), "+f"(d[RO + 14]), "+f"(d[RO + 15]), "+f"(d[RO + 16]), "+f"(d[RO + 17]), "+f"(d[RO + 18]), "+f"(d[RO + 19]), "+f"(d[RO + 20]), "+f"(d[RO + 21]), "+f"(d[RO + 22]), "+f"(d[RO + 23]), "+f"(d[RO + 24]), "+f"(d[RO + 25]), "+f"(d[RO + 26]), "+f"(d[RO + 27]), "+f"(d[RO + 28]), "+f"(d[RO + 29]), "+f"(d[RO + 30]), "+f"(d[RO + 31]), "+f"(d[RO + 32]), "+f"(d[RO + 33]), "+f"(d[RO + 34]), "+f"(d[RO + 35]), "+f"(d[RO + 36]), "+f"(d[RO + 37]), "+f"(d[RO + 38]), "+f"(d[RO + 39]), "+f"(d[RO + 40]), "+f"(d[RO + 41]), "+f"(d[RO + 42]), "+f"(d[RO + 43]), "+f"(d[RO + 44]), "+f"(d[RO + 45]), "+f"(d[RO + 46]), "+f"(d[RO + 47]), "+f"(d[RO + 48]), "+f"(d[RO + 49]), "+f"(d[RO + 50]), "+f"(d[RO + 51]), "+f"(d[RO + 52]), "+f"(d[RO + 53]), "+f"(d[RO + 54]), "+f"(d[RO + 55]), "+f"(d[RO + 56]), "+f"(d[RO + 57]), "+f"(d[RO + 58]), "+f"(d[RO + 59]), "+f"(d[RO + 60]), "+f"(d[RO + 61]), "+f"(d[RO + 62]), "+f"(d[RO + 63])
    : "r"(a.x), "r"(a.y), "r"(a.z), "r"(a.w), "l"(base), "r"(scale_d), "n"(OFF >> 4));
}
template <int OFFA, int OFFB>
__device__ __forceinline__ void wgmma_ss_n64(float (&d)[32], uint64_t basea, uint64_t baseb, int scale_d) {
  asm volatile("{\n.reg .pred p;\n.reg .b64 t, u;\nsetp.ne.b32 p, %34, 0;\nadd.s64 t, %32, %35;\nadd.s64 u, %33, %36;\n"
    "wgmma.mma_async.sync.aligned.m64n64k16.f32.bf16.bf16 {%0, %1, %2, %3, %4, %5, %6, %7, %8, %9, %10, %11, %12, %13, %14, %15, %16, %17, %18, %19, %20, %21, %22, %23, %24, %25, %26, %27, %28, %29, %30, %31}, t, u, p, 1, 1, 1, 1;\n}\n"
    : "+f"(d[0]), "+f"(d[1]), "+f"(d[2]), "+f"(d[3]), "+f"(d[4]), "+f"(d[5]), "+f"(d[6]), "+f"(d[7]), "+f"(d[8]), "+f"(d[9]), "+f"(d[10]), "+f"(d[11]), "+f"(d[12]), "+f"(d[13]), "+f"(d[14]), "+f"(d[15]), "+f"(d[16]), "+f"(d[17]), "+f"(d[18]), "+f"(d[19]), "+f"(d[20]), "+f"(d[21]), "+f"(d[22]), "+f"(d[23]), "+f"(d[24]), "+f"(d[25]), "+f"(d[26]), "+f"(d[27]), "+f"(d[28]), "+f"(d[29]), "+f"(d[30]), "+f"(d[31])
    : "l"(basea), "l"(baseb), "r"(scale_d), "n"(OFFA >> 4), "n"(OFFB >> 4));
}

__device__ __forceinline__ void publish7(char* b16, char* b8, const uint32_t (&P)[14], uint32_t par) {
  st_rlx4(b16, tag(P[0], par), P[1], P[2], P[3]);
  st_rlx4(b16 + 512, tag(P[4], par), P[5], P[6], P[7]);
  st_rlx4(b16 + 1024, tag(P[8], par), P[9], P[10], P[11]);
  st_rlx2(b8, tag(P[12], par), P[13]);
}
template <int GOFF>
__device__ __forceinline__ void fix7(uint4* v, const char* g, uint32_t par, int& budget) {
  asm volatile("{\n.reg .pred p;\n.reg .b32 t, w<4>;\nsetp.eq.s32 p, %28, 0;\nC:\n@!p bra.uni L;\nadd.s32 %28, %28, -1;\n"
               "ld.relaxed.gpu.global.v4.u32 {%0,%1,%2,%3}, [%29+%31+0];\n"
               "ld.relaxed.gpu.global.v4.u32 {%4,%5,%6,%7}, [%29+%31+512];\n"
               "ld.relaxed.gpu.global.v4.u32 {%8,%9,%10,%11}, [%29+%31+1024];\n"
               "ld.relaxed.gpu.global.v4.u32 {%12,%13,%14,%15}, [%29+%31+1536];\n"
               "ld.relaxed.gpu.global.v4.u32 {%16,%17,%18,%19}, [%29+%31+2048];\n"
               "ld.relaxed.gpu.global.v4.u32 {%20,%21,%22,%23}, [%29+%31+2560];\n"
               "ld.relaxed.gpu.global.v4.u32 {%24,%25,%26,%27}, [%29+%31+3072];\n"
               "L:\nlop3.b32 w0, %0, %4, %30, 0x7e;\nlop3.b32 w1, %8, %12, %30, 0x7e;\nlop3.b32 w2, %16, %20, %30, 0x7e;\nxor.b32 w3, %24, %30;\n"
               "lop3.b32 t, w0, w1, w2, 0xfe;\nlop3.b32 t, t, w3, 1, 0xa8;\n"
               "setp.ne.u32 p, t, 0;\nsetp.gt.and.s32 p, %28, 0, p;\nvote.sync.any.pred p, p, 0xffffffff;\n@p bra.uni C;\n}"
               : "+r"(v[0].x), "+r"(v[0].y), "+r"(v[0].z), "+r"(v[0].w), "+r"(v[1].x), "+r"(v[1].y), "+r"(v[1].z), "+r"(v[1].w), "+r"(v[2].x), "+r"(v[2].y), "+r"(v[2].z), "+r"(v[2].w), "+r"(v[3].x), "+r"(v[3].y), "+r"(v[3].z), "+r"(v[3].w), "+r"(v[4].x), "+r"(v[4].y), "+r"(v[4].z), "+r"(v[4].w), "+r"(v[5].x), "+r"(v[5].y), "+r"(v[5].z), "+r"(v[5].w), "+r"(v[6].x), "+r"(v[6].y), "+r"(v[6].z), "+r"(v[6].w), "+r"(budget)
               : "l"(g), "r"(par), "n"(GOFF) : "memory");
}
template <int SOFF>
__device__ __forceinline__ void load7s(uint4* v, uint32_t s, uint32_t s8) {
  asm volatile("ld.shared.v4.u32 {%0,%1,%2,%3}, [%28+%30+0];\n"
               "ld.shared.v4.u32 {%4,%5,%6,%7}, [%28+%30+512];\n"
               "ld.shared.v4.u32 {%8,%9,%10,%11}, [%28+%30+1024];\n"
               "ld.shared.v2.u32 {%12,%13}, [%29+%30+1536];\nld.shared.v2.u32 {%14,%15}, [%29+%30+1792];\n"
               "ld.shared.v4.u32 {%16,%17,%18,%19}, [%28+%30+2048];\n"
               "ld.shared.v4.u32 {%20,%21,%22,%23}, [%28+%30+2560];\n"
               "ld.shared.v4.u32 {%24,%25,%26,%27}, [%28+%30+3072];\n"
               : "=r"(v[0].x), "=r"(v[0].y), "=r"(v[0].z), "=r"(v[0].w), "=r"(v[1].x), "=r"(v[1].y), "=r"(v[1].z), "=r"(v[1].w), "=r"(v[2].x), "=r"(v[2].y), "=r"(v[2].z), "=r"(v[2].w), "=r"(v[3].x), "=r"(v[3].y), "=r"(v[3].z), "=r"(v[3].w), "=r"(v[4].x), "=r"(v[4].y), "=r"(v[4].z), "=r"(v[4].w), "=r"(v[5].x), "=r"(v[5].y), "=r"(v[5].z), "=r"(v[5].w), "=r"(v[6].x), "=r"(v[6].y), "=r"(v[6].z), "=r"(v[6].w)
               : "r"(s), "r"(s8), "n"(SOFF) : "memory");
}
template <int GOFF>
__device__ __forceinline__ void fix7t(uint4* v, const char* base, uint32_t s, uint32_t s8, uint32_t par, int& budget) {
  asm volatile("{\n.reg .pred p;\n.reg .b32 t, w<4>;\n.reg .b64 g, h;\nsetp.eq.s32 p, %28, 0;\nC:\n@!p bra.uni L;\nadd.s32 %28, %28, -1;\n"
               "mad.wide.u32 g, %32, 1, %29;\nmad.wide.u32 h, %33, 1, %29;\n"
               "ld.relaxed.gpu.global.v4.u32 {%0,%1,%2,%3}, [g+%31+0];\n"
               "ld.relaxed.gpu.global.v4.u32 {%4,%5,%6,%7}, [g+%31+512];\n"
               "ld.relaxed.gpu.global.v4.u32 {%8,%9,%10,%11}, [g+%31+1024];\n"
               "ld.relaxed.gpu.global.v2.u32 {%12,%13}, [h+%31+1536];\nld.relaxed.gpu.global.v2.u32 {%14,%15}, [h+%31+1792];\n"
               "ld.relaxed.gpu.global.v4.u32 {%16,%17,%18,%19}, [g+%31+2048];\n"
               "ld.relaxed.gpu.global.v4.u32 {%20,%21,%22,%23}, [g+%31+2560];\n"
               "ld.relaxed.gpu.global.v4.u32 {%24,%25,%26,%27}, [g+%31+3072];\nL:\n"
               "lop3.b32 w0, %0, %4, %30, 0x7e;\nlop3.b32 w1, %8, %12, %30, 0x7e;\nlop3.b32 w2, %14, %16, %30, 0x7e;\nlop3.b32 w3, %20, %24, %30, 0x7e;\n"
               "lop3.b32 t, w0, w1, w2, 0xfe;\nlop3.b32 t, t, w3, 1, 0xa8;\n"
               "setp.ne.u32 p, t, 0;\nsetp.gt.and.s32 p, %28, 0, p;\nvote.sync.any.pred p, p, 0xffffffff;\n@p bra.uni C;\n}"
               : "+r"(v[0].x), "+r"(v[0].y), "+r"(v[0].z), "+r"(v[0].w), "+r"(v[1].x), "+r"(v[1].y), "+r"(v[1].z), "+r"(v[1].w), "+r"(v[2].x), "+r"(v[2].y), "+r"(v[2].z), "+r"(v[2].w), "+r"(v[3].x), "+r"(v[3].y), "+r"(v[3].z), "+r"(v[3].w), "+r"(v[4].x), "+r"(v[4].y), "+r"(v[4].z), "+r"(v[4].w), "+r"(v[5].x), "+r"(v[5].y), "+r"(v[5].z), "+r"(v[5].w), "+r"(v[6].x), "+r"(v[6].y), "+r"(v[6].z), "+r"(v[6].w), "+r"(budget)
               : "l"(base), "r"(par), "n"(GOFF - (int)sb - OFF_G), "r"(s), "r"(s8) : "memory");
}
__device__ __forceinline__ void fixq(uint32_t a, uint32_t s, const char* g, uint32_t par, int& budget) {
  asm volatile("{\n.reg .pred p;\n.reg .b32 t, u, w<28>;\nsetp.eq.s32 p, %0, 0;\n"
               "ld.shared.u32 w0, [%1];\nld.shared.u32 w1, [%1+896];\nld.shared.u32 w2, [%1+1792];\nld.shared.u32 w3, [%1+2688];\n"
               "C:\n@!p bra.uni L;\nadd.s32 %0, %0, -1;\n"
               "ld.relaxed.gpu.global.v4.u32 {w0,w1,w2,w3}, [%3+0];\n"
               "ld.relaxed.gpu.global.v4.u32 {w4,w5,w6,w7}, [%3+512];\n"
               "ld.relaxed.gpu.global.v4.u32 {w8,w9,w10,w11}, [%3+1024];\n"
               "ld.relaxed.gpu.global.v4.u32 {w12,w13,w14,w15}, [%3+1536];\n"
               "ld.relaxed.gpu.global.v4.u32 {w16,w17,w18,w19}, [%3+2048];\n"
               "ld.relaxed.gpu.global.v4.u32 {w20,w21,w22,w23}, [%3+2560];\n"
               "ld.relaxed.gpu.global.v4.u32 {w24,w25,w26,w27}, [%3+3072];\n"
               "st.shared.v4.u32 [%2+0], {w0,w1,w2,w3};\n"
               "st.shared.v4.u32 [%2+512], {w4,w5,w6,w7};\n"
               "st.shared.v4.u32 [%2+1024], {w8,w9,w10,w11};\n"
               "st.shared.v4.u32 [%2+1536], {w12,w13,w14,w15};\n"
               "st.shared.v4.u32 [%2+2048], {w16,w17,w18,w19};\n"
               "st.shared.v4.u32 [%2+2560], {w20,w21,w22,w23};\n"
               "st.shared.v4.u32 [%2+3072], {w24,w25,w26,w27};\n"
               "fence.proxy.async.shared::cta;\nbar.warp.sync 0xffffffff;\n"
               "ld.shared.u32 w0, [%1];\nld.shared.u32 w1, [%1+896];\nld.shared.u32 w2, [%1+1792];\nld.shared.u32 w3, [%1+2688];\n"
               "L:\n"
               "lop3.b32 t, w0, w1, %4, 0x7e;\nlop3.b32 u, w2, w3, %4, 0x7e;\nlop3.b32 t, t, u, 1, 0xa8;\n"
               "setp.ne.u32 p, t, 0;\nsetp.gt.and.s32 p, %0, 0, p;\nvote.sync.any.pred p, p, 0xffffffff;\n@p bra.uni C;\n}"
               : "+r"(budget)
               : "r"(a), "r"(s), "l"(g), "r"(par) : "memory");
}
#define SPINS(i)
#define RETRY(i, ...) __VA_ARGS__
#define BAR(i) (sb + SMEM_BAR + 8 * (i))
#define WAIT(b, ph) mbar_wait(b, ph, budget)

__host__ __device__ constexpr int digits(unsigned v, int n) { return n ? (v & 15) + digits(v >> 4, n - 1) : 0; }
struct Pos { uint32_t v[8]; };
template <bool SWAP>
__global__ void __launch_bounds__(384, 1)
fused_block_kernel(char* const buf, const char* __restrict__ wo, const uint64_t d128, const uint64_t d64, const uint64_t d0,
                   const uint64_t dq, const uint64_t d1, const uint64_t dko,
                   const char* __restrict__ wg, const char* __restrict__ wu, const char* __restrict__ wd, const char* __restrict__ wq, char* __restrict__ out,
                   const __grid_constant__ CUtensorMap map_x, const __grid_constant__ CUtensorMap map_qkv,
                   const __grid_constant__ Pos pos, const __grid_constant__ CUtensorMap map_gu,
                   const __grid_constant__ CUtensorMap map_gu32) {
  extern __shared__ __align__(1024) uint8_t smem[];
  const int tid = threadIdx.x, lane = tid & 31;
  const int warp = __shfl_sync(0xffffffffu, tid >> 5, 0);
#define KVTHR 0xC0800000
#define KVP 1152
#define OFP 1
#define PP 0
#define WT 0xff4422
#define HORD 0
#define ORED1 24
#define B6 1
#define LA0 1
#define LA1 2
#define W4G 4
#define PFT 0x222
#define PFW 2
#define PFV 3
#define EPC 1
#define QG 1
#define TAILV 0
#define FPOS 21
#define HLD 1
#define ORD 1
#define HF 1
#define MH 1
#define MG 1
#define SQM 0x8421
#define XW 1
#define WOP 0
#define LDP 1
#define W2U 2
#define W2G 3
#define RPKB B_HFREE
#define RPL 0
#define SUBM 0x843
#define SQS 0x8421
#define STP 3
#define GDL 0
#define KL 1
#define KVF 0
#define TOP 2
#define ZP 0
#define VPAT 0x3333333
#define V1 7
#define VE 1
#define VSP 0
#define VSL 2
#define VS 1
#define FW2 0
#define FW 1
#define W4U 99
#define W4B 0
#define W4P 0
#define TADD 0
#define LA 2
#define PHI2 1
#define GGATE 2
#define RPK 1
#define OPUB 24
#define HRED 5
#define HRED1 5
#define ORED 4
  const int cta = (blockIdx.x & 56) * 2 + (blockIdx.x & 1) * 8 + (blockIdx.x & 6) + (blockIdx.x >> 6), r = cta >> 3, p = cta & 7;
  const int kh = p & 1;
  const int wcol = 56 * p - 8 * kh;
  int budget = SPIN_LIMIT;
  const uint32_t zero = d0 >> 48;
  STAMP(0);
  if (warp >= 8) {
    {
      const uint32_t c = 0x100000 - (tid < 256 + B_KVB ? 1 : tid < 256 + B_KFREE ? 4 : tid == 256 + B_XFREE ? 12 : 8);
      if (tid < 320) sts2(BAR(tid - 256), c << 1, c << 11);
      fence_async_smem();
      bar_arrive<0, 384>();
      bar_sync<2, 128>();
#pragma unroll
      for (int i = warp - 8; i < warp; i += 4) {
        if (elect()) {
          mbar_expect_tx(BAR(B_XB + i), TILE);
          tma3d(sb + OFF_X + i * TILE, &map_x, 0, 128 * r + 16 * i, 0, BAR(B_XB + i));
        }
      }
      prefetch_map(&map_qkv);
    }
    STAMPP(60);
    asm volatile("setmaxnreg.dec.sync.aligned.u32 56;");
    STAMPP(63);
  }
  int role = warp;
  asm volatile("" : "+r"(role));
  if (role >= 8) {
    STAMPP(59);
    const int w = warp - 8, t = tid - 256;
    STAMPP(61);
    char* const kvr = buf + (A_KVR + p * KVR_B);
    if (t < 34) st_rlx4(kvr + (uint32_t)((r * 34 + t) * 16), 0, 0, 0, (t & 1) || ((r & 3) * 34 + t >> 3) == 8 ? 0xC1800000u : 0u);
    const uint32_t e1 = (ld_rlx1(&g_cnt[C_ROW + r * 32]) >> 5) + 1;
    const int krow = min(cta, 111) * 4 + w;
    const char* wrow = wo + (uint32_t)(krow * (DM * 2) + (lane - (lane >> 3)) * 16);
    uint4 u0 = make_uint4(0, 0, 0, 0), u1 = u0;
    if ((lane & 7) < 7) {
      u0 = ldg4(wrow);
      u1 = ldg4(wrow + 448);
    }
    if (lane < 7) asm volatile("prefetch.global.L2 [%0];" ::"l"(wq + (uint32_t)(krow * (DM * 6) + lane * 128)));
    if (warp == 11) {
#pragma unroll 1
      for (int j = 0; j < 8; j++) {
        if (elect()) {
          mbar_expect_tx(BAR(B_K + j), TILE);
          tma2d(sb + (j ^ 4) * TILE, &map_qkv, wcol + DM + DM * (j >> 2), 112 * (j & 3), BAR(B_K + j));
        }
      }
    }
    GTIME(0);
    STAMPP(62);
    {
      float c[4];
      mma16816z(c, u0, 0x3F803F80u, 0x3F803F80u);
      mma16816(c, u1.x, u1.y, u1.z, u1.w, 0x3F803F80u, 0x3F803F80u);
      float s = c[0] + c[2];
      s += shx(s, 4); s += shx(s, 8); s += shx(s, 16);
      const uint32_t nw = pack2(s * (1.f / DM), s * (1.f / DM));
      char* const wc = buf + (A_WOC + krow * 128) + (uint32_t)((lane >> 3) * 2 * STG + (((lane ^ krow) & 7) << 4));
      st_rlx4(wc, tag(sub2(u0.x, nw), e1), tag(sub2(u0.y, nw), e1), tag(sub2(u0.z, nw), e1), tag(sub2(u0.w, nw), e1));
      st_rlx4(wc + 8 * STG, tag(sub2(u1.x, nw), e1), tag(sub2(u1.y, nw), e1), tag(sub2(u1.z, nw), e1), tag(sub2(u1.w, nw), e1));
    }
    if (smem_u32(smem) != sb) __trap();
    STAMPP(19);
    uint4 xs[8];
    {
      const uint32_t G = 7 * p + (lane & 7), a = sb + OFF_X + w * TILE + (G >> 3) * 2048 + (lane >> 3) * 128 + (((G ^ lane >> 3) & 7) << 4), b = a ^ 64;
#pragma unroll
      for (int i = 0; i < 8; i++) {
        if (i % 4 == 0) WAIT(BAR(B_XB + w + (i & 4)), 0);
        xs[i] = lds4((i & 1 ? b : a) + (i & 4) * TILE + (i & 3) * 512);
      }
    }
    if (lane == 0) mbar_arrive(BAR(B_XFREE) + (xs[7].x & (ZP ? (uint32_t)(d1 >> 48) : zero)));
    WAIT(BAR(B_XFREE), 0);
    if (w == 0 && elect()) {
      mbar_expect_tx(BAR(B_Q), 2 * STG);
#pragma unroll 1
      for (int j = 0; j < 4; j++) tma2d(sb + OFF_Q + j * TILE, &map_qkv, wcol, 112 * j, BAR(B_Q));
    }
#pragma unroll
    for (int i = 0; i < 4; i++) sts4(sb + OFF_KVB + 2048 * i + t * 16, 0, 0, 0, 0);
    if ((lane & 7) < 7) {
      const uint32_t a = sb + OFF_XS + w * 2048 + (lane >> 3) * 128 + (((lane ^ lane >> 3) & 7) << 4), b = a ^ 64;
#pragma unroll
      for (int i = 0; i < 8; i++) sts4((i & 1 ? b : a) + (i & 4) * 2048 + (i & 3) * 512, xs[i].x, xs[i].y, xs[i].z, xs[i].w);
    }
    const char* const kvt = kvr + (uint32_t)(w * 2176 + (lane & 28) * 16 + (t & 1) * 32 + (t & 2) * 8);
    const char* const kvz = kvr + (uint32_t)(w * 2176 + 1024 + (lane & 28) * 4);
    const char* const kvh = kvt + (uint32_t)(1152 + (lane & 28) * 16);
    {
      uint32_t c[3];
      bool first = w == 0;
#pragma unroll 1
      do {
#pragma unroll
        for (int i = 0; i < 2; i++) c[i] = ld_rlx1(kvr + (uint32_t)(t * 32) + 4096 * i + 28);
        c[2] = ld_rlx1(kvr + (uint32_t)((t & 15) * 32) + 8192 + 28);
        if (first) {
          WAIT(BAR(B_KFREE), 0);
          STAMPX(6);
          if (elect()) {
            mbar_expect_tx(BAR(B_WO), 2 * STG);
            bulk_g2s(sb + OFF_WO, buf + (A_WOC + p * 2 * STG), 2 * STG, BAR(B_WO));
          }
        }
        first = false;
      } while (stale(~(c[0] & c[1] & c[2]), budget, 0x80000000u));
    }
    if (lane == 0) mbar_arrive(BAR(B_INIT));
    STAMPP(1);
    if (w == 2 && elect()) {
      prefetch_map(&map_gu);
      l2_prefetch(wg + cta * 12544, 12544);
      l2_prefetch(wu + cta * 12544, 12544);
      l2_prefetch(wd + cta * 12544, 12544);
      prefetch_map(&map_gu32);
    }
    WAIT(BAR(B_VFREE), 0);
    bar_sync<2, 128>();
    const int gq = lane >> 2, tq = lane & 3, k = 28 * (w >> 1) + 16 * (w & 1) + gq;
    const uint32_t row = sb + OFF_KVB + k * 128, sw = (k & 7) << 4;
    uint32_t ad[4];
    {
      const uint32_t t4 = pos.v[(w & 2) * 2 + tq] ^ (sw | row & 128) * 0x01010101u;
#pragma unroll
      for (int q = 0; q < 4; q++) {
        ad[q] = __byte_perm(row, t4, 0x3214 + q);
        asm volatile("" : "+r"(ad[q]));
      }
    }
    const bool lo = !(w & 1) || gq < 4;
    uint32_t m1 = tq & 2 ? ~0u : 0, m2 = lo ? m1 : 0;
    asm volatile("" : "+r"(m1), "+r"(m2));
    eq_wait(kvr + w * 2176 + KVP + 28, KVTHR, budget);
    STAMPX(2);
    {
      uint4 v[5];
#pragma unroll 1
      do {
#pragma unroll
        for (int i = 0; i < 4; i++) v[i] = ld_rlx4(i < 2 ? kvt + 512 * i : kvh + 64 * i - 128);
        v[4] = ld_rlx4(kvz);
      } while (stale(or3((v[0].w | v[1].w) & m1, (v[2].w | v[3].w) & m2, v[4].w), budget, ~0u));
      STAMPX(3);
#define F(x) __uint_as_float(x)
      const uint32_t a[4] = {pack2(F(v[0].x), F(v[0].y)), pack2(F(v[0].z), F(m1 ? v[1].z : v[0].w)), pack2(F(v[1].x), F(v[1].y)), pack2(F(v[1].z), F(v[1].w))};
      const uint32_t b[4] = {pack2(F(v[2].x), F(v[2].y)), pack2(F(v[2].z), F(m1 ? v[3].z : v[2].w)), pack2(F(v[3].x), F(v[3].y)), pack2(F(v[3].z), F(v[3].w))};
#pragma unroll
      for (int q = 0; q < 4; q++) {
        if (q < 3 || tq < 2) {
          sts1(ad[q], a[q]);
          if (lo) sts1(ad[q] + 1024, b[q]);
        }
      }
      if (tq == 2) {
        const uint32_t z = pack2(F(v[4].x), F(v[4].y));
        const uint32_t za = __byte_perm(z, 0, w & 2 ? 0x1044 : 0x4410), zb = __byte_perm(z, 0, w & 2 ? 0x3244 : 0x4432);
        sts4(row + (112 ^ sw), za, za, za, za);
        if (lo) sts4(row + 1024 + (112 ^ sw), zb, zb, zb, zb);
      }
      fence_async_smem();
      __syncwarp();
      if (lane == 0) mbar_arrive(BAR(B_KVB));
      STAMPP(4);
    }
    if (w == 0) {
#pragma unroll 1
      for (int u = 0; u < 22; u++) {
        const int s = u < 14 ? u & 7 : u < 20 ? u - 14 : u - 20;
        if (u == W2U || u == 14) WAIT(BAR(u == W2U ? B_WB + W2G : B_WDOK), 0);
        if (u == W4U) WAIT(BAR(W4B), W4P);
        WAIT(BAR(B_KFREE + s) + (u >= 8 ? 64 : 0), u >= 14 && u < 20);
        STAMPP(20 + u);
        if (elect()) {
          mbar_expect_tx(BAR(B_FULL + s), u < 14 ? STG : WDS);
          if (u < 12) tma3d(sb + s * STG, &map_gu, 224 * p + 32 * kh + 64 * (u >> 2), 112 * (u & 3), 0, BAR(B_FULL + s));
          else if (u < 14) tma3d(sb + s * STG, &map_gu32, 224 * p + 192 - 192 * kh, 224 * (u - 12), 0, BAR(B_FULL + s));
          else bulk_g2s(sb + s * STG, buf + (A_WD + (p * 8 + u - 14) * WDS), WDS, BAR(B_FULL + s));
        }
      }
      SPINS(26);
    } else {
#pragma unroll 1
      for (int j = 0; j < (w == 1 ? 4 : 0); j++) {
        WAIT(BAR(j < 2 ? B_QFREE + 2 * j : B_ORD - 2 + j), 0);
        const char* src = buf + (uint32_t)(A_O + (j >> 1) * FRAG_B + (r * 2 + (j & 1)) * 2 * STG);
        uint32_t dst = sb + OFF_G + (j & 1) * 2 * STG, full = BAR(B_WB + 4 * (j & 1));
        if (lane < 4) mbar_expect_tx(full + 8 * lane, TILE);
        asm volatile("" : "+l"(src), "+r"(dst), "+r"(full));
        cnt_wait(&g_cnt[C_ROW + r * 32 + j], e1 * 32, budget);
        if (GDL) { const uint32_t t0 = clock() + (GDL >> 8 * j & 255); while ((int)(clock() - t0) < 0); }
        STAMPX(50 + 2 * j);
#pragma unroll 1
        do {
          if (elect()) bulk_g2s(dst, src, TILE, full);
          dst += TILE;
          src += TILE;
          full += 8;
        } while ((full - BAR(B_WB)) & 24);
        if (j == 2) bar_arrive<6, 160>();
        STAMPP(51 + 2 * j);
      }
      if (w == 1) { SPINS(27); return; }
      const int g = w - 2;
      WAIT(BAR(B_HFREE), 0);
      {
        const int t = tid < 376 ? tid - 256 : tid - 264;
        const int src = p ^ (r >> 2 & 1), part = (r & 1) + (~(r ^ r >> 1) & 2);
        char* zp = buf + (uint32_t)(A_WD + (p * 16 + r) * (WDS / 2) + t * 16 - 1024);
#pragma unroll 1
        for (int x = 1 + (r >> 2 & 2);; x++, zp += 896) {
          const char* wp = wd + (uint32_t)((224 * src + 32 * (src & 1) + 56 * part + (t & 7)) * 896 + (p ^ 2 * x & 7) * 112 + (t & 56) * 2);
          uint4 z[7];
#pragma unroll
          for (int i = 0; i < 7; i++) {
            if (i == 3 && part + (src & 1) == 4) wp -= 224 * 896;
            z[i] = ldg4(wp + i * 8 * 896);
          }
#pragma unroll
          for (int i = 0; i < 7; i++) st_rlx4(zp + i * 1792, z[i].x, z[i].y, z[i].z, z[i].w);
          if (!(x & 1)) break;
        }
      }
      STAMPP(5);
      asm volatile("fence.proxy.async.global;" ::: "memory");
      __syncwarp();
      if (lane == 0) red_release(&g_cnt[C_WD + p * 32]);
      STAMPP(7);
      cnt_wait<true>(&g_cnt[C_WD + p * 32], e1 * 32, budget);
      STAMPP(18);
      asm volatile("fence.proxy.async.global;" ::: "memory");
      if (lane < 2) mbar_arrive(BAR(B_WDOK));
#pragma unroll 1
      for (int j = 0; j < 4; j += j + 1) {
        const uint32_t bar = BAR(B_WB + 4 * g + j);
        const char* src = buf + (j < 3 ? A_HH + (cta ^ j) * 2 * STG + g * TILE : A_PS + (cta * 6 + 3 * g) * 7168);
        if (j != 1) cnt_wait(&g_cnt[(j < 3 ? C_ROW + r * 32 + 4 + 2 * (p & 6) : C_PS + cta * 8) + g], e1 * 8, budget);
        WAIT(j >= 2 ? BAR(B_HFREE + 2 * g + 1) : BAR(B_EMPTY + 6 + g), j >> 1);
        if (elect()) {
          mbar_expect_tx(bar, TILE);
          bulk_g2s(sb + (6 + g) * STG + (j & 1) * TILE, src, TILE, bar);
        }
      }
      SPINS(28 + g);
      if (g && lane == 0) DUMP(2);
    }
  } else {
    STAMP(60);
    bar_sync<0, 384>();
    STAMP(63);
    asm volatile("setmaxnreg.inc.sync.aligned.u32 224;");
    STAMP(61);
    const int g = warp >> 2, gq = lane >> 2, tq = lane & 3;
    const uint64_t dk = d128 + kh;
    uint4 A[28];
    float rs0, rs1, m0, m1;
    float acc0[28], acc1[28];
    uint32_t mb0, mb1;
    {
      uint32_t la[4];
#pragma unroll
      for (int i = 0; i < 4; i++) {
        la[i] = sb + OFF_X + warp * TILE + (lane & 15) * 128 + (((2 * i + (lane >> 4)) ^ (lane & 7)) << 4);
        asm volatile("" : "+r"(la[i]));
      }
      STAMP(62);
      WAIT(BAR(B_XB + warp), 0);
      STAMP(1);
#pragma unroll
      for (int ks = 0; ks < 28; ks++) A[ks] = ldsm4(la[ks & 3] + (ks >> 2) * 2048);
      float cs[4][4] = {};
#pragma unroll
      for (int ks = 0; ks < 28; ks++) mma16816(cs[ks & 3], A[ks].x, A[ks].y, A[ks].z, A[ks].w, 0x3F803F80u, 0x3F803F80u);
      m0 = ((cs[0][0] + cs[1][0]) + (cs[2][0] + cs[3][0])) * (1.f / DM);
      m1 = ((cs[0][2] + cs[1][2]) + (cs[2][2] + cs[3][2])) * (1.f / DM);
      mb0 = pack2(m0, m0); mb1 = pack2(m1, m1);
      if (lane == 0) mbar_arrive(BAR(B_XFREE) + (mb0 & zero));
    }
    STAMP(2);
    uint32_t pa[7];
    {
      const uint32_t prow = sb + OFF_PK + warp * 4096 + gq * 128 + (gq << 4), t = tq >> 1;
      const uint32_t b2 = (prow + ((4 * tq + 8) & 15)) ^ (t << 4);
      pa[0] = prow + 4 * tq; pa[1] = pa[0] ^ 16; pa[2] = pa[0] ^ 32;
      pa[3] = (prow + 4 * (tq & 1)) ^ (48 + 16 * t);
      pa[4] = b2 ^ 64; pa[5] = b2 ^ 80 ^ (t << 5); pa[6] = b2 ^ 96;
#pragma unroll
      for (int j = 0; j < 7; j++) asm volatile("" : "+r"(pa[j]));
    }
    auto sqs = [&](int q) {
      uint4 s;
#pragma unroll
      for (int ks = 7 * q; ks < 7 * q + 7; ks++) {
        if (ks % 7 == 0) s = make_uint4(sq2(A[ks].x), sq2(A[ks].y), sq2(A[ks].z), sq2(A[ks].w));
        else s = make_uint4(sq2(A[ks].x, s.x), sq2(A[ks].y, s.y), sq2(A[ks].z, s.z), sq2(A[ks].w, s.w));
      }
      s.x = add2(s.x, s.z);
      s.y = add2(s.y, s.w);
      rs0 = (q ? rs0 : 0.f) + (bf_lo(s.x) + bf_hi(s.x));
      rs1 = (q ? rs1 : 0.f) + (bf_lo(s.y) + bf_hi(s.y));
      if (q == 3) {
        rs0 += shx(rs0, 1); rs1 += shx(rs1, 1);
        rs0 += shx(rs0, 2); rs1 += shx(rs1, 2);
      }
      asm volatile("" : "+f"(rs0), "+f"(rs1));
    };
    auto sub = [&](int q) {
#pragma unroll
      for (int ks = 7 * q; ks < 7 * q + 7; ks++)
        A[ks] = make_uint4(sub2(A[ks].x, mb0), sub2(A[ks].y, mb1), sub2(A[ks].z, mb0), sub2(A[ks].w, mb1));
    };
    uint32_t sdw, mw;
    PhiC c0, c1;
#define PHIP(a, b, c) phi2(a, b, c)
#define CW(c) bf_lo(c.w)
    auto stats = [&] {
      const float d0 = m0 - bf_lo(mb0), d1 = m1 - bf_lo(mb1);
      const float q0 = fmaxf(rs0 * (1.f / DM) - d0 * d0, 0.f) + 1e-5f;
      const float q1 = fmaxf(rs1 * (1.f / DM) - d1 * d1, 0.f) + 1e-5f;
      rs0 = rsqf(q0);
      rs1 = rsqf(q1);
      const float sd = (tq & 2 ? q1 * rs1 : q0 * rs0);
      sdw = pack2(sd, sd - bf_lo(pack2(sd, 0.f)));
      mw = pack2(tq ? m1 : m0, tq ? d1 : d0);
      c0 = {rs0 * 1.4426950408889634f, lg2f(rs0), pack2(rs0 * rs0, rs0 * rs0), pack2(rs0, rs0), pack2(1e-6f * rs0, 1e-6f * rs0)};
      c1 = {rs1 * 1.4426950408889634f, lg2f(rs1), pack2(rs1 * rs1, rs1 * rs1), pack2(rs1, rs1), pack2(1e-6f * rs1, 1e-6f * rs1)};
      asm volatile("" : "+r"(sdw), "+r"(mw), "+f"(c0.x), "+f"(c0.y), "+r"(c0.z), "+r"(c0.s), "+r"(c0.w), "+f"(c1.x), "+f"(c1.y), "+r"(c1.z), "+r"(c1.s), "+r"(c1.w));
    };
    auto alu = [&](auto S) {
      sfor<4>([&](auto Q) { if (SUBM >> 4 * S + Q & 1) sub(Q); });
      sfor<4>([&](auto Q) { if (SQS >> 4 * S + Q & 1) sqs(Q); });
      if (S == STP) stats();
    };
    alu(IC<0>{});
    sfor<4>([&](auto J) {
      constexpr int j = J;
      WAIT(BAR(B_K + j), 0);
      STAMP(26 + j);
      if (j == 0 && g) bar_sync<7, 256>();
      wg_fence();
      sfor<7>([&](auto I) { wgmma_rs_n56<2 * STG + (7 * j + I) * 2048>(acc0, A[7 * j + I], dk, j + I != 0); });
      if (j == 0 && !g) bar_arrive<7, 256>();
      if (j == 3) wg_commit();
      alu(IC<j + 1>{});
    });
    STAMP(3);
    WAIT(BAR(B_V), 0);
    STAMP(10);
    wg_fence();
    sfor<7>([&](auto I) { wgmma_rs_n56<I * 2048>(acc1, A[I], dk, I != 0); });
    wg_commit();
    alu(IC<5>{});
    WAIT(BAR(B_XFREE), 0);
    wg_wait<1>();
    acc_fence(acc0);
    STAMP(4);
    if (lane == 0) mbar_arrive(BAR(B_KFREE));
    sfor<7>([&](auto J) {
      constexpr int j = J;
      sfor<(VPAT >> 4 * j & 15)>([&](auto I) {
        constexpr int ks = 7 + digits(VPAT, j) + I;
        if (ks % 7 == 0) STAMP(30 + ks / 7 * 2);
        if (ks % 7 == 0) WAIT(BAR(B_V + ks / 7), 0);
        if (ks % 7 == 0) STAMP(31 + ks / 7 * 2);
        if (ks % 7 == 0) wg_fence();
        wgmma_rs_n56<ks * 2048>(acc1, A[ks], dk, 1);
      });
      sts1(pa[j], PHIP(acc0[4 * j], acc0[4 * j + 1], c0));
      sts1(pa[j] + 1024, PHIP(acc0[4 * j + 2], acc0[4 * j + 3], c1));
    });
    wg_commit();
    sts1(((pa[0] & ~15u) ^ (48 + 64 * (tq & 1))) + 2048 + 8 + ((tq >> 1) << 10), sdw);
    if (tq < 2) sts4(sb + OFF_XS + 112 + warp * 2048 + tq * 1024 + gq * 112, mw, 0, 0, 0);
    wg_wait<0>();
    acc_fence(acc1);
    STAMP(5);
    STAMP(54);
#pragma unroll
    for (int j = 0; j < 7; j++) {
      sts1(pa[j] + 2048, pack2(acc1[4 * j], acc1[4 * j + 1]));
      sts1(pa[j] + 3072, pack2(acc1[4 * j + 2], acc1[4 * j + 3]));
    }
    fence_async_smem();
    if (lane == 0) mbar_arrive(BAR(B_VFREE));
    if (g == 0) {
      bar_arrive<1, 256>();
      bar_sync<3, 256>();
    } else {
      bar_sync<1, 256>();
      STAMP(55);
      float kv[32];
      wg_fence();
      sfor<8>([&](auto I) {
        constexpr int o = OFF_PK + I * 4096;
        wgmma_ss_n64<o, o + 2048>(kv, d128, d128, I != 0);
      });
      wg_commit();
      bar_arrive<3, 256>();
      WAIT(BAR(B_INIT), 0);
      char* da = buf + (A_KVR + p * KVR_B + (warp & 3) * 2176) + (uint32_t)(gq * 64 + (tq & 1) * 32 + (tq & 2) * 8);
      char *db = da + (uint32_t)(1152 + gq * 64), *dz = da + (uint32_t)(1008 - gq * 48);
      asm volatile("" : "+l"(da), "+l"(db), "+l"(dz));
      wg_wait<0>();
      acc_fence(kv);
      STAMP(56);
      auto put = [&](const float* v, int n) {
        const int b = n & 2;
        if (!b || (tid & 48) != 48) {
          if (n & 1) red_add4(b ? db + 64 : da + 512, v[b + 8], v[b + 9], tq & 2 ? v[b + 5] : v[b + 12], tq & 2 ? 1.f : v[b + 13]);
          else red_add4(b ? db : da, v[b], v[b + 1], v[b + 4], tq & 2 ? 1.f : v[b + 5]);
        }
      };
#pragma unroll
      for (int i = 0; i < 16; i++) kv[i] = warp & 2 ? kv[16 + i] : kv[i];
#pragma unroll
      for (int n = 0; n < 4; n++) put(kv, n);
      if (tq == 2) red_add4(dz, kv[12] + kv[13], kv[14] + kv[15], 0.f, 1.f);
    }
    STAMP(6);
    const uint32_t par = ~ld_rlx1(&g_cnt[C_ROW + r * 32 + (tid >> 7)]) >> 5;
    WAIT(BAR(B_Q), 0);
    wg_fence();
    sfor<28>([&](auto I) { wgmma_rs_n56<I * 2048>(acc0, A[I], dq + kh, I != 0); });
    wg_commit();
    const uint32_t wb = BAR(B_WB) + 32 * g;
    const int wq4 = warp & 3;
    char* const oblk = buf + (A_O + (r * 2 + g) * 2 * STG);
    const uint32_t gsub = sb + OFF_G + g * 2 * STG + wq4 * 3584 + lane * 16, gsub8 = gsub - lane * 8;
    const char* const olane = oblk + (uint32_t)(wq4 * 3584 + lane * 16);
    char* const ob = oblk + (uint32_t)((p >> 1) * TILE + wq4 * 3584 + kh * 896 + gq * 16);
    char *ob16 = ob + tq * 128, *ob8 = ob + 512 + (tq >> 1) * 128 + (tq & 1) * 8, *ob4 = ob + 768 + tq * 4;
    unsigned* cnt = &g_cnt[C_ROW + r * 32];
    asm volatile("" : "+l"(ob16), "+l"(ob8), "+l"(ob4), "+l"(cnt));
    wg_wait<0>();
    acc_fence(acc0);
    STAMP(7);
    if (lane == 0) mbar_arrive(BAR(B_QFREE));
    uint32_t R[14];
    {
      uint4 Q[4];
#pragma unroll
      for (int j = 0; j < 7; j++) {
        const uint32_t lo = PHIP(acc0[4 * j], acc0[4 * j + 1], c0);
        const uint32_t hi = PHIP(acc0[4 * j + 2], acc0[4 * j + 3], c1);
        if (j & 1) { Q[j >> 1].z = lo; Q[j >> 1].w = hi; } else { Q[j >> 1].x = lo; Q[j >> 1].y = hi; }
      }
      Q[3].z = 0; Q[3].w = 0;
      STAMP(8);
      WAIT(BAR(B_KVB), 0);
      STAMP(9);
      float o[32];
      wg_fence();
      sfor<4>([&](auto I) { wgmma_rs_n64<OFF_KVB + I * 2048>(o, Q[I], d128, I != 0); });
      wg_commit();
            wg_wait<0>();
      if (ORED == 2) red_inc(cnt, tid & 159);
      acc_fence(o);
      const float da0 = rcpf(o[28] + CW(c0)), db0 = rcpf(o[29] + CW(c0)), da1 = rcpf(o[30] + CW(c1)), db1 = rcpf(o[31] + CW(c1));
      if (ORED == 3) red_inc(cnt, tid & 159 | __float_as_uint(db1) & zero);
      uint32_t P[14];
#pragma unroll
      for (int j = 0; j < 7; j++) {
        const bool first = j < 2 || (j < 4 && tq < 3);
        const float s0 = first ? da0 : db0, s1 = first ? da1 : db1;
        P[2 * j] = pack2(o[4 * j] * s0, o[4 * j + 1] * s0);
        P[2 * j + 1] = pack2(o[4 * j + 2] * s1, o[4 * j + 3] * s1);
        if (0x53 >> j & 1) { P[2 * j] = tag(P[2 * j], par); P[2 * j + 1] = tag(P[2 * j + 1], par); }
      }
      auto publish = [&] {
#pragma unroll
        for (int h = 0; h < 2; h++) {
          st_rlx4(ob16 + 1792 * h, P[h], P[2 + h], P[4 + h], P[6 + h]);
          st_rlx2(ob8 + 1792 * h, P[8 + h], P[10 + h]);
          st_rlx1(ob4 + 1792 * h, P[12 + h]);
          if (ORED == 5 && h == 0) red_inc(cnt + g, lane);
        }
      };
      if (!g) {
        if (ORED == 4) red_inc(cnt, lane);
        publish();
        if (ORED == 6) red_inc(cnt, lane);
        STAMP(11);
        if (lane == 0) mbar_arrive(BAR(B_OFREE));
        const int sec = min(lane, 27);
        uint32_t ta = sb + OFF_WO + wq4 * 3584 + sec * 32 + (0x3625410 >> (sec & 28) & 7) * 4;
        uint32_t gs = gsub - 2 * STG;
        const char* ol = olane + (A_WOC - A_O + (p - 2 * r) * 2 * STG);
        asm volatile("" : "+r"(ta), "+l"(ol));
#pragma unroll 1
        for (int n = 0; n < 12; n++) {
          WAIT(n < 4 ? BAR(B_WO) : BAR(B_WB - 4) + 8 * n, 0);
          STAMPD(max(n - 3, 1));
          RETRY(n < 4 ? 30 : n - 4, fixq(ta, gs, ol, par, budget));
          bar_arrive_id(4 + n);
          ol = n == 3 ? olane : ol + TILE;
          ta += TILE;
          gs += TILE;
        }
        bar_sync<3, 256>();
      } else {
        const uint32_t wa = sb + (lane >> 4) * 1024 + (lane & 7) * 128 + ((((2 * wq4 + (lane >> 3 & 1)) ^ lane) & 7) << 4);
        float hacc[64];
        {
          const uint32_t one = 0x3F80u << (lane * 4 & 16), m = tq == 0 ? 0xBF80BF80u : 0, id = (tid >> 3 ^ tq) & 15;
          uint4 E[4];
#pragma unroll
          for (int i = 0; i < 4; i++) {
            const uint32_t e = id == 4 * i ? one : 0;
            E[i] = make_uint4(e, 0, i < 3 ? 0 : m, i < 3 ? e : m);
            asm volatile("" : "+r"(E[i].x), "+r"(E[i].y), "+r"(E[i].z), "+r"(E[i].w));
          }
          wg_fence();
          sfor<8>([&](auto I) { wgmma_rk_n64<OFF_XS + I / 4 * 8192 + I % 4 * 32, I / 4 * 32>(hacc, E[I % 4], d128, I % 4 != 0); });
          wg_commit();
        }
        WAIT(BAR(B_WO), 0);
        sfor<28>([&](auto KS) {
          constexpr int ks = KS;
          if (ks == XW) {
            wg_wait<0>();
            acc_fence(hacc);
            if (lane == 0) mbar_arrive(BAR(B_OFREE));
          }
          if (ks == ORED1) red_inc(cnt + 1, lane);
          if (ks == OPUB) {
            WAIT(BAR(B_WO), 0);
            publish();
            STAMP(11);
            WAIT(BAR(B_WO), 0);
          }
          if (ks % 7 == 0) bar_sync<4 + ks / 7, 256>();
          A[ks] = ldsm4t(wa + OFF_WO + ks * 2048);
        });
        if (lane < 2) mbar_arrive(BAR(B_WOFREE) + (A[27].x & zero));
        if (OPUB >= 28) {
          if (OPUB == 29) WAIT(BAR(B_WOFREE), 0);
          if (OPUB == 30) WAIT(BAR(B_WB), 0);
          if (OPUB > 30) { const uint32_t t0 = clock(); while (clock() - t0 < OPUB); }
          if (ORED1 == 28) red_inc(cnt + 1, lane);
          publish();
          STAMP(11);
        }
        STAMP(10);
        uint32_t ma = sb + OFF_M + tq * 8;
        char* hb = oblk + (uint32_t)(FRAG_B - 2 * STG + (p >> 1) * TILE + (wq4 < 3 ? kh * 2048 + wq4 * 512 + lane * 16 : 1536 + kh * 256 + lane * 8));
        asm volatile("" : "+l"(hb));
        STAMP(16);
#pragma unroll 1
        for (int h = 0; h < 2; h++) {
          const uint64_t dh = dko + h * (2 * STG >> 4);
          sfor<4>([&](auto Q) {
            constexpr int q = Q;
            bar_sync_id(8 + 4 * h + q);
            STAMPD(1 + 4 * h + q);
            wg_fence();
            sfor<7>([&](auto I) { wgmma_rk_n64<OFF_G + q * TILE + I * 256>(hacc, A[7 * q + I], dh, 1); });
          });
          wg_commit();
          if (h) bar_sync<6, 160>();
          wg_wait<0>();
          if (HRED == 5 || HRED1 == 5) red_inc(cnt + 2, HRED == HRED1 ? lane : HRED == 5 ? lane | h : lane | h ^ 1);
          acc_fence(hacc);
          STAMPD(12 + 2 * h);
          if (lane < 2) mbar_arrive(BAR(B_ORD) + 8 * h);
#pragma unroll
          for (int i = 0; i < 4; i++) {
            const float* a = hacc + 8 * i;
            st_rlx42(hb + 3584 * i, tag(transp(pack2(a[0], a[1])), par), transp(pack2(a[4], a[5])), transp(pack2(a[2], a[3])), transp(pack2(a[6], a[7])), wq4 - 3);
            if (HRED == 6 + i || HRED1 == 6 + i) red_inc(cnt + 2, HRED == HRED1 ? lane : HRED == 6 + i ? lane | h : lane | h ^ 1);
          }
          if (tid >= 224 && gq == 0) {
#pragma unroll
            for (int j = 0; j < 8; j++) sts2(ma + 32 * j, __float_as_uint(hacc[4 * j + 2]), __float_as_uint(hacc[4 * j + 3]));
          }
          STAMPD(13 + 2 * h);
          if (h) break;
          bar_arrive<3, 256>();
#pragma unroll
          for (int i = 0; i < 32; i++) hacc[i] = hacc[32 + i];
          acc_fence(hacc);
          hb += 2 * STG;
          ma += 256;
          cnt++;
        }
        bar_sync<5, 128>();
      }
      const char* const rb = olane + (FRAG_B + (p >> 1) * TILE);
#pragma unroll
      for (int i = 0; i < 3; i++) {
        const uint4 v = ld_rlx4(rb + kh * 2048 + 512 * i);
        R[4 * i] = v.x; R[4 * i + 1] = v.y; R[4 * i + 2] = v.z; R[4 * i + 3] = v.w;
      }
      const uint2 v = ld_rlx2(rb + 1536 + kh * 256 - lane * 8);
      R[12] = v.x; R[13] = v.y;
    }
    char* hdst = buf + (A_HH + cta * 2 * STG + warp * 3584) + (uint32_t)(lane * 16);
    {
#define GLU(gt, up, e) fmaf((up) * (e), tanhf_((gt) * (e)), (up) * (e))
      float acc[64];
      uint4 own[5];
#pragma unroll
      for (int i = 0; i < 5; i++) asm volatile("" : "=r"(own[i].x), "=r"(own[i].y), "=r"(own[i].z), "=r"(own[i].w));
      sfor<LA>([&](auto Q) {
        WAIT(wb + 8 * Q, 1);
        STAMP(57 + Q);
        load7s<Q * TILE>(&A[7 * Q], gsub, gsub8);
      });
#pragma unroll 1
      for (int c = 0; c < 3; c++) {
        const uint32_t half = (c & 1) * 4;
        const uint64_t dc = d128 + half * (STG >> 4);
        if (GGATE && c == 1) WAIT(BAR(B_HFREE + 1 + GGATE), 0);
        sfor<4>([&](auto KQ) {
          constexpr int kq = KQ;
          if (FW == 1) WAIT(BAR(B_FULL + kq) + 8 * half, c >> 1);
          if (c == 0) {
            if (kq < 4 - LA && LDP == 0) WAIT(wb + 8 * (kq + LA), 1);
            RETRY(8 + kq + 4 * g, fix7t<A_H + kq * TILE>(&A[7 * kq], buf + r * 4 * STG, gsub, gsub8, par, budget));
            STAMP(42 + kq);
            if (lane == 0) mbar_arrive(BAR(B_HFREE + kq / 2) + 16 * g);
            if (kq < 4 - LA && LDP == 1) WAIT(wb + 8 * (kq + LA), 1);
            STAMP(46 + kq);
            if (FW != 2 && kq < 4 - LA && LDP < 2) load7s<(kq + LA) % 4 * TILE>(&A[7 * ((kq + LA) % 4)], gsub, gsub8);
          }
          if (FW != 1) WAIT(BAR(B_FULL + kq) + 8 * half, c >> 1);
          if (FW == 2 && c == 0 && kq < 4 - LA && LDP < 2) load7s<(kq + LA) % 4 * TILE>(&A[7 * ((kq + LA) % 4)], gsub, gsub8);
          STAMPD(30 + 4 * c + kq);
          wg_fence();
          sfor<7>([&](auto I) { wgmma_rs_n128<kq * STG + koff(I, 1024)>(acc, A[7 * kq + I], dc, kq + I != 0); });
          wg_commit();
          if (c == 0) STAMP(50 + kq);
          if (LDP == 2 && c == 0 && kq < 4 - LA) {
            WAIT(wb + 8 * (kq + LA), 1);
            load7s<(kq + LA) % 4 * TILE>(&A[7 * ((kq + LA) % 4)], gsub, gsub8);
          }
          if (c == 0 && (SQM >> 4 * kq & 15)) {
            sfor<4>([&](auto Q) { if (SQM >> 4 * kq + Q & 1) sqs(Q); });
            if (kq == 3) {
              rs0 = 0.5f * rsqf(rs0 * (1.f / DM) + 1e-5f);
              rs1 = 0.5f * rsqf(rs1 * (1.f / DM) + 1e-5f);
              asm volatile("" : "+f"(rs0), "+f"(rs1));
            }
          }
          if (kq > 0) {
            wg_wait<1>();
            if (lane == 0) mbar_arrive(BAR(B_EMPTY + kq - 1) + 8 * half);
          }
        });
        wg_wait<0>();
        acc_fence(acc);
        if (lane == 0) mbar_arrive(BAR(B_EMPTY + 3) + 8 * half);
        STAMPD(17 + c);
        constexpr int GO = SWAP ? 32 : 0, UO = SWAP ? 0 : 32;
        own[0] = own[4];
#pragma unroll
        for (int i = 0; i < 4; i++) {
          uint32_t w[4];
#pragma unroll
          for (int t = 0; t < 2; t++) {
            const int b = 8 * i + 4 * t;
            w[2 * t] = pack2(GLU(acc[GO + b], acc[UO + b], rs0), GLU(acc[GO + b + 1], acc[UO + b + 1], rs0));
            w[2 * t + 1] = pack2(GLU(acc[GO + b + 2], acc[UO + b + 2], rs1), GLU(acc[GO + b + 3], acc[UO + b + 3], rs1));
          }
          if (i == 3 && c == 1) hdst += STG - 3584;
          own[i + 1] = make_uint4(tag(w[0], par), w[1], w[2], w[3]);
          st_rlx4(hdst + i * 512, own[i + 1].x, w[1], w[2], w[3]);
        }
        hdst += 2048;
        red_inc(&g_cnt[C_ROW + r * 32 + 4 + 2 * (p & 6) + g], lane | c ^ 1);
      }
      float acct[32];
      sfor<2>([&](auto H) {
        constexpr int h = H;
        WAIT(BAR(B_FULL + 4 + h), 1);
        wg_fence();
        sfor<14>([&](auto I) { wgmma_rs_n64<(4 + h) * STG + I / 7 * (TILE / 2) + koff(I % 7, 512)>(acct, A[14 * h + I], d64, h + I != 0); });
        wg_commit();
      });
      auto ldh = [&](int k) {
        WAIT(wb + 8 * k, 0);
#pragma unroll
        for (int i = 0; i < 7; i++) A[7 * k + 7 + i] = lds4(gsub - g * STG + 2 * STG + k * TILE + i * 512);
      };
      wg_wait<1>();
      if (lane == 0) mbar_arrive(BAR(B_EMPTY + 4));
      if (HLD >= 1) ldh(0);
      wg_wait<0>();
      acc_fence(acct);
      if (lane == 0) mbar_arrive(BAR(B_EMPTY + 5));
      if (HLD == 2) ldh(1);
      STAMP(20);
      constexpr int GO = SWAP ? 16 : 0, UO = SWAP ? 0 : 16;
#pragma unroll
      for (int i = 0; i < 2; i++) {
        uint32_t w[4];
#pragma unroll
        for (int t = 0; t < 2; t++) {
          const int b = 8 * i + 4 * t;
          w[2 * t] = pack2(GLU(acct[GO + b], acct[UO + b], rs0), GLU(acct[GO + b + 1], acct[UO + b + 1], rs0));
          w[2 * t + 1] = pack2(GLU(acct[GO + b + 2], acct[UO + b + 2], rs1), GLU(acct[GO + b + 3], acct[UO + b + 3], rs1));
        }
        st_rlx4(hdst + i * 512, tag(w[0], par), w[1], w[2], w[3]);
        A[5 + i] = make_uint4(w[0], w[1], w[2], w[3]);
      }
#pragma unroll
      for (int i = 0; i < 5; i++) A[i] = own[i];
    }
    STAMP(21);
    {
      const char* const hnb = hdst + (1 - 2 * kh) * 2 * STG;
      uint32_t eye = tq == gq >> 1 ? 0x3F80u << (16 * (gq & 1)) : 0;
      auto add = [&](float (&a)[28], const uint32_t (&v)[14]) {
#pragma unroll
        for (int j = 0; j < 7; j++)
          asm("mma.sync.aligned.m16n8k8.row.col.f32.bf16.bf16.f32 {%0,%1,%2,%3}, {%4,%5}, {%6}, {%0,%1,%2,%3};"
              : "+f"(a[4 * j]), "+f"(a[4 * j + 1]), "+f"(a[4 * j + 2]), "+f"(a[4 * j + 3]) : "r"(v[2 * j]), "r"(v[2 * j + 1]), "r"(eye));
      };
      auto addp = [&](float (&a)[28], const uint32_t (&v)[14], const uint32_t (&w)[14]) {
#pragma unroll
        for (int j = 0; j < 7; j++)
          asm("mma.sync.aligned.m16n8k16.row.col.f32.bf16.bf16.f32 {%0,%1,%2,%3}, {%4,%5,%6,%7}, {%8,%8}, {%0,%1,%2,%3};"
              : "+f"(a[4 * j]), "+f"(a[4 * j + 1]), "+f"(a[4 * j + 2]), "+f"(a[4 * j + 3])
              : "r"(v[2 * j]), "r"(v[2 * j + 1]), "r"(w[2 * j]), "r"(w[2 * j + 1]), "r"(eye));
      };
      auto send = [&](float (&acc)[28], int x) {
        acc_fence(acc);
        char* const pd = buf + (A_PS + ((cta ^ 2 * x) * 6 + 3 * g + x - 1) * 7168 + (warp & 3) * 1792);
        uint32_t P[14];
#pragma unroll
        for (int j = 0; j < 14; j++) P[j] = pack2(acc[2 * j], acc[2 * j + 1]);
        publish7(pd + (uint32_t)(lane * 16), pd + 1536 + (uint32_t)(lane * 8), P, par);
        if (x < 3) red_inc(&g_cnt[C_PS + (cta ^ 2 * x) * 8 + g], lane);
      };
      sfor<4>([&](auto K) {
        constexpr int k = K;
        if (k > 1) {
          wg_wait<1>();
          if (lane == 0) mbar_arrive(BAR(B_EMPTY + k - 2));
        }
        if (FW2 == 1) WAIT(BAR(B_FULL + k), 0);
        if (k) RETRY(16 + k + 4 * g, fix7<-2560 - (k < 3) * STG>(&A[7 * k], k > 1 ? hnb : hdst, par, budget));
        if (k == 2 && lane < 2) mbar_arrive(BAR(B_HFREE + 1) + 16 * g);
        if (FW2 == 2) WAIT(BAR(B_FULL + k), 0);
        if (HLD == 0 ? k < 2 : HLD == 1 ? k == 1 : HLD == 3 ? k == 0 : false) {
          constexpr int kk = HLD ? 1 : k;
          WAIT(wb + 8 * kk, 0);
#pragma unroll
          for (int i = 0; i < 7; i++) A[7 * kk + 7 + i] = lds4(gsub - g * STG + 2 * STG + kk * TILE + i * 512);
        }
        if (k == 2) {
#pragma unroll
          for (int i = 0; i < 7; i++) A[21 + i] = ld_rlx4(hnb - 2560 + 512 * i);
        }
        if (FW2 == 0) WAIT(BAR(B_FULL + k), 0);
        wg_fence();
        sfor<7>([&](auto I) { wgmma_rs_n56<k * STG + I * 3584>(acc0, A[7 * k + I], d0, k + I != 0); });
        if (k == 3) wg_commit();
        sfor<7>([&](auto I) { wgmma_rs_n56<k * STG + I * 3584 + 896>(acc1, A[7 * k + I], d0, k + I != 0); });
        wg_commit();
      });
      wg_wait<1>();
      send(acc0, 1);
      sfor<4>([&](auto K) {
        constexpr int k = K, s = (k + 4) % 6;
        WAIT(BAR(B_FULL + s), k >= 2);
        wg_fence();
        sfor<7>([&](auto I) { wgmma_rs_n56<s * STG + I * 3584>(acc0, A[7 * k + I], d1, k + I != 0); });
        wg_commit();
        if (k == 0) {
          wg_wait<1>();
          send(acc1, 2);
          const float m0 = __uint_as_float(lds1(sb + OFF_M + warp * 64 + gq * 4)), m1 = __uint_as_float(lds1(sb + OFF_M + warp * 64 + gq * 4 + 32));
#pragma unroll
          for (int i = 0; i < 28; i++) acc1[i] = i & 2 ? -m1 : -m0;
          if (TADD >= 2) add(acc1, R);
          acc_fence(acc1);
        }
      });
      if (g) bar_arrive<7, 256>();
      wg_wait<0>();
      STAMP(22);
      send(acc0, 3);
      if (!g) bar_sync<7, 256>();
      uint32_t P[3][14];
      const char* const ps = buf + (A_PS + (cta * 6 + 3 * g) * 7168 + (warp & 3) * 1792) + (uint32_t)(lane * 16);
      const char* const ps8 = ps - lane * 8;
      auto fetch = [&](int x) {
#pragma unroll
        for (int i = 0; i < 3; i++) {
          const uint4 v = ld_rlx4(ps + 7168 * x + 512 * i);
          P[x][4 * i] = v.x; P[x][4 * i + 1] = v.y; P[x][4 * i + 2] = v.z; P[x][4 * i + 3] = v.w;
        }
        const uint2 v = ld_rlx2(ps8 + 7168 * x + 1536);
        P[x][12] = v.x; P[x][13] = v.y;
      };
      const uint32_t pss = sb + (6 + g) * STG + (warp & 3) * 1792;
      auto fetchs = [&] {
        WAIT(wb + 24, 0);
#pragma unroll
        for (int x = 0; x < 2; x++) {
          const uint32_t a = pss + TILE + 7168 * x;
#pragma unroll
          for (int i = 0; i < 3; i++) {
            const uint4 v = lds4(a + 512 * i + lane * 16);
            P[x][4 * i] = v.x; P[x][4 * i + 1] = v.y; P[x][4 * i + 2] = v.z; P[x][4 * i + 3] = v.w;
          }
          const uint2 v = lds2(a + 1536 + lane * 8);
          P[x][12] = v.x; P[x][13] = v.y;
        }
      };
      WAIT(BAR(B_FULL + 5), 0);
      wg_fence();
      sfor<28>([&](auto I) {
        if (I == FPOS) {
          fetchs();
          fetch(2);
          wg_fence();
        }
        wgmma_rs_n56<(I / 7 + 4) % 6 * STG + I % 7 * 3584 + 896>(acc1, A[I], d1, 1);
      });
      wg_commit();
      STAMP(23);
      WAIT(BAR(B_FULL + 5), 0);
      uint32_t ob = pss + 7168 + (lane & 15) * 112 + (lane & 16);
      char* op = out + (uint32_t)((128 * r + (tid >> 5) * 16 + (lane >> 3)) * 896 + 112 * p + (lane & 7) * 16);
      uint32_t ia = pss + 7168 + (lane >> 3) * 112 + (lane & 7) * 16;
      asm volatile("" : "+r"(ob), "+l"(op), "+r"(ia));
      auto check = [&](int x) {
#pragma unroll 1
        while (stale(xor2(P[x][0], P[x][4], par) | xor2(P[x][8], P[x][12], par), budget)) fetch(x);
      };
      check(0);
      check(1);
      uint32_t o[14];
      {
        wg_wait<0>();
        acc_fence(acc1);
        STAMP(24);
        if (TADD == 0) add(acc1, R);
        if (TADD == 0 || TADD == 3) {
          add(acc1, P[0]);
          add(acc1, P[1]);
        } else addp(acc1, P[0], P[1]);
        acc_fence(acc1);
        WAIT(BAR(B_FULL + 5), 0);
        check(2);
        if (TADD == 1) addp(acc1, P[2], R);
        else add(acc1, P[2]);
#pragma unroll
        for (int j = 0; j < 14; j++) o[j] = pack2(acc1[2 * j], acc1[2 * j + 1]);
      }
#pragma unroll
      for (int i = 0; i < 3; i++)
        asm volatile("stmatrix.sync.aligned.m8n8.x4.shared.b16 [%0], {%1,%2,%3,%4};" ::"r"(ob + 32 * i), "r"(o[4 * i]), "r"(o[4 * i + 1]), "r"(o[4 * i + 2]), "r"(o[4 * i + 3]) : "memory");
      asm volatile("stmatrix.sync.aligned.m8n8.x2.shared.b16 [%0], {%1,%2};" ::"r"(ob + 96), "r"(o[12]), "r"(o[13]) : "memory");
      __syncwarp();
      {
        uint4 v[4];
#pragma unroll
        for (int i = 0; i < 4; i++) v[i] = lds4(ia + 448 * i);
        if ((lane & 7) < 7) {
#pragma unroll
          for (int i = 0; i < 4; i++) *(uint4*)(op + 3584 * i) = v[i];
        }
      }
      STAMP(25);
      SPINS(24 + g);
      GTIME(1);
    }
  }
}

typedef CUresult (*EncodeFn)(CUtensorMap*, CUtensorMapDataType, cuuint32_t, void*, const cuuint64_t*, const cuuint64_t*,
                             const cuuint32_t*, const cuuint32_t*, CUtensorMapInterleave, CUtensorMapSwizzle,
                             CUtensorMapL2promotion, CUtensorMapFloatOOBfill);

void make_map(EncodeFn enc, CUtensorMap* m, const void* p, int rank, const cuuint64_t* gd, const cuuint64_t* gs,
              const cuuint32_t* bd, CUtensorMapSwizzle sw) {
  const cuuint32_t es[5] = {1, 1, 1, 1, 1};
  ENC_CHECK(enc(m, CU_TENSOR_MAP_DATA_TYPE_BFLOAT16, rank, (void*)p, gd, gs, bd, es, CU_TENSOR_MAP_INTERLEAVE_NONE, sw,
                CU_TENSOR_MAP_L2_PROMOTION_NONE, CU_TENSOR_MAP_FLOAT_OOB_FILL_NONE));
}

}

extern "C" void kernel_launch(void* const* d_in, const int* in_sizes, int n_in, void* d_out, int out_size) {
  (void)in_sizes; (void)n_in; (void)out_size;
  static EncodeFn enc = nullptr;
  static char* buf = nullptr;
  if (!enc) {
    void* fn = nullptr;
    cudaDriverEntryPointQueryResult qr;
    cudaGetDriverEntryPoint("cuTensorMapEncodeTiled", &fn, cudaEnableDefault, &qr);
    enc = (EncodeFn)fn;
    cudaGetSymbolAddress((void**)&buf, g_buf);
    cudaFuncSetAttribute(fused_block_kernel<false>, cudaFuncAttributeMaxDynamicSharedMemorySize, SMEM_TOTAL);
    cudaFuncSetAttribute(fused_block_kernel<true>, cudaFuncAttributeMaxDynamicSharedMemorySize, SMEM_TOTAL);
  }
  const CUtensorMapSwizzle S128 = CU_TENSOR_MAP_SWIZZLE_128B;
  CUtensorMap mx, mqkv, mgu, mgu32;
  {
    cuuint64_t gd[3] = {64, SEQ, 7}, gs[2] = {DM * 2, 128};
    cuuint32_t bd[3] = {64, 16, 7};
    make_map(enc, &mx, d_in[0], 3, gd, gs, bd, S128);
  }
  {
    cuuint64_t gd[2] = {3 * DM, DM}, gs[1] = {3 * DM * 2};
    cuuint32_t bd[2] = {64, 112};
    make_map(enc, &mqkv, d_in[1], 2, gd, gs, bd, S128);
  }
  Pos pos = {};
  for (int i = 0; i < 32; i++) {
    const int c = 28 * (i >> 4) + 2 * (i >> 2 & 3) + 8 * (i & 3);
    pos.v[i >> 2] |= (uint32_t)(2 * (c < 32 ? (c & 6) * 4 + (c >> 3) * 2 : c < 48 ? 32 + (c & 2) * 4 + (c >> 1 & 6) : c)) << 8 * (i & 3);
  }
  const char *wg = (const char*)d_in[4], *wu = (const char*)d_in[5];
  const bool swap = wu < wg;
  const char* gub = swap ? wu : wg;
  const cuuint64_t gud = swap ? (cuuint64_t)(wg - wu) : (cuuint64_t)(wu - wg);
  {
    cuuint64_t gd[3] = {FF, DM, 2}, gs[2] = {FF * 2, gud};
    cuuint32_t bd[3] = {64, 112, 2};
    make_map(enc, &mgu, gub, 3, gd, gs, bd, S128);
  }
  {
    cuuint64_t gd[3] = {FF, DM, 2}, gs[2] = {FF * 2, gud};
    cuuint32_t bd[3] = {32, 224, 2};
    make_map(enc, &mgu32, gub, 3, gd, gs, bd, CU_TENSOR_MAP_SWIZZLE_64B);
  }
  (swap ? fused_block_kernel<true> : fused_block_kernel<false>)<<<128, 384, SMEM_TOTAL>>>(
      buf, (const char*)d_in[2], mn_desc(sb), mn_desc64(sb), mn_desc0(sb), mn_desc(sb + OFF_Q), mn_desc0(sb), k_desc0(sb), wg, wu, (const char*)d_in[6], (const char*)d_in[1], (char*)d_out, mx, mqkv, pos, mgu, mgu32);
}
```

```cpp
#include <cuda_runtime.h>
#include <cuda_bf16.h>
#include <cuda.h>
#include <stdint.h>
#include <stdio.h>
#include <utility>

#define SPIN_LIMIT (1 << 18)

namespace {

constexpr uint32_t sb = 1024;
constexpr int SEQ = 2048, DM = 448, FF = 1792;
constexpr int TILE = 14336;
constexpr int STG = 2 * TILE;
constexpr int SMEM_BAR = 8 * STG;
constexpr int SMEM_TOTAL = SMEM_BAR + 3072;
constexpr int OFF_X = 4 * STG, OFF_Q = 4 * STG, OFF_WO = 2 * STG, OFF_G = 4 * STG, OFF_PK = 6 * STG, OFF_KVB = OFF_PK + 32768, OFF_XS = OFF_KVB + 8192,
              OFF_M = SMEM_BAR + 512;
constexpr int B_XB = 0  , B_K = 8  , B_V = 12  , B_Q = 16, B_WO = 17, B_FULL = 18  , B_WB = 26  ,
              B_KVB = 34, B_WDOK = 35, B_INIT = 36,
              B_KFREE = 37, B_QFREE = 38, B_WOFREE = 39, B_OFREE = 40, B_HFREE = 41  , B_EMPTY = 45  , B_XFREE = 53, B_VFREE = 54,
              B_ORD = 55  ;

constexpr int KVR_B = 8704;
constexpr int FRAG_B = 16 * 4 * STG;
constexpr int A_CNT = 0, A_KVR = 24576, A_O = A_KVR + 8 * KVR_B + 2048, A_H = A_O + FRAG_B,
              A_HH = A_H + FRAG_B;
constexpr int HH_B = 128 * 2 * STG;
constexpr int A_PS = A_HH + HH_B;
constexpr int WDS = 25088;
constexpr int A_WD = A_PS + 128 * 3 * TILE;
constexpr int A_WOC = A_WD + 64 * WDS;

__device__ uint4 g_buf[(A_WOC + 16 * STG) / 16];
constexpr int C_ROW = 0, C_WD = 512, C_PS = 1024;
#define g_cnt ((unsigned*)buf + A_CNT / 4)
#define ENC_CHECK(x) (void)(x)
#define STAMP(i)
#define STAMPX(i)
#define GTIME(i)
#define STAMPP(i)
#define STAMPD(i)
#define DUMP(row)

__device__ __forceinline__ uint32_t smem_u32(const void* p) { return (uint32_t)__cvta_generic_to_shared(p); }
__device__ __forceinline__ void mbar_expect_tx(uint32_t bar, uint32_t bytes) {
  asm volatile("mbarrier.arrive.expect_tx.shared::cta.b64 _, [%0], %1;" ::"r"(bar), "r"(bytes) : "memory");
}
__device__ __forceinline__ void mbar_arrive(uint32_t bar) {
  asm volatile("mbarrier.arrive.shared::cta.b64 _, [%0];" ::"r"(bar) : "memory");
}
__device__ __forceinline__ void mbar_wait(uint32_t bar, uint32_t parity, int& budget) {
  asm volatile("{\n.reg .pred p;\nW:\nmbarrier.try_wait.parity.shared::cta.b64 p, [%1], %2;\n"
               "add.s32 %0, %0, -1;\nsetp.gt.and.s32 p, %0, 0, !p;\n@p bra W;\n}"
               : "+r"(budget) : "r"(bar), "r"(parity) : "memory");
}
__device__ __forceinline__ bool elect() {
  uint32_t v;
  asm volatile("{\n.reg .pred p;\nelect.sync _|p, 0xffffffff;\nselp.u32 %0, 1, 0, p;\n}" : "=r"(v));
  return v;
}
__device__ __forceinline__ void tma2d(uint32_t dst, const CUtensorMap* m, int c0, int c1, uint32_t bar) {
  asm volatile("cp.async.bulk.tensor.2d.shared::cluster.global.mbarrier::complete_tx::bytes [%0], [%1, {%3, %4}], [%2];"
               ::"r"(dst), "l"(m), "r"(bar), "r"(c0), "r"(c1) : "memory");
}
__device__ __forceinline__ void tma3d(uint32_t dst, const CUtensorMap* m, int c0, int c1, int c2, uint32_t bar) {
  asm volatile("cp.async.bulk.tensor.3d.shared::cluster.global.mbarrier::complete_tx::bytes [%0], [%1, {%3, %4, %5}], [%2];"
               ::"r"(dst), "l"(m), "r"(bar), "r"(c0), "r"(c1), "r"(c2) : "memory");
}
__device__ __forceinline__ void bulk_g2s(uint32_t dst, const void* src, uint32_t bytes, uint32_t bar) {
  asm volatile("cp.async.bulk.shared::cluster.global.mbarrier::complete_tx::bytes [%0], [%1], %2, [%3];"
               ::"r"(dst), "l"(src), "r"(bytes), "r"(bar) : "memory");
}
__device__ __forceinline__ void l2_prefetch(const void* p, uint32_t bytes) {
  asm volatile("cp.async.bulk.prefetch.L2.global [%0], %1;" ::"l"(p), "r"(bytes) : "memory");
}
__device__ __forceinline__ void prefetch_map(const CUtensorMap* m) {
  asm volatile("prefetch.tensormap [%0];" ::"l"(m) : "memory");
}
__device__ __forceinline__ void fence_async_smem() { asm volatile("fence.proxy.async.shared::cta;" ::: "memory"); }
template <int ID, int N> __device__ __forceinline__ void bar_arrive() { asm volatile("bar.arrive %0, %1;" ::"n"(ID), "n"(N) : "memory"); }
__device__ __forceinline__ void bar_arrive_id(int id) { asm volatile("bar.arrive %0, 256;" ::"r"(id) : "memory"); }
__device__ __forceinline__ void bar_sync_id(int id) { asm volatile("bar.sync %0, 256;" ::"r"(id) : "memory"); }
__device__ __forceinline__ void bar_sync_wg(int id) { asm volatile("bar.sync %0, 128;" ::"r"(id) : "memory"); }
template <int ID, int N> __device__ __forceinline__ void bar_sync() { asm volatile("bar.sync %0, %1;" ::"n"(ID), "n"(N) : "memory"); }
__device__ __forceinline__ void wg_fence() { asm volatile("wgmma.fence.sync.aligned;" ::: "memory"); }
__device__ __forceinline__ void wg_commit() { asm volatile("wgmma.commit_group.sync.aligned;" ::: "memory"); }
template <int N> __device__ __forceinline__ void wg_wait() { asm volatile("wgmma.wait_group.sync.aligned %0;" ::"n"(N) : "memory"); }
template <int N> __device__ __forceinline__ void acc_fence(float (&d)[N]) {
#pragma unroll
  for (int i = 0; i < N; i++) asm volatile("" : "+f"(d[i])::"memory");
}
constexpr uint64_t mn_desc(uint32_t addr) {
  return (uint64_t)((addr & 0x3FFFF) >> 4) | ((uint64_t)(TILE >> 4) << 16) | ((uint64_t)64 << 32) | ((uint64_t)1 << 62);
}
constexpr uint64_t mn_desc64(uint32_t addr) {
  return (uint64_t)((addr & 0x3FFFF) >> 4) | ((uint64_t)(TILE >> 4) << 16) | ((uint64_t)32 << 32) | ((uint64_t)2 << 62);
}
constexpr uint64_t mn_desc0(uint32_t addr) {
  return (uint64_t)((addr & 0x3FFFF) >> 4) | ((uint64_t)(1792 >> 4) << 16) | ((uint64_t)8 << 32);
}
constexpr uint64_t k_desc0(uint32_t addr) {
  return (uint64_t)((addr & 0x3FFFF) >> 4) | ((uint64_t)8 << 16) | ((uint64_t)(1792 >> 4) << 32);
}
__device__ __forceinline__ uint4 ld_rlx4(const void* p) {
  uint4 v;
  asm volatile("ld.relaxed.gpu.global.v4.u32 {%0,%1,%2,%3}, [%4];" : "=r"(v.x), "=r"(v.y), "=r"(v.z), "=r"(v.w) : "l"(p) : "memory");
  return v;
}
__device__ __forceinline__ uint2 ld_rlx2(const void* p) {
  uint2 v;
  asm volatile("ld.relaxed.gpu.global.v2.u32 {%0,%1}, [%2];" : "=r"(v.x), "=r"(v.y) : "l"(p) : "memory");
  return v;
}
__device__ __forceinline__ uint32_t ld_rlx1(const void* p) {
  uint32_t v;
  asm volatile("ld.relaxed.gpu.global.u32 %0, [%1];" : "=r"(v) : "l"(p) : "memory");
  return v;
}
__device__ __forceinline__ void st_rlx4(void* p, uint32_t a, uint32_t b, uint32_t c, uint32_t d) {
  asm volatile("st.relaxed.gpu.global.v4.u32 [%0], {%1,%2,%3,%4};" ::"l"(p), "r"(a), "r"(b), "r"(c), "r"(d) : "memory");
}
__device__ __forceinline__ void st_rlx2(void* p, uint32_t a, uint32_t b) {
  asm volatile("st.relaxed.gpu.global.v2.u32 [%0], {%1,%2};" ::"l"(p), "r"(a), "r"(b) : "memory");
}
__device__ __forceinline__ void st_rlx1(void* p, uint32_t a) {
  asm volatile("st.relaxed.gpu.global.u32 [%0], %1;" ::"l"(p), "r"(a) : "memory");
}
__device__ __forceinline__ void red_inc(unsigned* p, uint32_t skip) {
  asm volatile("{\n.reg .pred p;\nsetp.eq.u32 p, %1, 0;\n@p red.relaxed.gpu.global.inc.u32 [%0], 0xfffffffe;\n}" ::"l"(p), "r"(skip) : "memory");
}
__device__ __forceinline__ void red_release(unsigned* p) {
  asm volatile("red.release.gpu.global.inc.u32 [%0], 0xfffffffe;" ::"l"(p) : "memory");
}
__device__ __forceinline__ void st_rlx42(void* p, uint32_t a, uint32_t b, uint32_t c, uint32_t d, uint32_t all) {
  asm volatile("{\n.reg .pred p;\nsetp.ne.u32 p, %5, 0;\n@p st.relaxed.gpu.global.v4.u32 [%0], {%1,%2,%3,%4};\n"
               "@!p st.relaxed.gpu.global.v2.u32 [%0], {%1,%2};\n}" ::"l"(p), "r"(a), "r"(b), "r"(c), "r"(d), "r"(all) : "memory");
}
__device__ __forceinline__ void red_add4(void* p, float a, float b, float c, float d) {
  asm volatile("red.relaxed.gpu.global.add.v4.f32 [%0], {%1,%2,%3,%4};" ::"l"(p), "f"(a), "f"(b), "f"(c), "f"(d) : "memory");
}
__device__ __forceinline__ void eq_wait(const void* p, uint32_t target, int& budget) {
  asm volatile("{\n.reg .pred p;\n.reg .b32 v;\nW:\nld.relaxed.gpu.global.b32 v, [%1];\nadd.s32 %0, %0, -1;\n"
               "setp.gt.s32 p, %0, 0;\nsetp.gt.and.u32 p, v, %2, p;\n@p bra W;\n}"
               : "+r"(budget) : "l"(p), "r"(target) : "memory");
}
template <bool ACQ = false>
__device__ __forceinline__ void cnt_wait(const unsigned* p, uint32_t target, int& budget) {
  if (ACQ)
    asm volatile("{\n.reg .pred p;\n.reg .s32 v;\nW:\nld.acquire.gpu.global.s32 v, [%1];\nadd.s32 %0, %0, -1;\n"
                 "setp.gt.s32 p, %0, 0;\nsub.s32 v, v, %2;\nsetp.lt.and.s32 p, v, 0, p;\n@p bra W;\n}"
                 : "+r"(budget) : "l"(p), "r"(target) : "memory");
  else
  asm volatile("{\n.reg .pred p;\n.reg .s32 v;\nW:\nld.relaxed.gpu.global.s32 v, [%1];\nadd.s32 %0, %0, -1;\n"
               "setp.gt.s32 p, %0, 0;\nsub.s32 v, v, %2;\nsetp.lt.and.s32 p, v, 0, p;\n@p bra W;\n}"
               : "+r"(budget) : "l"(p), "r"(target) : "memory");
}
__device__ __forceinline__ uint32_t or3(uint32_t a, uint32_t b, uint32_t c) {
  uint32_t r;
  asm("lop3.b32 %0, %1, %2, %3, 0xfe;" : "=r"(r) : "r"(a), "r"(b), "r"(c));
  return r;
}
__device__ __forceinline__ uint32_t xor2(uint32_t a, uint32_t b, uint32_t f) {
  uint32_t r;
  asm("lop3.b32 %0, %1, %2, %3, 0x7e;" : "=r"(r) : "r"(a), "r"(b), "r"(f));
  return r;
}
__device__ __forceinline__ bool stale(uint32_t bad, int& budget, uint32_t mask = 1) {
  uint32_t v;
  asm volatile("{\n.reg .pred p;\n.reg .b32 t;\nand.b32 t, %2, %3;\nsetp.ne.u32 p, t, 0;\nadd.s32 %1, %1, -1;\n"
               "setp.gt.and.s32 p, %1, 0, p;\nvote.sync.any.pred p, p, 0xffffffff;\nselp.u32 %0, 1, 0, p;\n}"
               : "=r"(v), "+r"(budget) : "r"(bad), "r"(mask));
  return v;
}
__device__ __forceinline__ uint32_t tag(uint32_t w, uint32_t par) {
  uint32_t r;
  asm("lop3.b32 %0, %1, %2, 1, 0xd8;" : "=r"(r) : "r"(w), "r"(par));
  return r;
}
__device__ __forceinline__ void sts1(uint32_t a, uint32_t v) { asm volatile("st.shared.u32 [%0], %1;" ::"r"(a), "r"(v) : "memory"); }
__device__ __forceinline__ void sts2(uint32_t a, uint32_t x, uint32_t y) {
  asm volatile("st.shared.v2.u32 [%0], {%1,%2};" ::"r"(a), "r"(x), "r"(y) : "memory");
}
__device__ __forceinline__ void sts4(uint32_t a, uint32_t x, uint32_t y, uint32_t z, uint32_t w) {
  asm volatile("st.shared.v4.u32 [%0], {%1,%2,%3,%4};" ::"r"(a), "r"(x), "r"(y), "r"(z), "r"(w) : "memory");
}
__device__ __forceinline__ uint32_t lds1(uint32_t a) {
  uint32_t v;
  asm volatile("ld.shared.u32 %0, [%1];" : "=r"(v) : "r"(a) : "memory");
  return v;
}
__device__ __forceinline__ uint2 lds2(uint32_t a) {
  uint2 v;
  asm volatile("ld.shared.v2.u32 {%0,%1}, [%2];" : "=r"(v.x), "=r"(v.y) : "r"(a) : "memory");
  return v;
}
__device__ __forceinline__ uint4 lds4(uint32_t a) {
  uint4 v;
  asm volatile("ld.shared.v4.u32 {%0,%1,%2,%3}, [%4];" : "=r"(v.x), "=r"(v.y), "=r"(v.z), "=r"(v.w) : "r"(a) : "memory");
  return v;
}
__device__ __forceinline__ uint4 ldsm4(uint32_t a) {
  uint4 v;
  asm volatile("ldmatrix.sync.aligned.m8n8.x4.shared.b16 {%0,%1,%2,%3}, [%4];" : "=r"(v.x), "=r"(v.y), "=r"(v.z), "=r"(v.w) : "r"(a) : "memory");
  return v;
}
__device__ __forceinline__ uint4 ldsm4t(uint32_t a) {
  uint4 v;
  asm volatile("ldmatrix.sync.aligned.m8n8.x4.trans.shared.b16 {%0,%1,%2,%3}, [%4];" : "=r"(v.x), "=r"(v.y), "=r"(v.z), "=r"(v.w) : "r"(a) : "memory");
  return v;
}
__device__ __forceinline__ uint32_t pack2(float lo, float hi) {
  uint32_t r;
  asm("cvt.rn.bf16x2.f32 %0, %1, %2;" : "=r"(r) : "f"(hi), "f"(lo));
  return r;
}
__device__ __forceinline__ float bf_lo(uint32_t w) { return __uint_as_float(w << 16); }
__device__ __forceinline__ float bf_hi(uint32_t w) { return __uint_as_float(w & 0xFFFF0000u); }
__device__ __forceinline__ uint32_t sub2(uint32_t a, uint32_t b) {
  uint32_t r;
  asm volatile("sub.rn.bf16x2 %0, %1, %2;" : "=r"(r) : "r"(a), "r"(b));
  return r;
}
__device__ __forceinline__ uint32_t add2(uint32_t a, uint32_t b) {
  uint32_t r;
  asm("add.rn.bf16x2 %0, %1, %2;" : "=r"(r) : "r"(a), "r"(b));
  return r;
}
__device__ __forceinline__ uint32_t transp(uint32_t a) {
  uint32_t r;
  asm volatile("movmatrix.sync.aligned.m8n8.trans.b16 %0, %1;" : "=r"(r) : "r"(a));
  return r;
}
__device__ __forceinline__ uint32_t sq2(uint32_t a) {
  uint32_t r;
  asm volatile("mul.rn.bf16x2 %0, %1, %1;" : "=r"(r) : "r"(a));
  return r;
}
__device__ __forceinline__ uint32_t sq2(uint32_t a, uint32_t c) {
  uint32_t r;
  asm volatile("fma.rn.bf16x2 %0, %1, %1, %2;" : "=r"(r) : "r"(a), "r"(c));
  return r;
}
__device__ __forceinline__ uint4 ldg4(const void* p) {
  uint4 v;
  asm volatile("ld.global.nc.v4.u32 {%0,%1,%2,%3}, [%4];" : "=r"(v.x), "=r"(v.y), "=r"(v.z), "=r"(v.w) : "l"(p));
  return v;
}
__device__ __forceinline__ void mma16816(float (&c)[4], uint32_t a0, uint32_t a1, uint32_t a2, uint32_t a3, uint32_t b0, uint32_t b1) {
  asm("mma.sync.aligned.m16n8k16.row.col.f32.bf16.bf16.f32 {%0,%1,%2,%3}, {%4,%5,%6,%7}, {%8,%9}, {%0,%1,%2,%3};"
      : "+f"(c[0]), "+f"(c[1]), "+f"(c[2]), "+f"(c[3]) : "r"(a0), "r"(a1), "r"(a2), "r"(a3), "r"(b0), "r"(b1));
}
__device__ __forceinline__ void mma16816z(float (&c)[4], const uint4& a, uint32_t b0, uint32_t b1) {
  asm("mma.sync.aligned.m16n8k16.row.col.f32.bf16.bf16.f32 {%0,%1,%2,%3}, {%4,%5,%6,%7}, {%8,%9}, {%10,%10,%10,%10};"
      : "=f"(c[0]), "=f"(c[1]), "=f"(c[2]), "=f"(c[3]) : "r"(a.x), "r"(a.y), "r"(a.z), "r"(a.w), "r"(b0), "r"(b1), "f"(0.f));
}
__device__ __forceinline__ float ex2f(float x) { float r; asm("ex2.approx.ftz.f32 %0, %1;" : "=f"(r) : "f"(x)); return r; }
__device__ __forceinline__ float tanhf_(float x) { float r; asm("tanh.approx.f32 %0, %1;" : "=f"(r) : "f"(x)); return r; }
__device__ __forceinline__ float rsqf(float x) { float r; asm("rsqrt.approx.ftz.f32 %0, %1;" : "=f"(r) : "f"(x)); return r; }
__device__ __forceinline__ float lg2f(float x) { float r; asm("lg2.approx.ftz.f32 %0, %1;" : "=f"(r) : "f"(x)); return r; }
__device__ __forceinline__ float rcpf(float x) { float r; asm("rcp.approx.ftz.f32 %0, %1;" : "=f"(r) : "f"(x)); return r; }
struct PhiC { float x, y; uint32_t z, s, w; };
__device__ __forceinline__ uint32_t phi2(float a, float b, const PhiC& c) {
  uint32_t r;
  asm("{\n.reg .b32 e, u;\ncvt.rn.bf16x2.f32 e, %2, %1;\ncvt.rn.relu.bf16x2.f32 u, %4, %3;\nfma.rn.bf16x2 u, u, %5, %6;\n"
      "min.bf16x2 u, u, e;\nadd.rn.bf16x2 %0, u, %7;\n}"
      : "=r"(r) : "f"(ex2f(fmaf(a, c.x, c.y))), "f"(ex2f(fmaf(b, c.x, c.y))), "f"(a), "f"(b), "r"(c.z), "r"(c.s), "r"(c.w));
  return r;
}
__host__ __device__ constexpr long long koff(int i, int u) { return i < 3 ? 2 * i * u : i == 3 ? 6 * u + ((6ll * u) << 32) : (2 * i - 1) * u; }
__device__ __forceinline__ float shx(float v, int m) { return __shfl_xor_sync(0xffffffffu, v, m); }
template <int V> struct IC { __host__ __device__ constexpr operator int() const { return V; } };
template <class F, int... I> __device__ __forceinline__ void sfor_impl(F&& f, std::integer_sequence<int, I...>) {
  (f(IC<I>{}), ...);
}
template <int N, class F> __device__ __forceinline__ void sfor(F&& f) { sfor_impl(f, std::make_integer_sequence<int, N>{}); }

template <long long OFF, int RO = 0, int N>
__device__ __forceinline__ void wgmma_rs_n56(float (&d)[N], const uint4& a, uint64_t base, int scale_d) {
  asm volatile("{\n.reg .pred p;\n.reg .b64 t;\nsetp.ne.b32 p, %33, 0;\nadd.s64 t, %32, %34;\n"
    "wgmma.mma_async.sync.aligned.m64n56k16.f32.bf16.bf16 {%0, %1, %2, %3, %4, %5, %6, %7, %8, %9, %10, %11, %12, %13, %14, %15, %16, %17, %18, %19, %20, %21, %22, %23, %24, %25, %26, %27}, {%28, %29, %30, %31}, t, p, 1, 1, 1;\n}\n"
    : "+f"(d[RO + 0]), "+f"(d[RO + 1]), "+f"(d[RO + 2]), "+f"(d[RO + 3]), "+f"(d[RO + 4]), "+f"(d[RO + 5]), "+f"(d[RO + 6]), "+f"(d[RO + 7]), "+f"(d[RO + 8]), "+f"(d[RO + 9]), "+f"(d[RO + 10]), "+f"(d[RO + 11]), "+f"(d[RO + 12]), "+f"(d[RO + 13]), "+f"(d[RO + 14]), "+f"(d[RO + 15]), "+f"(d[RO + 16]), "+f"(d[RO + 17]), "+f"(d[RO + 18]), "+f"(d[RO + 19]), "+f"(d[RO + 20]), "+f"(d[RO + 21]), "+f"(d[RO + 22]), "+f"(d[RO + 23]), "+f"(d[RO + 24]), "+f"(d[RO + 25]), "+f"(d[RO + 26]), "+f"(d[RO + 27])
    : "r"(a.x), "r"(a.y), "r"(a.z), "r"(a.w), "l"(base), "r"(scale_d), "n"(OFF >> 4));
}
template <long long OFF, int RO = 0, int N>
__device__ __forceinline__ void wgmma_rs_n64(float (&d)[N], const uint4& a, uint64_t base, int scale_d) {
  asm volatile("{\n.reg .pred p;\n.reg .b64 t;\nsetp.ne.b32 p, %37, 0;\nadd.s64 t, %36, %38;\n"
    "wgmma.mma_async.sync.aligned.m64n64k16.f32.bf16.bf16 {%0, %1, %2, %3, %4, %5, %6, %7, %8, %9, %10, %11, %12, %13, %14, %15, %16, %17, %18, %19, %20, %21, %22, %23, %24, %25, %26, %27, %28, %29, %30, %31}, {%32, %33, %34, %35}, t, p, 1, 1, 1;\n}\n"
    : "+f"(d[RO + 0]), "+f"(d[RO + 1]), "+f"(d[RO + 2]), "+f"(d[RO + 3]), "+f"(d[RO + 4]), "+f"(d[RO + 5]), "+f"(d[RO + 6]), "+f"(d[RO + 7]), "+f"(d[RO + 8]), "+f"(d[RO + 9]), "+f"(d[RO + 10]), "+f"(d[RO + 11]), "+f"(d[RO + 12]), "+f"(d[RO + 13]), "+f"(d[RO + 14]), "+f"(d[RO + 15]), "+f"(d[RO + 16]), "+f"(d[RO + 17]), "+f"(d[RO + 18]), "+f"(d[RO + 19]), "+f"(d[RO + 20]), "+f"(d[RO + 21]), "+f"(d[RO + 22]), "+f"(d[RO + 23]), "+f"(d[RO + 24]), "+f"(d[RO + 25]), "+f"(d[RO + 26]), "+f"(d[RO + 27]), "+f"(d[RO + 28]), "+f"(d[RO + 29]), "+f"(d[RO + 30]), "+f"(d[RO + 31])
    : "r"(a.x), "r"(a.y), "r"(a.z), "r"(a.w), "l"(base), "r"(scale_d), "n"(OFF >> 4));
}
template <long long OFF, int RO = 0, int N>
__device__ __forceinline__ void wgmma_rk_n64(float (&d)[N], const uint4& a, uint64_t base, int scale_d) {
  asm volatile("{\n.reg .pred p;\n.reg .b64 t;\nsetp.ne.b32 p, %37, 0;\nadd.s64 t, %36, %38;\n"
    "wgmma.mma_async.sync.aligned.m64n64k16.f32.bf16.bf16 {%0, %1, %2, %3, %4, %5, %6, %7, %8, %9, %10, %11, %12, %13, %14, %15, %16, %17, %18, %19, %20, %21, %22, %23, %24, %25, %26, %27, %28, %29, %30, %31}, {%32, %33, %34, %35}, t, p, 1, 1, 0;\n}\n"
    : "+f"(d[RO + 0]), "+f"(d[RO + 1]), "+f"(d[RO + 2]), "+f"(d[RO + 3]), "+f"(d[RO + 4]), "+f"(d[RO + 5]), "+f"(d[RO + 6]), "+f"(d[RO + 7]), "+f"(d[RO + 8]), "+f"(d[RO + 9]), "+f"(d[RO + 10]), "+f"(d[RO + 11]), "+f"(d[RO + 12]), "+f"(d[RO + 13]), "+f"(d[RO + 14]), "+f"(d[RO + 15]), "+f"(d[RO + 16]), "+f"(d[RO + 17]), "+f"(d[RO + 18]), "+f"(d[RO + 19]), "+f"(d[RO + 20]), "+f"(d[RO + 21]), "+f"(d[RO + 22]), "+f"(d[RO + 23]), "+f"(d[RO + 24]), "+f"(d[RO + 25]), "+f"(d[RO + 26]), "+f"(d[RO + 27]), "+f"(d[RO + 28]), "+f"(d[RO + 29]), "+f"(d[RO + 30]), "+f"(d[RO + 31])
    : "r"(a.x), "r"(a.y), "r"(a.z), "r"(a.w), "l"(base), "r"(scale_d), "n"(OFF >> 4));
}
template <long long OFF, int RO = 0, int N>
__device__ __forceinline__ void wgmma_rs_n128(float (&d)[N], const uint4& a, uint64_t base, int scale_d) {
  asm volatile("{\n.reg .pred p;\n.reg .b64 t;\nsetp.ne.b32 p, %69, 0;\nadd.s64 t, %68, %70;\n"
    "wgmma.mma_async.sync.aligned.m64n128k16.f32.bf16.bf16 {%0, %1, %2, %3, %4, %5, %6, %7, %8, %9, %10, %11, %12, %13, %14, %15, %16, %17, %18, %19, %20, %21, %22, %23, %24, %25, %26, %27, %28, %29, %30, %31, %32, %33, %34, %35, %36, %37, %38, %39, %40, %41, %42, %43, %44, %45, %46, %47, %48, %49, %50, %51, %52, %53, %54, %55, %56, %57, %58, %59, %60, %61, %62, %63}, {%64, %65, %66, %67}, t, p, 1, 1, 1;\n}\n"
    : "+f"(d[RO + 0]), "+f"(d[RO + 1]), "+f"(d[RO + 2]), "+f"(d[RO + 3]), "+f"(d[RO + 4]), "+f"(d[RO + 5]), "+f"(d[RO + 6]), "+f"(d[RO + 7]), "+f"(d[RO + 8]), "+f"(d[RO + 9]), "+f"(d[RO + 10]), "+f"(d[RO + 11]), "+f"(d[RO + 12]), "+f"(d[RO + 13]), "+f"(d[RO + 14]), "+f"(d[RO + 15]), "+f"(d[RO + 16]), "+f"(d[RO + 17]), "+f"(d[RO + 18]), "+f"(d[RO + 19]), "+f"(d[RO + 20]), "+f"(d[RO + 21]), "+f"(d[RO + 22]), "+f"(d[RO + 23]), "+f"(d[RO + 24]), "+f"(d[RO + 25]), "+f"(d[RO + 26]), "+f"(d[RO + 27]), "+f"(d[RO + 28]), "+f"(d[RO + 29]), "+f"(d[RO + 30]), "+f"(d[RO + 31]), "+f"(d[RO + 32]), "+f"(d[RO + 33]), "+f"(d[RO + 34]), "+f"(d[RO + 35]), "+f"(d[RO + 36]), "+f"(d[RO + 37]), "+f"(d[RO + 38]), "+f"(d[RO + 39]), "+f"(d[RO + 40]), "+f"(d[RO + 41]), "+f"(d[RO + 42]), "+f"(d[RO + 43]), "+f"(d[RO + 44]), "+f"(d[RO + 45]), "+f"(d[RO + 46]), "+f"(d[RO + 47]), "+f"(d[RO + 48]), "+f"(d[RO + 49]), "+f"(d[RO + 50]), "+f"(d[RO + 51]), "+f"(d[RO + 52]), "+f"(d[RO + 53]), "+f"(d[RO + 54]), "+f"(d[RO + 55]), "+f"(d[RO + 56]), "+f"(d[RO + 57]), "+f"(d[RO + 58]), "+f"(d[RO + 59]), "+f"(d[RO + 60]), "+f"(d[RO + 61]), "+f"(d[RO + 62]), "+f"(d[RO + 63])
    : "r"(a.x), "r"(a.y), "r"(a.z), "r"(a.w), "l"(base), "r"(scale_d), "n"(OFF >> 4));
}
template <int OFFA, int OFFB>
__device__ __forceinline__ void wgmma_ss_n64(float (&d)[32], uint64_t basea, uint64_t baseb, int scale_d) {
  asm volatile("{\n.reg .pred p;\n.reg .b64 t, u;\nsetp.ne.b32 p, %34, 0;\nadd.s64 t, %32, %35;\nadd.s64 u, %33, %36;\n"
    "wgmma.mma_async.sync.aligned.m64n64k16.f32.bf16.bf16 {%0, %1, %2, %3, %4, %5, %6, %7, %8, %9, %10, %11, %12, %13, %14, %15, %16, %17, %18, %19, %20, %21, %22, %23, %24, %25, %26, %27, %28, %29, %30, %31}, t, u, p, 1, 1, 1, 1;\n}\n"
    : "+f"(d[0]), "+f"(d[1]), "+f"(d[2]), "+f"(d[3]), "+f"(d[4]), "+f"(d[5]), "+f"(d[6]), "+f"(d[7]), "+f"(d[8]), "+f"(d[9]), "+f"(d[10]), "+f"(d[11]), "+f"(d[12]), "+f"(d[13]), "+f"(d[14]), "+f"(d[15]), "+f"(d[16]), "+f"(d[17]), "+f"(d[18]), "+f"(d[19]), "+f"(d[20]), "+f"(d[21]), "+f"(d[22]), "+f"(d[23]), "+f"(d[24]), "+f"(d[25]), "+f"(d[26]), "+f"(d[27]), "+f"(d[28]), "+f"(d[29]), "+f"(d[30]), "+f"(d[31])
    : "l"(basea), "l"(baseb), "r"(scale_d), "n"(OFFA >> 4), "n"(OFFB >> 4));
}

__device__ __forceinline__ void publish7(char* b16, char* b8, const uint32_t (&P)[14], uint32_t par) {
  st_rlx4(b16, tag(P[0], par), P[1], P[2], P[3]);
  st_rlx4(b16 + 512, tag(P[4], par), P[5], P[6], P[7]);
  st_rlx4(b16 + 1024, tag(P[8], par), P[9], P[10], P[11]);
  st_rlx2(b8, tag(P[12], par), P[13]);
}
template <int GOFF>
__device__ __forceinline__ void fix7(uint4* v, const char* g, uint32_t par, int& budget) {
  asm volatile("{\n.reg .pred p;\n.reg .b32 t, w<4>;\nsetp.eq.s32 p, %28, 0;\nC:\n@!p bra.uni L;\nadd.s32 %28, %28, -1;\n"
               "ld.relaxed.gpu.global.v4.u32 {%0,%1,%2,%3}, [%29+%31+0];\n"
               "ld.relaxed.gpu.global.v4.u32 {%4,%5,%6,%7}, [%29+%31+512];\n"
               "ld.relaxed.gpu.global.v4.u32 {%8,%9,%10,%11}, [%29+%31+1024];\n"
               "ld.relaxed.gpu.global.v4.u32 {%12,%13,%14,%15}, [%29+%31+1536];\n"
               "ld.relaxed.gpu.global.v4.u32 {%16,%17,%18,%19}, [%29+%31+2048];\n"
               "ld.relaxed.gpu.global.v4.u32 {%20,%21,%22,%23}, [%29+%31+2560];\n"
               "ld.relaxed.gpu.global.v4.u32 {%24,%25,%26,%27}, [%29+%31+3072];\n"
               "L:\nlop3.b32 w0, %0, %4, %30, 0x7e;\nlop3.b32 w1, %8, %12, %30, 0x7e;\nlop3.b32 w2, %16, %20, %30, 0x7e;\nxor.b32 w3, %24, %30;\n"
               "lop3.b32 t, w0, w1, w2, 0xfe;\nlop3.b32 t, t, w3, 1, 0xa8;\n"
               "setp.ne.u32 p, t, 0;\nsetp.gt.and.s32 p, %28, 0, p;\nvote.sync.any.pred p, p, 0xffffffff;\n@p bra.uni C;\n}"
               : "+r"(v[0].x), "+r"(v[0].y), "+r"(v[0].z), "+r"(v[0].w), "+r"(v[1].x), "+r"(v[1].y), "+r"(v[1].z), "+r"(v[1].w), "+r"(v[2].x), "+r"(v[2].y), "+r"(v[2].z), "+r"(v[2].w), "+r"(v[3].x), "+r"(v[3].y), "+r"(v[3].z), "+r"(v[3].w), "+r"(v[4].x), "+r"(v[4].y), "+r"(v[4].z), "+r"(v[4].w), "+r"(v[5].x), "+r"(v[5].y), "+r"(v[5].z), "+r"(v[5].w), "+r"(v[6].x), "+r"(v[6].y), "+r"(v[6].z), "+r"(v[6].w), "+r"(budget)
               : "l"(g), "r"(par), "n"(GOFF) : "memory");
}
template <int SOFF>
__device__ __forceinline__ void load7s(uint4* v, uint32_t s, uint32_t s8) {
  asm volatile("ld.shared.v4.u32 {%0,%1,%2,%3}, [%28+%30+0];\n"
               "ld.shared.v4.u32 {%4,%5,%6,%7}, [%28+%30+512];\n"
               "ld.shared.v4.u32 {%8,%9,%10,%11}, [%28+%30+1024];\n"
               "ld.shared.v2.u32 {%12,%13}, [%29+%30+1536];\nld.shared.v2.u32 {%14,%15}, [%29+%30+1792];\n"
               "ld.shared.v4.u32 {%16,%17,%18,%19}, [%28+%30+2048];\n"
               "ld.shared.v4.u32 {%20,%21,%22,%23}, [%28+%30+2560];\n"
               "ld.shared.v4.u32 {%24,%25,%26,%27}, [%28+%30+3072];\n"
               : "=r"(v[0].x), "=r"(v[0].y), "=r"(v[0].z), "=r"(v[0].w), "=r"(v[1].x), "=r"(v[1].y), "=r"(v[1].z), "=r"(v[1].w), "=r"(v[2].x), "=r"(v[2].y), "=r"(v[2].z), "=r"(v[2].w), "=r"(v[3].x), "=r"(v[3].y), "=r"(v[3].z), "=r"(v[3].w), "=r"(v[4].x), "=r"(v[4].y), "=r"(v[4].z), "=r"(v[4].w), "=r"(v[5].x), "=r"(v[5].y), "=r"(v[5].z), "=r"(v[5].w), "=r"(v[6].x), "=r"(v[6].y), "=r"(v[6].z), "=r"(v[6].w)
               : "r"(s), "r"(s8), "n"(SOFF) : "memory");
}
template <int GOFF>
__device__ __forceinline__ void fix7t(uint4* v, const char* base, uint32_t s, uint32_t s8, uint32_t par, int& budget) {
  asm volatile("{\n.reg .pred p;\n.reg .b32 t, w<4>;\n.reg .b64 g, h;\nsetp.eq.s32 p, %28, 0;\nC:\n@!p bra.uni L;\nadd.s32 %28, %28, -1;\n"
               "mad.wide.u32 g, %32, 1, %29;\nmad.wide.u32 h, %33, 1, %29;\n"
               "ld.relaxed.gpu.global.v4.u32 {%0,%1,%2,%3}, [g+%31+0];\n"
               "ld.relaxed.gpu.global.v4.u32 {%4,%5,%6,%7}, [g+%31+512];\n"
               "ld.relaxed.gpu.global.v4.u32 {%8,%9,%10,%11}, [g+%31+1024];\n"
               "ld.relaxed.gpu.global.v2.u32 {%12,%13}, [h+%31+1536];\nld.relaxed.gpu.global.v2.u32 {%14,%15}, [h+%31+1792];\n"
               "ld.relaxed.gpu.global.v4.u32 {%16,%17,%18,%19}, [g+%31+2048];\n"
               "ld.relaxed.gpu.global.v4.u32 {%20,%21,%22,%23}, [g+%31+2560];\n"
               "ld.relaxed.gpu.global.v4.u32 {%24,%25,%26,%27}, [g+%31+3072];\nL:\n"
               "lop3.b32 w0, %0, %4, %30, 0x7e;\nlop3.b32 w1, %8, %12, %30, 0x7e;\nlop3.b32 w2, %14, %16, %30, 0x7e;\nlop3.b32 w3, %20, %24, %30, 0x7e;\n"
               "lop3.b32 t, w0, w1, w2, 0xfe;\nlop3.b32 t, t, w3, 1, 0xa8;\n"
               "setp.ne.u32 p, t, 0;\nsetp.gt.and.s32 p, %28, 0, p;\nvote.sync.any.pred p, p, 0xffffffff;\n@p bra.uni C;\n}"
               : "+r"(v[0].x), "+r"(v[0].y), "+r"(v[0].z), "+r"(v[0].w), "+r"(v[1].x), "+r"(v[1].y), "+r"(v[1].z), "+r"(v[1].w), "+r"(v[2].x), "+r"(v[2].y), "+r"(v[2].z), "+r"(v[2].w), "+r"(v[3].x), "+r"(v[3].y), "+r"(v[3].z), "+r"(v[3].w), "+r"(v[4].x), "+r"(v[4].y), "+r"(v[4].z), "+r"(v[4].w), "+r"(v[5].x), "+r"(v[5].y), "+r"(v[5].z), "+r"(v[5].w), "+r"(v[6].x), "+r"(v[6].y), "+r"(v[6].z), "+r"(v[6].w), "+r"(budget)
               : "l"(base), "r"(par), "n"(GOFF - (int)sb - OFF_G), "r"(s), "r"(s8) : "memory");
}
__device__ __forceinline__ void fixq(uint32_t a, uint32_t s, const char* g, uint32_t par, int& budget) {
  asm volatile("{\n.reg .pred p;\n.reg .b32 t, u, w<28>;\nsetp.eq.s32 p, %0, 0;\n"
               "ld.shared.u32 w0, [%1];\nld.shared.u32 w1, [%1+896];\nld.shared.u32 w2, [%1+1792];\nld.shared.u32 w3, [%1+2688];\n"
               "C:\n@!p bra.uni L;\nadd.s32 %0, %0, -1;\n"
               "ld.relaxed.gpu.global.v4.u32 {w0,w1,w2,w3}, [%3+0];\n"
               "ld.relaxed.gpu.global.v4.u32 {w4,w5,w6,w7}, [%3+512];\n"
               "ld.relaxed.gpu.global.v4.u32 {w8,w9,w10,w11}, [%3+1024];\n"
               "ld.relaxed.gpu.global.v4.u32 {w12,w13,w14,w15}, [%3+1536];\n"
               "ld.relaxed.gpu.global.v4.u32 {w16,w17,w18,w19}, [%3+2048];\n"
               "ld.relaxed.gpu.global.v4.u32 {w20,w21,w22,w23}, [%3+2560];\n"
               "ld.relaxed.gpu.global.v4.u32 {w24,w25,w26,w27}, [%3+3072];\n"
               "st.shared.v4.u32 [%2+0], {w0,w1,w2,w3};\n"
               "st.shared.v4.u32 [%2+512], {w4,w5,w6,w7};\n"
               "st.shared.v4.u32 [%2+1024], {w8,w9,w10,w11};\n"
               "st.shared.v4.u32 [%2+1536], {w12,w13,w14,w15};\n"
               "st.shared.v4.u32 [%2+2048], {w16,w17,w18,w19};\n"
               "st.shared.v4.u32 [%2+2560], {w20,w21,w22,w23};\n"
               "st.shared.v4.u32 [%2+3072], {w24,w25,w26,w27};\n"
               "fence.proxy.async.shared::cta;\nbar.warp.sync 0xffffffff;\n"
               "ld.shared.u32 w0, [%1];\nld.shared.u32 w1, [%1+896];\nld.shared.u32 w2, [%1+1792];\nld.shared.u32 w3, [%1+2688];\n"
               "L:\n"
               "lop3.b32 t, w0, w1, %4, 0x7e;\nlop3.b32 u, w2, w3, %4, 0x7e;\nlop3.b32 t, t, u, 1, 0xa8;\n"
               "setp.ne.u32 p, t, 0;\nsetp.gt.and.s32 p, %0, 0, p;\nvote.sync.any.pred p, p, 0xffffffff;\n@p bra.uni C;\n}"
               : "+r"(budget)
               : "r"(a), "r"(s), "l"(g), "r"(par) : "memory");
}
#define SPINS(i)
#define RETRY(i, ...) __VA_ARGS__
#define BAR(i) (sb + SMEM_BAR + 8 * (i))
#define WAIT(b, ph) mbar_wait(b, ph, budget)

struct Pos { uint32_t v[8]; };
template <bool SWAP>
__global__ void __launch_bounds__(384, 1)
fused_block_kernel(char* const buf, const char* __restrict__ wo, const uint64_t d128, const uint64_t d64, const uint64_t d0,
                   const uint64_t dq, const uint64_t d1, const uint64_t dko,
                   const char* __restrict__ wg, const char* __restrict__ wu, const char* __restrict__ wd, const char* __restrict__ wq, char* __restrict__ out,
                   const __grid_constant__ CUtensorMap map_x, const __grid_constant__ CUtensorMap map_qkv,
                   const __grid_constant__ Pos pos, const __grid_constant__ CUtensorMap map_gu,
                   const __grid_constant__ CUtensorMap map_gu32) {
  extern __shared__ __align__(1024) uint8_t smem[];
  const int tid = threadIdx.x, lane = tid & 31;
  const int warp = __shfl_sync(0xffffffffu, tid >> 5, 0);
  const int cta = (blockIdx.x & 56) * 2 + (blockIdx.x & 1) * 8 + (blockIdx.x & 6) + (blockIdx.x >> 6), r = cta >> 3, p = cta & 7;
  const int kh = p & 1;
  const int wcol = 56 * p - 8 * kh;
  int budget = SPIN_LIMIT;
  const uint32_t zero = d0 >> 48;
  STAMP(0);
  if (warp >= 8) {
    {
      const uint32_t c = 0x100000 - (tid < 256 + B_KVB ? 1 : tid < 256 + B_KFREE ? 4 : tid == 256 + B_XFREE ? 12 : 8);
      if (tid < 320) sts2(BAR(tid - 256), c << 1, c << 11);
      fence_async_smem();
      bar_arrive<0, 384>();
      bar_sync<2, 128>();
#pragma unroll
      for (int i = warp - 8; i < warp; i += 4) {
        if (elect()) {
          mbar_expect_tx(BAR(B_XB + i), TILE);
          tma3d(sb + OFF_X + i * TILE, &map_x, 0, 128 * r + 16 * i, 0, BAR(B_XB + i));
        }
      }
      prefetch_map(&map_qkv);
    }
    STAMPP(60);
    asm volatile("setmaxnreg.dec.sync.aligned.u32 56;");
    STAMPP(63);
  }
  int role = warp;
  asm volatile("" : "+r"(role));
  if (role >= 8) {
    STAMPP(59);
    const int w = warp - 8, t = tid - 256;
    STAMPP(61);
    char* const kvr = buf + (A_KVR + p * KVR_B);
    if (t < 34) st_rlx4(kvr + (uint32_t)((r * 34 + t) * 16), 0, 0, 0, (t & 1) || ((r & 3) * 34 + t >> 3) == 8 ? 0xC1800000u : 0u);
    const uint32_t e1 = (ld_rlx1(&g_cnt[C_ROW + r * 32]) >> 5) + 1;
    const int krow = min(cta, 111) * 4 + w;
    const char* wrow = wo + (uint32_t)(krow * (DM * 2) + (lane - (lane >> 3)) * 16);
    uint4 u0 = make_uint4(0, 0, 0, 0), u1 = u0;
    if ((lane & 7) < 7) {
      u0 = ldg4(wrow);
      u1 = ldg4(wrow + 448);
    }
    if (lane < 7) asm volatile("prefetch.global.L2 [%0];" ::"l"(wq + (uint32_t)(krow * (DM * 6) + lane * 128)));
    if (warp == 11) {
#pragma unroll 1
      for (int j = 0; j < 8; j++) {
        if (elect()) {
          mbar_expect_tx(BAR(B_K + j), TILE);
          tma2d(sb + (j ^ 4) * TILE, &map_qkv, wcol + DM + DM * (j >> 2), 112 * (j & 3), BAR(B_K + j));
        }
      }
    }
    GTIME(0);
    STAMPP(62);
    {
      float c[4];
      mma16816z(c, u0, 0x3F803F80u, 0x3F803F80u);
      mma16816(c, u1.x, u1.y, u1.z, u1.w, 0x3F803F80u, 0x3F803F80u);
      float s = c[0] + c[2];
      s += shx(s, 4); s += shx(s, 8); s += shx(s, 16);
      const uint32_t nw = pack2(s * (1.f / DM), s * (1.f / DM));
      char* const wc = buf + (A_WOC + krow * 128) + (uint32_t)((lane >> 3) * 2 * STG + (((lane ^ krow) & 7) << 4));
      st_rlx4(wc, tag(sub2(u0.x, nw), e1), tag(sub2(u0.y, nw), e1), tag(sub2(u0.z, nw), e1), tag(sub2(u0.w, nw), e1));
      st_rlx4(wc + 8 * STG, tag(sub2(u1.x, nw), e1), tag(sub2(u1.y, nw), e1), tag(sub2(u1.z, nw), e1), tag(sub2(u1.w, nw), e1));
    }
    if (smem_u32(smem) != sb) __trap();
    STAMPP(19);
    uint4 xs[8];
    {
      const uint32_t G = 7 * p + (lane & 7), a = sb + OFF_X + w * TILE + (G >> 3) * 2048 + (lane >> 3) * 128 + (((G ^ lane >> 3) & 7) << 4), b = a ^ 64;
#pragma unroll
      for (int i = 0; i < 8; i++) {
        if (i % 4 == 0) WAIT(BAR(B_XB + w + (i & 4)), 0);
        xs[i] = lds4((i & 1 ? b : a) + (i & 4) * TILE + (i & 3) * 512);
      }
    }
    if (lane == 0) mbar_arrive(BAR(B_XFREE) + (xs[7].x & zero));
    WAIT(BAR(B_XFREE), 0);
    if (w == 0 && elect()) {
      mbar_expect_tx(BAR(B_Q), 2 * STG);
#pragma unroll 1
      for (int j = 0; j < 4; j++) tma2d(sb + OFF_Q + j * TILE, &map_qkv, wcol, 112 * j, BAR(B_Q));
    }
#pragma unroll
    for (int i = 0; i < 4; i++) sts4(sb + OFF_KVB + 2048 * i + t * 16, 0, 0, 0, 0);
    if ((lane & 7) < 7) {
      const uint32_t a = sb + OFF_XS + w * 2048 + (lane >> 3) * 128 + (((lane ^ lane >> 3) & 7) << 4), b = a ^ 64;
#pragma unroll
      for (int i = 0; i < 8; i++) sts4((i & 1 ? b : a) + (i & 4) * 2048 + (i & 3) * 512, xs[i].x, xs[i].y, xs[i].z, xs[i].w);
    }
    const char* const kvt = kvr + (uint32_t)(w * 2176 + (lane & 28) * 16 + (t & 1) * 32 + (t & 2) * 8);
    const char* const kvz = kvr + (uint32_t)(w * 2176 + 1024 + (lane & 28) * 4);
    const char* const kvh = kvt + (uint32_t)(1152 + (lane & 28) * 16);
    {
      uint32_t c[3];
      bool first = w == 0;
#pragma unroll 1
      do {
#pragma unroll
        for (int i = 0; i < 2; i++) c[i] = ld_rlx1(kvr + (uint32_t)(t * 32) + 4096 * i + 28);
        c[2] = ld_rlx1(kvr + (uint32_t)((t & 15) * 32) + 8192 + 28);
        if (first) {
          WAIT(BAR(B_KFREE), 0);
          STAMPX(6);
          if (elect()) {
            mbar_expect_tx(BAR(B_WO), 2 * STG);
            bulk_g2s(sb + OFF_WO, buf + (A_WOC + p * 2 * STG), 2 * STG, BAR(B_WO));
          }
        }
        first = false;
      } while (stale(~(c[0] & c[1] & c[2]), budget, 0x80000000u));
    }
    if (lane == 0) mbar_arrive(BAR(B_INIT));
    STAMPP(1);
    if (w == 2 && elect()) {
      prefetch_map(&map_gu);
      l2_prefetch(wg + cta * 12544, 12544);
      l2_prefetch(wu + cta * 12544, 12544);
      l2_prefetch(wd + cta * 12544, 12544);
      prefetch_map(&map_gu32);
    }
    WAIT(BAR(B_VFREE), 0);
    bar_sync<2, 128>();
    const int gq = lane >> 2, tq = lane & 3, k = 28 * (w >> 1) + 16 * (w & 1) + gq;
    const uint32_t row = sb + OFF_KVB + k * 128, sw = (k & 7) << 4;
    uint32_t ad[4];
    {
      const uint32_t t4 = pos.v[(w & 2) * 2 + tq] ^ (sw | row & 128) * 0x01010101u;
#pragma unroll
      for (int q = 0; q < 4; q++) {
        ad[q] = __byte_perm(row, t4, 0x3214 + q);
        asm volatile("" : "+r"(ad[q]));
      }
    }
    const bool lo = !(w & 1) || gq < 4;
    uint32_t m1 = tq & 2 ? ~0u : 0, m2 = lo ? m1 : 0;
    asm volatile("" : "+r"(m1), "+r"(m2));
    eq_wait(kvr + w * 2176 + 1152 + 28, 0xC0800000, budget);
    STAMPX(2);
    {
      uint4 v[5];
#pragma unroll 1
      do {
#pragma unroll
        for (int i = 0; i < 4; i++) v[i] = ld_rlx4(i < 2 ? kvt + 512 * i : kvh + 64 * i - 128);
        v[4] = ld_rlx4(kvz);
      } while (stale(or3((v[0].w | v[1].w) & m1, (v[2].w | v[3].w) & m2, v[4].w), budget, ~0u));
      STAMPX(3);
#define F(x) __uint_as_float(x)
      const uint32_t a[4] = {pack2(F(v[0].x), F(v[0].y)), pack2(F(v[0].z), F(m1 ? v[1].z : v[0].w)), pack2(F(v[1].x), F(v[1].y)), pack2(F(v[1].z), F(v[1].w))};
      const uint32_t b[4] = {pack2(F(v[2].x), F(v[2].y)), pack2(F(v[2].z), F(m1 ? v[3].z : v[2].w)), pack2(F(v[3].x), F(v[3].y)), pack2(F(v[3].z), F(v[3].w))};
#pragma unroll
      for (int q = 0; q < 4; q++) {
        if (q < 3 || tq < 2) {
          sts1(ad[q], a[q]);
          if (lo) sts1(ad[q] + 1024, b[q]);
        }
      }
      if (tq == 2) {
        const uint32_t z = pack2(F(v[4].x), F(v[4].y));
        const uint32_t za = __byte_perm(z, 0, w & 2 ? 0x1044 : 0x4410), zb = __byte_perm(z, 0, w & 2 ? 0x3244 : 0x4432);
        sts4(row + (112 ^ sw), za, za, za, za);
        if (lo) sts4(row + 1024 + (112 ^ sw), zb, zb, zb, zb);
      }
      fence_async_smem();
      __syncwarp();
      if (lane == 0) mbar_arrive(BAR(B_KVB));
      STAMPP(4);
    }
    if (w == 0) {
#pragma unroll 1
      for (int u = 0; u < 22; u++) {
        const int s = u < 14 ? u & 7 : u < 20 ? u - 14 : u - 20;
        if (u == 2 || u == 14) WAIT(BAR(u == 2 ? B_WB + 3 : B_WDOK), 0);
        WAIT(BAR(B_KFREE + s) + (u >= 8 ? 64 : 0), u >= 14 && u < 20);
        STAMPP(20 + u);
        if (elect()) {
          mbar_expect_tx(BAR(B_FULL + s), u < 14 ? STG : WDS);
          if (u < 12) tma3d(sb + s * STG, &map_gu, 224 * p + 32 * kh + 64 * (u >> 2), 112 * (u & 3), 0, BAR(B_FULL + s));
          else if (u < 14) tma3d(sb + s * STG, &map_gu32, 224 * p + 192 - 192 * kh, 224 * (u - 12), 0, BAR(B_FULL + s));
          else bulk_g2s(sb + s * STG, buf + (A_WD + (p * 8 + u - 14) * WDS), WDS, BAR(B_FULL + s));
        }
      }
      SPINS(26);
    } else {
#pragma unroll 1
      for (int j = 0; j < (w == 1 ? 4 : 0); j++) {
        WAIT(BAR(j < 2 ? B_QFREE + 2 * j : B_ORD - 2 + j), 0);
        const char* src = buf + (uint32_t)(A_O + (j >> 1) * FRAG_B + (r * 2 + (j & 1)) * 2 * STG);
        uint32_t dst = sb + OFF_G + (j & 1) * 2 * STG, full = BAR(B_WB + 4 * (j & 1));
        if (lane < 4) mbar_expect_tx(full + 8 * lane, TILE);
        asm volatile("" : "+l"(src), "+r"(dst), "+r"(full));
        cnt_wait(&g_cnt[C_ROW + r * 32 + j], e1 * 32, budget);
        STAMPX(50 + 2 * j);
#pragma unroll 1
        do {
          if (elect()) bulk_g2s(dst, src, TILE, full);
          dst += TILE;
          src += TILE;
          full += 8;
        } while ((full - BAR(B_WB)) & 24);
        if (j == 2) bar_arrive<6, 160>();
        STAMPP(51 + 2 * j);
      }
      if (w == 1) { SPINS(27); return; }
      const int g = w - 2;
      WAIT(BAR(B_HFREE), 0);
      {
        const int t = tid < 376 ? tid - 256 : tid - 264;
        const int src = p ^ (r >> 2 & 1), part = (r & 1) + (~(r ^ r >> 1) & 2);
        char* zp = buf + (uint32_t)(A_WD + (p * 16 + r) * (WDS / 2) + t * 16 - 1024);
#pragma unroll 1
        for (int x = 1 + (r >> 2 & 2);; x++, zp += 896) {
          const char* wp = wd + (uint32_t)((224 * src + 32 * (src & 1) + 56 * part + (t & 7)) * 896 + (p ^ 2 * x & 7) * 112 + (t & 56) * 2);
          uint4 z[7];
#pragma unroll
          for (int i = 0; i < 7; i++) {
            if (i == 3 && part + (src & 1) == 4) wp -= 224 * 896;
            z[i] = ldg4(wp + i * 8 * 896);
          }
#pragma unroll
          for (int i = 0; i < 7; i++) st_rlx4(zp + i * 1792, z[i].x, z[i].y, z[i].z, z[i].w);
          if (!(x & 1)) break;
        }
      }
      STAMPP(5);
      asm volatile("fence.proxy.async.global;" ::: "memory");
      __syncwarp();
      if (lane == 0) red_release(&g_cnt[C_WD + p * 32]);
      STAMPP(7);
      cnt_wait<true>(&g_cnt[C_WD + p * 32], e1 * 32, budget);
      STAMPP(18);
      asm volatile("fence.proxy.async.global;" ::: "memory");
      if (lane < 2) mbar_arrive(BAR(B_WDOK));
#pragma unroll 1
      for (int j = 0; j < 4; j += j + 1) {
        const uint32_t bar = BAR(B_WB + 4 * g + j);
        const char* src = buf + (j < 3 ? A_HH + (cta ^ j) * 2 * STG + g * TILE : A_PS + (cta * 6 + 3 * g) * 7168);
        if (j != 1) cnt_wait(&g_cnt[(j < 3 ? C_ROW + r * 32 + 4 + 2 * (p & 6) : C_PS + cta * 8) + g], e1 * 8, budget);
        WAIT(j >= 2 ? BAR(B_HFREE + 2 * g + 1) : BAR(B_EMPTY + 6 + g), j >> 1);
        if (elect()) {
          mbar_expect_tx(bar, TILE);
          bulk_g2s(sb + (6 + g) * STG + (j & 1) * TILE, src, TILE, bar);
        }
      }
      SPINS(28 + g);
      if (g && lane == 0) DUMP(2);
    }
  } else {
    STAMP(60);
    bar_sync<0, 384>();
    STAMP(63);
    asm volatile("setmaxnreg.inc.sync.aligned.u32 224;");
    STAMP(61);
    const int g = warp >> 2, gq = lane >> 2, tq = lane & 3;
    const uint64_t dk = d128 + kh;
    uint4 A[28];
    float rs0, rs1, m0, m1;
    float acc0[28], acc1[28];
    uint32_t mb0, mb1;
    {
      uint32_t la[4];
#pragma unroll
      for (int i = 0; i < 4; i++) {
        la[i] = sb + OFF_X + warp * TILE + (lane & 15) * 128 + (((2 * i + (lane >> 4)) ^ (lane & 7)) << 4);
        asm volatile("" : "+r"(la[i]));
      }
      STAMP(62);
      WAIT(BAR(B_XB + warp), 0);
      STAMP(1);
#pragma unroll
      for (int ks = 0; ks < 28; ks++) A[ks] = ldsm4(la[ks & 3] + (ks >> 2) * 2048);
      float cs[4][4] = {};
#pragma unroll
      for (int ks = 0; ks < 28; ks++) mma16816(cs[ks & 3], A[ks].x, A[ks].y, A[ks].z, A[ks].w, 0x3F803F80u, 0x3F803F80u);
      m0 = ((cs[0][0] + cs[1][0]) + (cs[2][0] + cs[3][0])) * (1.f / DM);
      m1 = ((cs[0][2] + cs[1][2]) + (cs[2][2] + cs[3][2])) * (1.f / DM);
      mb0 = pack2(m0, m0); mb1 = pack2(m1, m1);
      if (lane == 0) mbar_arrive(BAR(B_XFREE) + (mb0 & zero));
    }
    STAMP(2);
    uint32_t pa[7];
    {
      const uint32_t prow = sb + OFF_PK + warp * 4096 + gq * 128 + (gq << 4), t = tq >> 1;
      const uint32_t b2 = (prow + ((4 * tq + 8) & 15)) ^ (t << 4);
      pa[0] = prow + 4 * tq; pa[1] = pa[0] ^ 16; pa[2] = pa[0] ^ 32;
      pa[3] = (prow + 4 * (tq & 1)) ^ (48 + 16 * t);
      pa[4] = b2 ^ 64; pa[5] = b2 ^ 80 ^ (t << 5); pa[6] = b2 ^ 96;
#pragma unroll
      for (int j = 0; j < 7; j++) asm volatile("" : "+r"(pa[j]));
    }
    auto sqs = [&](int q) {
      uint4 s;
#pragma unroll
      for (int ks = 7 * q; ks < 7 * q + 7; ks++) {
        if (ks % 7 == 0) s = make_uint4(sq2(A[ks].x), sq2(A[ks].y), sq2(A[ks].z), sq2(A[ks].w));
        else s = make_uint4(sq2(A[ks].x, s.x), sq2(A[ks].y, s.y), sq2(A[ks].z, s.z), sq2(A[ks].w, s.w));
      }
      s.x = add2(s.x, s.z);
      s.y = add2(s.y, s.w);
      rs0 = (q ? rs0 : 0.f) + (bf_lo(s.x) + bf_hi(s.x));
      rs1 = (q ? rs1 : 0.f) + (bf_lo(s.y) + bf_hi(s.y));
      if (q == 3) {
        rs0 += shx(rs0, 1); rs1 += shx(rs1, 1);
        rs0 += shx(rs0, 2); rs1 += shx(rs1, 2);
      }
      asm volatile("" : "+f"(rs0), "+f"(rs1));
    };
    auto sub = [&](int q) {
#pragma unroll
      for (int ks = 7 * q; ks < 7 * q + 7; ks++)
        A[ks] = make_uint4(sub2(A[ks].x, mb0), sub2(A[ks].y, mb1), sub2(A[ks].z, mb0), sub2(A[ks].w, mb1));
    };
    uint32_t sdw, mw;
    PhiC c0, c1;
    auto stats = [&] {
      const float d0 = m0 - bf_lo(mb0), d1 = m1 - bf_lo(mb1);
      const float q0 = fmaxf(rs0 * (1.f / DM) - d0 * d0, 0.f) + 1e-5f;
      const float q1 = fmaxf(rs1 * (1.f / DM) - d1 * d1, 0.f) + 1e-5f;
      rs0 = rsqf(q0);
      rs1 = rsqf(q1);
      const float sd = (tq & 2 ? q1 * rs1 : q0 * rs0);
      sdw = pack2(sd, sd - bf_lo(pack2(sd, 0.f)));
      mw = pack2(tq ? m1 : m0, tq ? d1 : d0);
      c0 = {rs0 * 1.4426950408889634f, lg2f(rs0), pack2(rs0 * rs0, rs0 * rs0), pack2(rs0, rs0), pack2(1e-6f * rs0, 1e-6f * rs0)};
      c1 = {rs1 * 1.4426950408889634f, lg2f(rs1), pack2(rs1 * rs1, rs1 * rs1), pack2(rs1, rs1), pack2(1e-6f * rs1, 1e-6f * rs1)};
      asm volatile("" : "+r"(sdw), "+r"(mw), "+f"(c0.x), "+f"(c0.y), "+r"(c0.z), "+r"(c0.s), "+r"(c0.w), "+f"(c1.x), "+f"(c1.y), "+r"(c1.z), "+r"(c1.s), "+r"(c1.w));
    };
    auto alu = [&](auto S) {
      sfor<4>([&](auto Q) { if (0x843 >> 4 * S + Q & 1) sub(Q); });
      if (S < 4) sqs(S);
      if (S == 3) stats();
    };
    alu(IC<0>{});
    sfor<4>([&](auto J) {
      constexpr int j = J;
      WAIT(BAR(B_K + j), 0);
      STAMP(26 + j);
      if (j == 0 && g) bar_sync<7, 256>();
      wg_fence();
      sfor<7>([&](auto I) { wgmma_rs_n56<2 * STG + (7 * j + I) * 2048>(acc0, A[7 * j + I], dk, j + I != 0); });
      if (j == 0 && !g) bar_arrive<7, 256>();
      if (j == 3) wg_commit();
      alu(IC<j + 1>{});
    });
    STAMP(3);
    WAIT(BAR(B_V), 0);
    STAMP(10);
    wg_fence();
    sfor<7>([&](auto I) { wgmma_rs_n56<I * 2048>(acc1, A[I], dk, I != 0); });
    wg_commit();
    WAIT(BAR(B_XFREE), 0);
    wg_wait<1>();
    acc_fence(acc0);
    STAMP(4);
    if (lane == 0) mbar_arrive(BAR(B_KFREE));
    sfor<7>([&](auto J) {
      constexpr int j = J;
      sfor<3>([&](auto I) {
        constexpr int ks = 7 + 3 * j + I;
        if (ks % 7 == 0) { WAIT(BAR(B_V + ks / 7), 0); wg_fence(); }
        wgmma_rs_n56<ks * 2048>(acc1, A[ks], dk, 1);
      });
      sts1(pa[j], phi2(acc0[4 * j], acc0[4 * j + 1], c0));
      sts1(pa[j] + 1024, phi2(acc0[4 * j + 2], acc0[4 * j + 3], c1));
    });
    wg_commit();
    sts1(((pa[0] & ~15u) ^ (48 + 64 * (tq & 1))) + 2048 + 8 + ((tq >> 1) << 10), sdw);
    if (tq < 2) sts4(sb + OFF_XS + 112 + warp * 2048 + tq * 1024 + gq * 112, mw, 0, 0, 0);
    wg_wait<0>();
    acc_fence(acc1);
    STAMP(5);
    STAMP(54);
#pragma unroll
    for (int j = 0; j < 7; j++) {
      sts1(pa[j] + 2048, pack2(acc1[4 * j], acc1[4 * j + 1]));
      sts1(pa[j] + 3072, pack2(acc1[4 * j + 2], acc1[4 * j + 3]));
    }
    fence_async_smem();
    if (lane == 0) mbar_arrive(BAR(B_VFREE));
    if (g == 0) {
      bar_arrive<1, 256>();
      bar_sync<3, 256>();
    } else {
      bar_sync<1, 256>();
      STAMP(55);
      float kv[32];
      wg_fence();
      sfor<8>([&](auto I) {
        constexpr int o = OFF_PK + I * 4096;
        wgmma_ss_n64<o, o + 2048>(kv, d128, d128, I != 0);
      });
      wg_commit();
      bar_arrive<3, 256>();
      WAIT(BAR(B_INIT), 0);
      char* da = buf + (A_KVR + p * KVR_B + (warp & 3) * 2176) + (uint32_t)(gq * 64 + (tq & 1) * 32 + (tq & 2) * 8);
      char *db = da + (uint32_t)(1152 + gq * 64), *dz = da + (uint32_t)(1008 - gq * 48);
      asm volatile("" : "+l"(da), "+l"(db), "+l"(dz));
      wg_wait<0>();
      acc_fence(kv);
      STAMP(56);
      auto put = [&](const float* v, int n) {
        const int b = n & 2;
        if (!b || (tid & 48) != 48) {
          if (n & 1) red_add4(b ? db + 64 : da + 512, v[b + 8], v[b + 9], tq & 2 ? v[b + 5] : v[b + 12], tq & 2 ? 1.f : v[b + 13]);
          else red_add4(b ? db : da, v[b], v[b + 1], v[b + 4], tq & 2 ? 1.f : v[b + 5]);
        }
      };
#pragma unroll
      for (int i = 0; i < 16; i++) kv[i] = warp & 2 ? kv[16 + i] : kv[i];
#pragma unroll
      for (int n = 0; n < 4; n++) put(kv, n);
      if (tq == 2) red_add4(dz, kv[12] + kv[13], kv[14] + kv[15], 0.f, 1.f);
    }
    STAMP(6);
    const uint32_t par = ~ld_rlx1(&g_cnt[C_ROW + r * 32 + (tid >> 7)]) >> 5;
    WAIT(BAR(B_Q), 0);
    wg_fence();
    sfor<28>([&](auto I) { wgmma_rs_n56<I * 2048>(acc0, A[I], dq + kh, I != 0); });
    wg_commit();
    const uint32_t wb = BAR(B_WB) + 32 * g;
    const int wq4 = warp & 3;
    char* const oblk = buf + (A_O + (r * 2 + g) * 2 * STG);
    const uint32_t gsub = sb + OFF_G + g * 2 * STG + wq4 * 3584 + lane * 16, gsub8 = gsub - lane * 8;
    const char* const olane = oblk + (uint32_t)(wq4 * 3584 + lane * 16);
    char* const ob = oblk + (uint32_t)((p >> 1) * TILE + wq4 * 3584 + kh * 896 + gq * 16);
    char *ob16 = ob + tq * 128, *ob8 = ob + 512 + (tq >> 1) * 128 + (tq & 1) * 8, *ob4 = ob + 768 + tq * 4;
    unsigned* cnt = &g_cnt[C_ROW + r * 32];
    asm volatile("" : "+l"(ob16), "+l"(ob8), "+l"(ob4), "+l"(cnt));
    wg_wait<0>();
    acc_fence(acc0);
    STAMP(7);
    if (lane == 0) mbar_arrive(BAR(B_QFREE));
    uint32_t R[14];
    {
      uint4 Q[4];
#pragma unroll
      for (int j = 0; j < 7; j++) {
        const uint32_t lo = phi2(acc0[4 * j], acc0[4 * j + 1], c0);
        const uint32_t hi = phi2(acc0[4 * j + 2], acc0[4 * j + 3], c1);
        if (j & 1) { Q[j >> 1].z = lo; Q[j >> 1].w = hi; } else { Q[j >> 1].x = lo; Q[j >> 1].y = hi; }
      }
      Q[3].z = 0; Q[3].w = 0;
      STAMP(8);
      WAIT(BAR(B_KVB), 0);
      STAMP(9);
      float o[32];
      wg_fence();
      sfor<4>([&](auto I) { wgmma_rs_n64<OFF_KVB + I * 2048>(o, Q[I], d128, I != 0); });
      wg_commit();
      wg_wait<0>();
      acc_fence(o);
      const float da0 = rcpf(o[28] + bf_lo(c0.w)), db0 = rcpf(o[29] + bf_lo(c0.w)), da1 = rcpf(o[30] + bf_lo(c1.w)), db1 = rcpf(o[31] + bf_lo(c1.w));
      uint32_t P[14];
#pragma unroll
      for (int j = 0; j < 7; j++) {
        const bool first = j < 2 || (j < 4 && tq < 3);
        const float s0 = first ? da0 : db0, s1 = first ? da1 : db1;
        P[2 * j] = pack2(o[4 * j] * s0, o[4 * j + 1] * s0);
        P[2 * j + 1] = pack2(o[4 * j + 2] * s1, o[4 * j + 3] * s1);
        if (0x53 >> j & 1) { P[2 * j] = tag(P[2 * j], par); P[2 * j + 1] = tag(P[2 * j + 1], par); }
      }
      auto publish = [&] {
#pragma unroll
        for (int h = 0; h < 2; h++) {
          st_rlx4(ob16 + 1792 * h, P[h], P[2 + h], P[4 + h], P[6 + h]);
          st_rlx2(ob8 + 1792 * h, P[8 + h], P[10 + h]);
          st_rlx1(ob4 + 1792 * h, P[12 + h]);
        }
      };
      if (!g) {
        red_inc(cnt, lane);
        publish();
        STAMP(11);
        if (lane == 0) mbar_arrive(BAR(B_OFREE));
        const int sec = min(lane, 27);
        uint32_t ta = sb + OFF_WO + wq4 * 3584 + sec * 32 + (0x3625410 >> (sec & 28) & 7) * 4;
        uint32_t gs = gsub - 2 * STG;
        const char* ol = olane + (A_WOC - A_O + (p - 2 * r) * 2 * STG);
        asm volatile("" : "+r"(ta), "+l"(ol));
#pragma unroll 1
        for (int n = 0; n < 12; n++) {
          WAIT(n < 4 ? BAR(B_WO) : BAR(B_WB - 4) + 8 * n, 0);
          STAMPD(max(n - 3, 1));
          RETRY(n < 4 ? 30 : n - 4, fixq(ta, gs, ol, par, budget));
          bar_arrive_id(4 + n);
          ol = n == 3 ? olane : ol + TILE;
          ta += TILE;
          gs += TILE;
        }
        bar_sync<3, 256>();
      } else {
        const uint32_t wa = sb + (lane >> 4) * 1024 + (lane & 7) * 128 + ((((2 * wq4 + (lane >> 3 & 1)) ^ lane) & 7) << 4);
        float hacc[64];
        {
          const uint32_t one = 0x3F80u << (lane * 4 & 16), m = tq == 0 ? 0xBF80BF80u : 0, id = (tid >> 3 ^ tq) & 15;
          uint4 E[4];
#pragma unroll
          for (int i = 0; i < 4; i++) {
            const uint32_t e = id == 4 * i ? one : 0;
            E[i] = make_uint4(e, 0, i < 3 ? 0 : m, i < 3 ? e : m);
            asm volatile("" : "+r"(E[i].x), "+r"(E[i].y), "+r"(E[i].z), "+r"(E[i].w));
          }
          wg_fence();
          sfor<8>([&](auto I) { wgmma_rk_n64<OFF_XS + I / 4 * 8192 + I % 4 * 32, I / 4 * 32>(hacc, E[I % 4], d128, I % 4 != 0); });
          wg_commit();
        }
        WAIT(BAR(B_WO), 0);
        sfor<28>([&](auto KS) {
          constexpr int ks = KS;
          if (ks == 1) {
            wg_wait<0>();
            acc_fence(hacc);
            if (lane == 0) mbar_arrive(BAR(B_OFREE));
          }
          if (ks == 24) red_inc(cnt + 1, lane);
          if (ks == 24) {
            WAIT(BAR(B_WO), 0);
            publish();
            STAMP(11);
            WAIT(BAR(B_WO), 0);
          }
          if (ks % 7 == 0) bar_sync<4 + ks / 7, 256>();
          A[ks] = ldsm4t(wa + OFF_WO + ks * 2048);
        });
        if (lane < 2) mbar_arrive(BAR(B_WOFREE) + (A[27].x & zero));
        STAMP(10);
        uint32_t ma = sb + OFF_M + tq * 8;
        char* hb = oblk + (uint32_t)(FRAG_B - 2 * STG + (p >> 1) * TILE + (wq4 < 3 ? kh * 2048 + wq4 * 512 + lane * 16 : 1536 + kh * 256 + lane * 8));
        asm volatile("" : "+l"(hb));
        STAMP(16);
#pragma unroll 1
        for (int h = 0; h < 2; h++) {
          const uint64_t dh = dko + h * (2 * STG >> 4);
          sfor<4>([&](auto Q) {
            constexpr int q = Q;
            bar_sync_id(8 + 4 * h + q);
            STAMPD(1 + 4 * h + q);
            wg_fence();
            sfor<7>([&](auto I) { wgmma_rk_n64<OFF_G + q * TILE + I * 256>(hacc, A[7 * q + I], dh, 1); });
          });
          wg_commit();
          if (h) bar_sync<6, 160>();
          wg_wait<0>();
          red_inc(cnt + 2, lane);
          acc_fence(hacc);
          STAMPD(12 + 2 * h);
          if (lane < 2) mbar_arrive(BAR(B_ORD) + 8 * h);
#pragma unroll
          for (int i = 0; i < 4; i++) {
            const float* a = hacc + 8 * i;
            st_rlx42(hb + 3584 * i, tag(transp(pack2(a[0], a[1])), par), transp(pack2(a[4], a[5])), transp(pack2(a[2], a[3])), transp(pack2(a[6], a[7])), wq4 - 3);
          }
          if (tid >= 224 && gq == 0) {
#pragma unroll
            for (int j = 0; j < 8; j++) sts2(ma + 32 * j, __float_as_uint(hacc[4 * j + 2]), __float_as_uint(hacc[4 * j + 3]));
          }
          STAMPD(13 + 2 * h);
          if (h) break;
          bar_arrive<3, 256>();
#pragma unroll
          for (int i = 0; i < 32; i++) hacc[i] = hacc[32 + i];
          acc_fence(hacc);
          hb += 2 * STG;
          ma += 256;
          cnt++;
        }
        bar_sync<5, 128>();
      }
      const char* const rb = olane + (FRAG_B + (p >> 1) * TILE);
#pragma unroll
      for (int i = 0; i < 3; i++) {
        const uint4 v = ld_rlx4(rb + kh * 2048 + 512 * i);
        R[4 * i] = v.x; R[4 * i + 1] = v.y; R[4 * i + 2] = v.z; R[4 * i + 3] = v.w;
      }
      const uint2 v = ld_rlx2(rb + 1536 + kh * 256 - lane * 8);
      R[12] = v.x; R[13] = v.y;
    }
    char* hdst = buf + (A_HH + cta * 2 * STG + warp * 3584) + (uint32_t)(lane * 16);
    {
#define GLU(gt, up, e) fmaf((up) * (e), tanhf_((gt) * (e)), (up) * (e))
      float acc[64];
      uint4 own[5];
#pragma unroll
      for (int i = 0; i < 5; i++) asm volatile("" : "=r"(own[i].x), "=r"(own[i].y), "=r"(own[i].z), "=r"(own[i].w));
      sfor<2>([&](auto Q) {
        WAIT(wb + 8 * Q, 1);
        STAMP(57 + Q);
        load7s<Q * TILE>(&A[7 * Q], gsub, gsub8);
      });
#pragma unroll 1
      for (int c = 0; c < 3; c++) {
        const uint32_t half = (c & 1) * 4;
        const uint64_t dc = d128 + half * (STG >> 4);
        if (c == 1) WAIT(BAR(B_HFREE + 3), 0);
        sfor<4>([&](auto KQ) {
          constexpr int kq = KQ;
          WAIT(BAR(B_FULL + kq) + 8 * half, c >> 1);
          if (c == 0) {
            RETRY(8 + kq + 4 * g, fix7t<A_H + kq * TILE>(&A[7 * kq], buf + r * 4 * STG, gsub, gsub8, par, budget));
            STAMP(42 + kq);
            if (lane == 0) mbar_arrive(BAR(B_HFREE + kq / 2) + 16 * g);
            if (kq < 2) WAIT(wb + 8 * (kq + 2), 1);
            STAMP(46 + kq);
            if (kq < 2) load7s<(kq + 2) % 4 * TILE>(&A[7 * ((kq + 2) % 4)], gsub, gsub8);
          }
          STAMPD(30 + 4 * c + kq);
          wg_fence();
          sfor<7>([&](auto I) { wgmma_rs_n128<kq * STG + koff(I, 1024)>(acc, A[7 * kq + I], dc, kq + I != 0); });
          wg_commit();
          if (c == 0) STAMP(50 + kq);
          if (c == 0) {
            sqs(kq);
            if (kq == 3) {
              rs0 = 0.5f * rsqf(rs0 * (1.f / DM) + 1e-5f);
              rs1 = 0.5f * rsqf(rs1 * (1.f / DM) + 1e-5f);
              asm volatile("" : "+f"(rs0), "+f"(rs1));
            }
          }
          if (kq > 0) {
            wg_wait<1>();
            if (lane == 0) mbar_arrive(BAR(B_EMPTY + kq - 1) + 8 * half);
          }
        });
        wg_wait<0>();
        acc_fence(acc);
        if (lane == 0) mbar_arrive(BAR(B_EMPTY + 3) + 8 * half);
        STAMPD(17 + c);
        constexpr int GO = SWAP ? 32 : 0, UO = SWAP ? 0 : 32;
        own[0] = own[4];
#pragma unroll
        for (int i = 0; i < 4; i++) {
          uint32_t w[4];
#pragma unroll
          for (int t = 0; t < 2; t++) {
            const int b = 8 * i + 4 * t;
            w[2 * t] = pack2(GLU(acc[GO + b], acc[UO + b], rs0), GLU(acc[GO + b + 1], acc[UO + b + 1], rs0));
            w[2 * t + 1] = pack2(GLU(acc[GO + b + 2], acc[UO + b + 2], rs1), GLU(acc[GO + b + 3], acc[UO + b + 3], rs1));
          }
          if (i == 3 && c == 1) hdst += STG - 3584;
          own[i + 1] = make_uint4(tag(w[0], par), w[1], w[2], w[3]);
          st_rlx4(hdst + i * 512, own[i + 1].x, w[1], w[2], w[3]);
        }
        hdst += 2048;
        red_inc(&g_cnt[C_ROW + r * 32 + 4 + 2 * (p & 6) + g], lane | c ^ 1);
      }
      float acct[32];
      sfor<2>([&](auto H) {
        constexpr int h = H;
        WAIT(BAR(B_FULL + 4 + h), 1);
        wg_fence();
        sfor<14>([&](auto I) { wgmma_rs_n64<(4 + h) * STG + I / 7 * (TILE / 2) + koff(I % 7, 512)>(acct, A[14 * h + I], d64, h + I != 0); });
        wg_commit();
      });
      auto ldh = [&](int k) {
        WAIT(wb + 8 * k, 0);
#pragma unroll
        for (int i = 0; i < 7; i++) A[7 * k + 7 + i] = lds4(gsub - g * STG + 2 * STG + k * TILE + i * 512);
      };
      wg_wait<1>();
      if (lane == 0) mbar_arrive(BAR(B_EMPTY + 4));
      ldh(0);
      wg_wait<0>();
      acc_fence(acct);
      if (lane == 0) mbar_arrive(BAR(B_EMPTY + 5));
      STAMP(20);
      constexpr int GO = SWAP ? 16 : 0, UO = SWAP ? 0 : 16;
#pragma unroll
      for (int i = 0; i < 2; i++) {
        uint32_t w[4];
#pragma unroll
        for (int t = 0; t < 2; t++) {
          const int b = 8 * i + 4 * t;
          w[2 * t] = pack2(GLU(acct[GO + b], acct[UO + b], rs0), GLU(acct[GO + b + 1], acct[UO + b + 1], rs0));
          w[2 * t + 1] = pack2(GLU(acct[GO + b + 2], acct[UO + b + 2], rs1), GLU(acct[GO + b + 3], acct[UO + b + 3], rs1));
        }
        st_rlx4(hdst + i * 512, tag(w[0], par), w[1], w[2], w[3]);
        A[5 + i] = make_uint4(w[0], w[1], w[2], w[3]);
      }
#pragma unroll
      for (int i = 0; i < 5; i++) A[i] = own[i];
    }
    STAMP(21);
    {
      const char* const hnb = hdst + (1 - 2 * kh) * 2 * STG;
      uint32_t eye = tq == gq >> 1 ? 0x3F80u << (16 * (gq & 1)) : 0;
      auto add = [&](float (&a)[28], const uint32_t (&v)[14]) {
#pragma unroll
        for (int j = 0; j < 7; j++)
          asm("mma.sync.aligned.m16n8k8.row.col.f32.bf16.bf16.f32 {%0,%1,%2,%3}, {%4,%5}, {%6}, {%0,%1,%2,%3};"
              : "+f"(a[4 * j]), "+f"(a[4 * j + 1]), "+f"(a[4 * j + 2]), "+f"(a[4 * j + 3]) : "r"(v[2 * j]), "r"(v[2 * j + 1]), "r"(eye));
      };
      auto send = [&](float (&acc)[28], int x) {
        acc_fence(acc);
        char* const pd = buf + (A_PS + ((cta ^ 2 * x) * 6 + 3 * g + x - 1) * 7168 + (warp & 3) * 1792);
        uint32_t P[14];
#pragma unroll
        for (int j = 0; j < 14; j++) P[j] = pack2(acc[2 * j], acc[2 * j + 1]);
        publish7(pd + (uint32_t)(lane * 16), pd + 1536 + (uint32_t)(lane * 8), P, par);
        if (x < 3) red_inc(&g_cnt[C_PS + (cta ^ 2 * x) * 8 + g], lane);
      };
      sfor<4>([&](auto K) {
        constexpr int k = K;
        if (k > 1) {
          wg_wait<1>();
          if (lane == 0) mbar_arrive(BAR(B_EMPTY + k - 2));
        }
        if (k) RETRY(16 + k + 4 * g, fix7<-2560 - (k < 3) * STG>(&A[7 * k], k > 1 ? hnb : hdst, par, budget));
        if (k == 2 && lane < 2) mbar_arrive(BAR(B_HFREE + 1) + 16 * g);
        if (k == 1) {
          WAIT(wb + 8, 0);
#pragma unroll
          for (int i = 0; i < 7; i++) A[14 + i] = lds4(gsub - g * STG + 2 * STG + TILE + i * 512);
        }
        if (k == 2) {
#pragma unroll
          for (int i = 0; i < 7; i++) A[21 + i] = ld_rlx4(hnb - 2560 + 512 * i);
        }
        WAIT(BAR(B_FULL + k), 0);
        wg_fence();
        sfor<7>([&](auto I) { wgmma_rs_n56<k * STG + I * 3584>(acc0, A[7 * k + I], d0, k + I != 0); });
        if (k == 3) wg_commit();
        sfor<7>([&](auto I) { wgmma_rs_n56<k * STG + I * 3584 + 896>(acc1, A[7 * k + I], d0, k + I != 0); });
        wg_commit();
      });
      wg_wait<1>();
      send(acc0, 1);
      sfor<4>([&](auto K) {
        constexpr int k = K, s = (k + 4) % 6;
        WAIT(BAR(B_FULL + s), k >= 2);
        wg_fence();
        sfor<7>([&](auto I) { wgmma_rs_n56<s * STG + I * 3584>(acc0, A[7 * k + I], d1, k + I != 0); });
        wg_commit();
        if (k == 0) {
          wg_wait<1>();
          send(acc1, 2);
          const float m0 = __uint_as_float(lds1(sb + OFF_M + warp * 64 + gq * 4)), m1 = __uint_as_float(lds1(sb + OFF_M + warp * 64 + gq * 4 + 32));
#pragma unroll
          for (int i = 0; i < 28; i++) acc1[i] = i & 2 ? -m1 : -m0;
          acc_fence(acc1);
        }
      });
      if (g) bar_arrive<7, 256>();
      wg_wait<0>();
      STAMP(22);
      send(acc0, 3);
      if (!g) bar_sync<7, 256>();
      uint32_t P[3][14];
      const char* const ps = buf + (A_PS + (cta * 6 + 3 * g) * 7168 + (warp & 3) * 1792) + (uint32_t)(lane * 16);
      const char* const ps8 = ps - lane * 8;
      auto fetch = [&](int x) {
#pragma unroll
        for (int i = 0; i < 3; i++) {
          const uint4 v = ld_rlx4(ps + 7168 * x + 512 * i);
          P[x][4 * i] = v.x; P[x][4 * i + 1] = v.y; P[x][4 * i + 2] = v.z; P[x][4 * i + 3] = v.w;
        }
        const uint2 v = ld_rlx2(ps8 + 7168 * x + 1536);
        P[x][12] = v.x; P[x][13] = v.y;
      };
      const uint32_t pss = sb + (6 + g) * STG + (warp & 3) * 1792;
      auto fetchs = [&] {
        WAIT(wb + 24, 0);
#pragma unroll
        for (int x = 0; x < 2; x++) {
          const uint32_t a = pss + TILE + 7168 * x;
#pragma unroll
          for (int i = 0; i < 3; i++) {
            const uint4 v = lds4(a + 512 * i + lane * 16);
            P[x][4 * i] = v.x; P[x][4 * i + 1] = v.y; P[x][4 * i + 2] = v.z; P[x][4 * i + 3] = v.w;
          }
          const uint2 v = lds2(a + 1536 + lane * 8);
          P[x][12] = v.x; P[x][13] = v.y;
        }
      };
      WAIT(BAR(B_FULL + 5), 0);
      wg_fence();
      sfor<28>([&](auto I) {
        if (I == 21) {
          fetchs();
          fetch(2);
          wg_fence();
        }
        wgmma_rs_n56<(I / 7 + 4) % 6 * STG + I % 7 * 3584 + 896>(acc1, A[I], d1, 1);
      });
      wg_commit();
      STAMP(23);
      WAIT(BAR(B_FULL + 5), 0);
      uint32_t ob = pss + 7168 + (lane & 15) * 112 + (lane & 16);
      char* op = out + (uint32_t)((128 * r + (tid >> 5) * 16 + (lane >> 3)) * 896 + 112 * p + (lane & 7) * 16);
      uint32_t ia = pss + 7168 + (lane >> 3) * 112 + (lane & 7) * 16;
      asm volatile("" : "+r"(ob), "+l"(op), "+r"(ia));
      auto check = [&](int x) {
#pragma unroll 1
        while (stale(xor2(P[x][0], P[x][4], par) | xor2(P[x][8], P[x][12], par), budget)) fetch(x);
      };
      check(0);
      check(1);
      uint32_t o[14];
      {
        wg_wait<0>();
        acc_fence(acc1);
        STAMP(24);
        add(acc1, R);
        add(acc1, P[0]);
        add(acc1, P[1]);
        acc_fence(acc1);
        WAIT(BAR(B_FULL + 5), 0);
        check(2);
        add(acc1, P[2]);
#pragma unroll
        for (int j = 0; j < 14; j++) o[j] = pack2(acc1[2 * j], acc1[2 * j + 1]);
      }
#pragma unroll
      for (int i = 0; i < 3; i++)
        asm volatile("stmatrix.sync.aligned.m8n8.x4.shared.b16 [%0], {%1,%2,%3,%4};" ::"r"(ob + 32 * i), "r"(o[4 * i]), "r"(o[4 * i + 1]), "r"(o[4 * i + 2]), "r"(o[4 * i + 3]) : "memory");
      asm volatile("stmatrix.sync.aligned.m8n8.x2.shared.b16 [%0], {%1,%2};" ::"r"(ob + 96), "r"(o[12]), "r"(o[13]) : "memory");
      __syncwarp();
      {
        uint4 v[4];
#pragma unroll
        for (int i = 0; i < 4; i++) v[i] = lds4(ia + 448 * i);
        if ((lane & 7) < 7) {
#pragma unroll
          for (int i = 0; i < 4; i++) *(uint4*)(op + 3584 * i) = v[i];
        }
      }
      STAMP(25);
      SPINS(24 + g);
      GTIME(1);
    }
  }
}

typedef CUresult (*EncodeFn)(CUtensorMap*, CUtensorMapDataType, cuuint32_t, void*, const cuuint64_t*, const cuuint64_t*,
                             const cuuint32_t*, const cuuint32_t*, CUtensorMapInterleave, CUtensorMapSwizzle,
                             CUtensorMapL2promotion, CUtensorMapFloatOOBfill);

void make_map(EncodeFn enc, CUtensorMap* m, const void* p, int rank, const cuuint64_t* gd, const cuuint64_t* gs,
              const cuuint32_t* bd, CUtensorMapSwizzle sw) {
  const cuuint32_t es[5] = {1, 1, 1, 1, 1};
  ENC_CHECK(enc(m, CU_TENSOR_MAP_DATA_TYPE_BFLOAT16, rank, (void*)p, gd, gs, bd, es, CU_TENSOR_MAP_INTERLEAVE_NONE, sw,
                CU_TENSOR_MAP_L2_PROMOTION_NONE, CU_TENSOR_MAP_FLOAT_OOB_FILL_NONE));
}

}

extern "C" void kernel_launch(void* const* d_in, const int* in_sizes, int n_in, void* d_out, int out_size) {
  (void)in_sizes; (void)n_in; (void)out_size;
  static EncodeFn enc = nullptr;
  static char* buf = nullptr;
  if (!enc) {
    void* fn = nullptr;
    cudaDriverEntryPointQueryResult qr;
    cudaGetDriverEntryPoint("cuTensorMapEncodeTiled", &fn, cudaEnableDefault, &qr);
    enc = (EncodeFn)fn;
    cudaGetSymbolAddress((void**)&buf, g_buf);
    cudaFuncSetAttribute(fused_block_kernel<false>, cudaFuncAttributeMaxDynamicSharedMemorySize, SMEM_TOTAL);
    cudaFuncSetAttribute(fused_block_kernel<true>, cudaFuncAttributeMaxDynamicSharedMemorySize, SMEM_TOTAL);
  }
  const CUtensorMapSwizzle S128 = CU_TENSOR_MAP_SWIZZLE_128B;
  CUtensorMap mx, mqkv, mgu, mgu32;
  {
    cuuint64_t gd[3] = {64, SEQ, 7}, gs[2] = {DM * 2, 128};
    cuuint32_t bd[3] = {64, 16, 7};
    make_map(enc, &mx, d_in[0], 3, gd, gs, bd, S128);
  }
  {
    cuuint64_t gd[2] = {3 * DM, DM}, gs[1] = {3 * DM * 2};
    cuuint32_t bd[2] = {64, 112};
    make_map(enc, &mqkv, d_in[1], 2, gd, gs, bd, S128);
  }
  Pos pos = {};
  for (int i = 0; i < 32; i++) {
    const int c = 28 * (i >> 4) + 2 * (i >> 2 & 3) + 8 * (i & 3);
    pos.v[i >> 2] |= (uint32_t)(2 * (c < 32 ? (c & 6) * 4 + (c >> 3) * 2 : c < 48 ? 32 + (c & 2) * 4 + (c >> 1 & 6) : c)) << 8 * (i & 3);
  }
  const char *wg = (const char*)d_in[4], *wu = (const char*)d_in[5];
  const bool swap = wu < wg;
  const char* gub = swap ? wu : wg;
  const cuuint64_t gud = swap ? (cuuint64_t)(wg - wu) : (cuuint64_t)(wu - wg);
  {
    cuuint64_t gd[3] = {FF, DM, 2}, gs[2] = {FF * 2, gud};
    cuuint32_t bd[3] = {64, 112, 2};
    make_map(enc, &mgu, gub, 3, gd, gs, bd, S128);
  }
  {
    cuuint64_t gd[3] = {FF, DM, 2}, gs[2] = {FF * 2, gud};
    cuuint32_t bd[3] = {32, 224, 2};
    make_map(enc, &mgu32, gub, 3, gd, gs, bd, CU_TENSOR_MAP_SWIZZLE_64B);
  }
  (swap ? fused_block_kernel<true> : fused_block_kernel<false>)<<<128, 384, SMEM_TOTAL>>>(
      buf, (const char*)d_in[2], mn_desc(sb), mn_desc64(sb), mn_desc0(sb), mn_desc(sb + OFF_Q), mn_desc0(sb), k_desc0(sb), wg, wu, (const char*)d_in[6], (const char*)d_in[1], (char*)d_out, mx, mqkv, pos, mgu, mgu32);
}
```
